```python
import torch

def _softmax(x, axis=-1):
    return torch.softmax(x, dim=axis)
def _gelu(x):
    return torch.nn.functional.gelu(x, approximate="tanh")
def _silu(x):
    return torch.nn.functional.silu(x)
def _sigmoid(x):
    return torch.sigmoid(x)
def _layernorm(x, axis=-1, eps=1e-5):
    m = x.mean(dim=axis, keepdim=True)
    v = x.var(dim=axis, keepdim=True, unbiased=False)
    return (x - m) / torch.sqrt(v + eps)
def _scatter_add(tgt, idx, src, axis=0):
    return tgt.clone().index_add_(axis, idx, src)
def _segment_sum(src, seg, n):
    out = torch.zeros((n,) + src.shape[1:], dtype=src.dtype)
    return out.index_add_(0, seg, src)
def _pad(x, pw):
    flat = tuple(v for pair in reversed(pw) for v in pair)
    return torch.nn.functional.pad(x, flat)

kernel_name = 'concat_heads__mha_block_cached__compressed_kv_cla__decode'

def setup_inputs():

    _w = (lambda a: (lambda t: t.to(torch.bfloat16) if t.is_floating_point() else t)(torch.as_tensor(a)))
    def _A_setup():
        B, Sq, D = 4, 1, 576
        H, Sk, Dh = 32, 4096, 128
        return {
            "x": _w((lambda *s: torch.randn(*s, dtype=torch.bfloat16) * 1.6)(B, Sq, D)),
            "k_cache": _w((lambda *s: torch.randn(*s, dtype=torch.bfloat16) * 1.6)(B, H, Sk, Dh)),
            "v_cache": _w((lambda *s: torch.randn(*s, dtype=torch.bfloat16) * 0.05)(B, H, Sk, Dh)),
            "wq": _w((lambda *s: torch.randn(*s, dtype=torch.bfloat16) * 1.6)(D, H * Dh) * (D ** -0.5)),
            "wo": _w((lambda *s: torch.randn(*s, dtype=torch.bfloat16) * 0.05)(H * Dh, D) * ((H * Dh) ** -0.5)),
        }
    _A_in = _A_setup()

    def _B_setup():
        B, H, Sq, Sk, D, M = 4, 32, 1, 4096, 128, 576
        Dc = 4 * D
        return {
            "x": _w((lambda *s: torch.randn(*s, dtype=torch.bfloat16) * 3.2)(B, Sq, M)),
            "c_kv": _w((lambda *s: torch.randn(*s, dtype=torch.bfloat16) * 0.1)(B, Sk, Dc)),
            "w_q": _w((lambda *s: torch.randn(*s, dtype=torch.bfloat16) * 6.4)(M, H, D) * (M ** -0.5)),
            "w_uk": _w((lambda *s: torch.randn(*s, dtype=torch.bfloat16) * 6.4)(Dc, H, D) * (Dc ** -0.5)),
            "w_uv": _w((lambda *s: torch.randn(*s, dtype=torch.bfloat16) * 0.1)(Dc, H, D) * (Dc ** -0.5)),
            "w_o": _w((lambda *s: torch.randn(*s, dtype=torch.bfloat16) * 0.1)(H, D, M) * ((H * D) ** -0.5)),
        }
    _B_in = _B_setup()

    return {
        "A_x": _A_in["x"],
        "A_k_cache": _A_in["k_cache"],
        "A_v_cache": _A_in["v_cache"],
        "A_wq": _A_in["wq"],
        "A_wo": _A_in["wo"],
        "B_x": _B_in["x"],
        "B_c_kv": _B_in["c_kv"],
        "B_w_q": _B_in["w_q"],
        "B_w_uk": _B_in["w_uk"],
        "B_w_uv": _B_in["w_uv"],
        "B_w_o": _B_in["w_o"],
    }

def reference(A_x, A_k_cache, A_v_cache, A_wq, A_wo, B_x, B_c_kv, B_w_q, B_w_uk, B_w_uv, B_w_o):
    def _A_ref(x, k_cache, v_cache, wq, wo):
        B, Sq, D = x.shape
        H, Dh = 32, 128
        q = (lambda x, *d: x.permute(*d))((x @ wq).reshape(B, Sq, H, Dh), 0, 2, 1, 3)
        scores = torch.einsum("bhqd,bhkd->bhqk", q, k_cache) * (Dh ** -0.5)
        p = _softmax(scores, axis=-1)
        o = torch.einsum("bhqk,bhkd->bhqd", p, v_cache)
        return (lambda x, *d: x.permute(*d))(o, 0, 2, 1, 3).reshape(B, Sq, H * Dh) @ wo

    def _B_ref(x, c_kv, w_q, w_uk, w_uv, w_o):
        B, Sq, M = x.shape[0], x.shape[1], x.shape[2]
        Sk = c_kv.shape[1]
        H, D = w_q.shape[1], w_q.shape[2]
        q = torch.einsum("bqm,mhd->bhqd", x, w_q)
        k = torch.einsum("bkc,chd->bhkd", c_kv, w_uk)
        v = torch.einsum("bkc,chd->bhkd", c_kv, w_uv)
        scores = torch.einsum("bhqd,bhkd->bhqk", q, k) * (D ** -0.5)
        off = Sk - Sq
        qi = torch.arange(Sq)[:, None]
        kj = torch.arange(Sk)[None, :]
        cmask = kj <= (qi + off)
        scores = torch.where(cmask[None, None], scores, -1e9)
        p = _softmax(scores, axis=-1)
        ctx = torch.einsum("bhqk,bhkd->bhqd", p, v)
        return torch.einsum("bhqd,hdm->bqm", ctx, w_o)

    a = _A_ref(A_x, A_k_cache, A_v_cache, A_wq, A_wo)
    b = _B_ref(B_x, B_c_kv, B_w_q, B_w_uk, B_w_uv, B_w_o)
    return torch.concatenate([a, b], axis=-1)
```

```cpp
#include <cuda_runtime.h>
#include <cuda.h>
#include <cuda_bf16.h>
#include <stdint.h>

namespace {

constexpr int NH = 32, SK = 4096, DM = 576;
constexpr int KEYS = 128;
constexpr int UPP = SK / KEYS;
constexpr int NUK = 4 * NH * UPP;
constexpr int TILE_BYTES = KEYS * 256;
#define NWORK 2
constexpr int NW = NWORK;
constexpr int NBCTA = 32;
constexpr int MINCL = 15;
constexpr int NFIN = 72;
constexpr int SLOT = 32768;
constexpr int NSLOT = 6;
constexpr int BRING = 5;
constexpr int J0W = 5 * SLOT;
constexpr int MISC = NSLOT * SLOT + 4096;
constexpr int XP = 1168, CP = 1040, QP = 272;
constexpr int M_XA = MISC;
constexpr int M_XB = M_XA + 4 * XP;
constexpr int M_CH = M_XB + 4 * XP;
constexpr int M_CL = M_CH + 4 * CP;
constexpr int M_QB = M_CL + 4 * CP;
constexpr int M_QA = M_CH;
constexpr int M_J0 = M_QB + 4 * QP;
constexpr int M_P = M_J0 + 2048;
constexpr int M_ALPHA = M_P + 2560;
constexpr int M_OMEGA = M_ALPHA + 128;
constexpr int M_BAR = M_OMEGA + 128;
constexpr int M_HELP = M_BAR + 128;
#define NDIR 3
constexpr int L_W = 0;
constexpr int L_BF = L_W + NDIR * 18432 + 128;
constexpr int L_FLAG = L_BF + NDIR * 256;
constexpr int L_BAR = L_FLAG + 16;
constexpr int F_CTX = M_XB, F_RECV = M_CH, F_BAR = M_BAR + NSLOT * 8, F_W = 3 * SLOT;
constexpr int SMEM_BYTES = M_HELP + 128 + 1024;
static_assert(L_BAR + 8 + NDIR * 8 <= 5 * SLOT && NDIR >= 2 && NDIR <= 3, "final phase layout");
static_assert(SMEM_BYTES <= 232448 && M_BAR % 8 == 0 && M_QA % 16 == 0 && M_P % 16 == 0, "smem layout");
#define XW 2
#define X3 1
#define X3C 2
#define NEARLY 2
#define BD 4
#define FPF 3
#define FSLEEP 800
#define VS0 24
#define GHEAD 23
#define FILL 1
#define FJ 280
#define NPOLL 2
#define PGAP 200
static_assert(NH - NDIR >= VS0 && NDIR >= 2 && GHEAD < NH - NDIR, "direct heads");
static_assert(NW + XW <= 4 && NEARLY <= NW + XW && BD <= BRING, "slots 4 and 5 hold the finisher weights");
constexpr int KMIN = 2, KMAX = 4, VMIN = 0, VMAX = 4;
constexpr float SCALE = 0.08838834764831845f;
constexpr float LOG2E = 1.4426950408889634f;
constexpr unsigned SPIN_LIMIT = 1u << 24;

#define NREP 2
constexpr int C_QUEUE = 0, C_KDONE = 1, C_BBAR = 3, C_LINES = 5;
constexpr unsigned UNSET = 0xffffffffu;

struct Params {
    const __nv_bfloat16 *kc, *xa, *vc, *wo, *xb;
    __nv_bfloat16* out;
    CUtensorMap tm_j0;
    CUtensorMap tm_wq, tm_wuk, tm_ckv, tm_wuv, tm_wo;
    CUtensorMap tm_wl;
    CUtensorMap tm_wf;
};

__device__ unsigned g_epoch;
__device__ unsigned g_ctl[2][C_LINES][32];
__device__ uint2 g_qll[4 * 2048];
__device__ uint2 g_scores[128 * SK / 4];
__device__ float2 g_stats[128 * UPP];
__device__ float4 g_oacc[128 * 32];
__device__ unsigned g_vdone[NREP * NH][32];
__device__ float2 g_base[4 * DM / 2];
__device__ float4 g_part[NDIR * 4 * UPP * 32];
__device__ uint4 g_qabs[4 * 8 * 4 * 4 * 32];
__device__ float2 g_bpart[NBCTA * NH * 256];
__device__ float2 g_bml[NBCTA * NH];
__device__ uint4 g_ctx[NH * 128];
__device__ uint4 g_outb[NBCTA * NH * 36];

#define TS(i)
#define TSV(i, v)
#define LAND(i)
#define CLK(x)
#define ACC(a, x, y)

__device__ __forceinline__ uint32_t smem_u32(const void* p) { return (uint32_t)__cvta_generic_to_shared(p); }
__device__ __forceinline__ void mbar_init(uint32_t bar, uint32_t cnt) {
    asm volatile("mbarrier.init.shared::cta.b64 [%0], %1;" ::"r"(bar), "r"(cnt) : "memory");
}
__device__ __forceinline__ void mbar_expect_tx(uint32_t bar, uint32_t bytes) {
    asm volatile("mbarrier.arrive.expect_tx.shared::cta.b64 _, [%0], %1;" ::"r"(bar), "r"(bytes) : "memory");
}
__device__ __forceinline__ bool mbar_try(uint32_t bar, uint32_t parity) {
    uint32_t ok;
    asm volatile("{\n.reg .pred p;\nmbarrier.try_wait.parity.shared::cta.b64 p, [%1], %2;\nselp.u32 %0, 1, 0, p;\n}\n"
                 : "=r"(ok) : "r"(bar), "r"(parity) : "memory");
    return ok;
}
__device__ __forceinline__ void mbar_wait(uint32_t bar, uint32_t parity) {
    unsigned n = 0;
    while (!mbar_try(bar, parity)) { if (++n > SPIN_LIMIT) __trap(); }
}
__device__ __forceinline__ void bulk_load(uint32_t dst, const void* src, uint32_t bytes, uint32_t bar, uint64_t pol) {
    asm volatile("cp.async.bulk.shared::cluster.global.mbarrier::complete_tx::bytes.L2::cache_hint [%0], [%1], %2, [%3], %4;"
                 ::"r"(dst), "l"(src), "r"(bytes), "r"(bar), "l"(pol) : "memory");
}
__device__ __forceinline__ void tma3d(uint32_t dst, const CUtensorMap* tm, int c0, int c1, int c2, uint32_t bar, uint64_t pol) {
    asm volatile("cp.async.bulk.tensor.3d.shared::cluster.global.mbarrier::complete_tx::bytes.L2::cache_hint [%0], [%1, {%3,%4,%5}], [%2], %6;"
                 ::"r"(dst), "l"(tm), "r"(bar), "r"(c0), "r"(c1), "r"(c2), "l"(pol) : "memory");
}
__device__ __forceinline__ void l2_prefetch(const void* src, uint32_t bytes) {
    asm volatile("cp.async.bulk.prefetch.L2.global [%0], %1;" ::"l"(src), "r"(bytes) : "memory");
}
__device__ __forceinline__ void ldsm4(uint32_t (&r)[4], uint32_t addr) {
    asm volatile("ldmatrix.sync.aligned.m8n8.x4.shared.b16 {%0,%1,%2,%3}, [%4];"
                 : "=r"(r[0]), "=r"(r[1]), "=r"(r[2]), "=r"(r[3]) : "r"(addr));
}
__device__ __forceinline__ void ldsm4t(uint32_t (&r)[4], uint32_t addr) {
    asm volatile("ldmatrix.sync.aligned.m8n8.x4.trans.shared.b16 {%0,%1,%2,%3}, [%4];"
                 : "=r"(r[0]), "=r"(r[1]), "=r"(r[2]), "=r"(r[3]) : "r"(addr));
}
__device__ __forceinline__ void mma16816(float (&d)[4], const uint32_t (&a)[4], uint32_t b0, uint32_t b1) {
    asm("mma.sync.aligned.m16n8k16.row.col.f32.bf16.bf16.f32 {%0,%1,%2,%3}, {%4,%5,%6,%7}, {%8,%9}, {%0,%1,%2,%3};"
        : "+f"(d[0]), "+f"(d[1]), "+f"(d[2]), "+f"(d[3])
        : "r"(a[0]), "r"(a[1]), "r"(a[2]), "r"(a[3]), "r"(b0), "r"(b1));
}
__device__ __forceinline__ uint32_t lds32(uint32_t a) {
    uint32_t v;
    asm volatile("ld.shared.u32 %0, [%1];" : "=r"(v) : "r"(a));
    return v;
}
__device__ __forceinline__ unsigned ld_acquire(const unsigned* p) {
    unsigned v;
    asm volatile("ld.acquire.gpu.global.u32 %0, [%1];" : "=r"(v) : "l"(p) : "memory");
    return v;
}
__device__ __forceinline__ uint2 ld_relaxed8(const void* p) {
    uint2 v;
    asm volatile("ld.relaxed.gpu.global.v2.u32 {%0,%1}, [%2];" : "=r"(v.x), "=r"(v.y) : "l"(p) : "memory");
    return v;
}
__device__ __forceinline__ unsigned ld_relaxed4(const void* p) {
    unsigned v;
    asm volatile("ld.relaxed.gpu.global.u32 %0, [%1];" : "=r"(v) : "l"(p) : "memory");
    return v;
}
__device__ __forceinline__ unsigned atom_inc(unsigned* p) {
    unsigned v;
    asm volatile("atom.relaxed.gpu.global.inc.u32 %0, [%1], 0x7fffffff;" : "=r"(v) : "l"(p) : "memory");
    return v;
}
__device__ __forceinline__ unsigned long long ld_relaxed64(const void* p) {
    unsigned long long v;
    asm volatile("ld.relaxed.gpu.global.u64 %0, [%1];" : "=l"(v) : "l"(p) : "memory");
    return v;
}
__device__ __forceinline__ void st_relaxed64(void* p, unsigned long long v) {
    asm volatile("st.relaxed.gpu.global.u64 [%0], %1;" ::"l"(p), "l"(v) : "memory");
}
__device__ __forceinline__ float4 ld_relaxed16(const void* p) {
    float4 v;
    asm volatile("ld.relaxed.gpu.global.v4.f32 {%0,%1,%2,%3}, [%4];" : "=f"(v.x), "=f"(v.y), "=f"(v.z), "=f"(v.w) : "l"(p) : "memory");
    return v;
}
__device__ __forceinline__ uint32_t not_unset(float v) { return min(__float_as_uint(v), UNSET - 1); }
__device__ __forceinline__ void st_relaxed16(void* p, uint32_t a, uint32_t b, uint32_t c, uint32_t d) {
    asm volatile("st.relaxed.gpu.global.v4.u32 [%0], {%1,%2,%3,%4};" ::"l"(p), "r"(a), "r"(b), "r"(c), "r"(d) : "memory");
}
__device__ __forceinline__ bool is_unset(const float4& v) {
    return max(max(__float_as_uint(v.x), __float_as_uint(v.y)), max(__float_as_uint(v.z), __float_as_uint(v.w))) == UNSET;
}
__device__ __forceinline__ float4 ld_if16(const float4* src, bool c) {
    float4 v;
    asm volatile("{\n.reg .pred p;\nsetp.ne.u32 p, %5, 0;\n@p ld.relaxed.gpu.global.v4.f32 {%0,%1,%2,%3}, [%4];\n}"
                 : "=f"(v.x), "=f"(v.y), "=f"(v.z), "=f"(v.w) : "l"(src), "r"((uint32_t)c) : "memory");
    return v;
}
__device__ __forceinline__ uint32_t mapa(uint32_t a, uint32_t rank) {
    uint32_t r;
    asm("mapa.shared::cluster.u32 %0, %1, %2;" : "=r"(r) : "r"(a), "r"(rank));
    return r;
}
__device__ __forceinline__ void mbar_wait_cluster(uint32_t bar, uint32_t parity) {
    unsigned n = 0;
    while (true) {
        uint32_t ok;
        asm volatile("{\n.reg .pred p;\nmbarrier.test_wait.parity.acquire.cluster.shared::cta.b64 p, [%1], %2;\nselp.u32 %0, 1, 0, p;\n}\n"
                     : "=r"(ok) : "r"(bar), "r"(parity) : "memory");
        if (ok) break;
        if (++n > SPIN_LIMIT) __trap();
    }
}
__device__ __forceinline__ void fence_gpu() { asm volatile("fence.acq_rel.gpu;" ::: "memory"); }
__device__ __forceinline__ void red_add_u32(unsigned* p, unsigned v) {
    asm volatile("red.relaxed.gpu.global.add.u32 [%0], %1;" ::"l"(p), "r"(v) : "memory");
}
__device__ __forceinline__ void st_tagged2(void* p, float a, float b, unsigned tag) {
    const unsigned long long hi = (unsigned long long)tag << 32;
    asm volatile("st.relaxed.gpu.global.v2.b64 [%0], {%1,%2};" ::"l"(p), "l"(hi | __float_as_uint(a)), "l"(hi | __float_as_uint(b)) : "memory");
}
__device__ __forceinline__ ulonglong2 ld_tagged2(const void* p) {
    ulonglong2 v;
    asm volatile("ld.relaxed.gpu.global.v2.b64 {%0,%1}, [%2];" : "=l"(v.x), "=l"(v.y) : "l"(p) : "memory");
    return v;
}
__device__ __forceinline__ float4 atom_add_f4(void* p, float a, float b, float c, float d) {
    float4 r;
    asm volatile("atom.relaxed.gpu.global.add.v4.f32 {%0,%1,%2,%3}, [%4], {%5,%6,%7,%8};"
                 : "=f"(r.x), "=f"(r.y), "=f"(r.z), "=f"(r.w) : "l"(p), "f"(a), "f"(b), "f"(c), "f"(d) : "memory");
    return r;
}
__device__ __forceinline__ void red_release_cta_shared(uint32_t a, unsigned v) {
    asm volatile("red.release.cta.shared::cta.add.u32 [%0], %1;" ::"r"(a), "r"(v) : "memory");
}
__device__ __forceinline__ unsigned ld_acquire_cta_shared(uint32_t a) {
    unsigned v;
    asm volatile("ld.acquire.cta.shared::cta.u32 %0, [%1];" : "=r"(v) : "r"(a) : "memory");
    return v;
}
__device__ __forceinline__ void st_release_cta_shared(uint32_t a, unsigned v) {
    asm volatile("st.release.cta.shared::cta.u32 [%0], %1;" ::"r"(a), "r"(v) : "memory");
}
__device__ __forceinline__ void wait_count(const unsigned* p, unsigned target) {
    unsigned n = 0;
    while (ld_acquire(p) < target) { if (++n > SPIN_LIMIT) __trap(); }
}
__device__ __forceinline__ uint32_t pack_bf16(float lo, float hi) {
    uint32_t r;
    asm("cvt.rn.bf16x2.f32 %0, %1, %2;" : "=r"(r) : "f"(hi), "f"(lo));
    return r;
}
__device__ __forceinline__ float bf_lo(uint32_t v) { return __uint_as_float(v << 16); }
__device__ __forceinline__ float bf_hi(uint32_t v) { return __uint_as_float(v & 0xffff0000u); }
__device__ __forceinline__ float ex2(float x) { float y; asm("ex2.approx.ftz.f32 %0, %1;" : "=f"(y) : "f"(x)); return y; }
__device__ __forceinline__ float expsub(float a, float b) { return ex2((a - b) * LOG2E); }
__device__ __forceinline__ float warp_max(float v) {
#pragma unroll
    for (int m = 16; m; m >>= 1) v = fmaxf(v, __shfl_xor_sync(~0u, v, m));
    return v;
}
__device__ __forceinline__ float warp_sum(float v) {
#pragma unroll
    for (int m = 16; m; m >>= 1) v += __shfl_xor_sync(~0u, v, m);
    return v;
}
template <int HL>
__device__ __forceinline__ unsigned unit_block(int u) {
    const unsigned x = ((unsigned)u & (NUK - 1)) / UPP;
    const int lg = u < NUK ? min(KMAX, max(KMIN, 29 - __clz(x | 1))) : (HL < NH && (int)x >= 4 * VS0 ? 0 : min(VMAX, max(VMIN, 29 - __clz((127 - x) | 1))));
    const unsigned r = x & ((4u << lg) - 1);
    return ((x - r + (r & ((1u << lg) - 1)) * 4 + (r >> lg)) * UPP) | ((unsigned)u & (UPP - 1));
}
__device__ __forceinline__ const char* block_src(const void* base, unsigned blk) {
    const unsigned po = blk / UPP;
    return reinterpret_cast<const char*>(base) + (size_t)(((po & 3) * NH + (po >> 2)) * UPP + blk % UPP) * TILE_BYTES;
}

template <int HD>
__device__ __forceinline__ void a_worker(const Params& p, int un, bool once, bool pre, bool hold, int nstatic, uint32_t slot, uint32_t bar,
                                         uint32_t help, unsigned epoch, uint64_t pol) {
    constexpr int NU = 2 * NUK;
    const int lane = threadIdx.x & 31, g = lane >> 2, t = lane & 3;
    const int li = lane & 7;
    uint32_t kaddr[4], vaddr[8];
    {
        const int e = (lane >> 3) & 1, kk = lane >> 4;
#pragma unroll
        for (int s = 0; s < 4; s++) kaddr[s] = slot + (16 * li + e) * 256 + ((2 * s + kk + li) & 7) * 16;
        const int vrow = 4 * (li >> 1) + (li & 1) + 2 * kk;
#pragma unroll
        for (int c = 0; c < 8; c++) vaddr[c] = slot + vrow * 256 + e * 128 + ((c + li) & 7) * 16;
#pragma unroll
        for (int c = 0; c < 8; c++) asm volatile("" : "+r"(vaddr[c]));
    }
    const uint32_t vmask = (g >> 1) != t ? 0u : ((g & 1) ? 0xffff0000u : 0xffffu);
    int kseen = -1;
    unsigned long long H0 = 0, H1 = 0;
    auto header = [&](int v, unsigned vb) {
        if (v >= NU) return;
        const void *a0, *a1;
        if (v < NUK) {
            const unsigned po = vb / UPP;
            a0 = g_qll + (po & 3) * 2048 + (po >> 2) * 64 + lane;
            a1 = reinterpret_cast<const uint2*>(a0) + 32;
        } else {
            const int half = vb / (NUK / 2);
            if (half > kseen) {
                unsigned n = 0;
                while (ld_acquire_cta_shared(help + 12 + 4 * half) == 0) { if (++n > (SPIN_LIMIT << 4)) __trap(); }
                kseen = half;
            }
            a0 = &g_scores[vb * (KEYS / 4) + lane];
            a1 = &g_stats[(vb / UPP) * UPP + lane];
        }
        H0 = ld_relaxed64(a0);
        H1 = ld_relaxed64(a1);
    };
    asm volatile("bar.sync 2, %0;" ::"n"(32 * (NW + XW + 1)) : "memory");
    epoch = __shfl_sync(~0u, epoch, 0);
    if (hold) { unsigned n = 0; while (ld_acquire_cta_shared(help + 24) < 2) { if (++n > (SPIN_LIMIT << 4)) __trap(); } }
    unsigned (*ctl)[32] = g_ctl[epoch & 1];
    const unsigned tag = epoch + 1;
    unsigned nxt = once ? NU : 0;
    int u = -1;
    unsigned bu = 0, bn = unit_block<HD>(un);
    bool have = false;
    uint32_t phase = 0;
    unsigned kpend = 0;
    const unsigned zero = gridDim.x >> 24;
    uint32_t Q[16];
    float4 oret = make_float4(0.f, 0.f, 0.f, 0.f);
    while (true) {
        const char* nsrc = block_src(un < NUK ? p.kc : p.vc, bn);
        float4* odst = &g_oacc[(bu / UPP) * 32 + lane];
        unsigned* vdst = &g_vdone[(lane & (NREP - 1)) * NH + bu / (4 * UPP)][0];
        float d[8][4];
        CLK(c1);
        const bool dir = HD < NH && u >= NUK && bu >= HD * 4 * UPP;
        if (dir) odst = &g_part[((bu / UPP - HD * 4) * 8 + g) * (UPP * 4) + (bu % UPP) * 4 + t];
        asm volatile("" : "+l"(odst));
        if (u >= NUK) {
#pragma unroll
            for (int j = 0; j < 8; j++) { d[j][0] = d[j][1] = d[j][2] = d[j][3] = 0.f; }
            mbar_wait(bar, phase);
            LAND(NUK + bu);
            uint32_t a[2][8][4];
#pragma unroll
            for (int c = 0; c < 8; c++) ldsm4t(a[0][c], vaddr[c]);
#pragma unroll
            for (int j = 0; j < 8; j++) {
                if (j < 7) {
#pragma unroll
                    for (int c = 0; c < 8; c++) ldsm4t(a[(j + 1) & 1][c], vaddr[c] + (j + 1) * 4096);
                }
#pragma unroll
                for (int c = 0; c < 8; c++) mma16816(d[c], a[j & 1][c], Q[2 * j], Q[2 * j + 1]);
            }
            float o[4];
#pragma unroll
            for (int r = 0; r < 2; r++) {
                o[2 * r] = d[0][2 * r] + d[7][2 * r + 1];
                o[2 * r + 1] = d[0][2 * r + 1] + d[1][2 * r];
#pragma unroll
                for (int k = 1; k < 4; k++) {
                    const int src = (lane & 28) | ((t - k) & 3);
                    o[2 * r] += __shfl_sync(~0u, d[2 * k][2 * r] + d[2 * k - 1][2 * r + 1], src);
                    o[2 * r + 1] += __shfl_sync(~0u, d[2 * k][2 * r + 1] + d[2 * k + 1][2 * r], src);
                }
            }
            if (dir) {
                st_relaxed16(odst, not_unset(o[0]), not_unset(o[1]), not_unset(o[2]), not_unset(o[3]));
            } else {
                oret = atom_add_f4(odst, o[0], o[1], o[2], o[3]);
            }
        } else if (u >= 0) {
#pragma unroll
            for (int j = 0; j < 8; j++) { d[j][0] = d[j][1] = d[j][2] = d[j][3] = 0.f; }
            mbar_wait(bar, phase);
            LAND(bu);
            uint32_t a[2][8][4];
#pragma unroll
            for (int j = 0; j < 8; j++) ldsm4(a[0][j], kaddr[0] + (4 * (j & 3) + 2 * (j >> 2)) * 256);
#pragma unroll
            for (int s = 0; s < 8; s++) {
                if (s < 7) {
#pragma unroll
                    for (int j = 0; j < 8; j++)
                        ldsm4(a[(s + 1) & 1][j], kaddr[(s + 1) & 3] + (4 * (j & 3) + 2 * (j >> 2)) * 256 + ((s + 1) >> 2) * 128);
                }
#pragma unroll
                for (int j = 0; j < 8; j++)
                    mma16816(d[j], a[s & 1][j], Q[(s & 4) * 2 + ((2 * s - 2 * j) & 7)], Q[(s & 4) * 2 + ((2 * s + 1 - 2 * j) & 7)]);
            }
        }
        if (u >= 0) phase ^= 1;
        CLK(c2b);
        if (un < NU && lane == 0) {
            if (!once) nxt = atom_inc(&ctl[C_QUEUE][0]);
            if (u >= 0 || !pre) {
                mbar_expect_tx(bar, TILE_BYTES);
                bulk_load(slot, nsrc, TILE_BYTES, bar, pol);
            }
        }
        const uint32_t tiss = (uint32_t)clock();
        CLK(c3);
        if ((unsigned)u < (unsigned)NUK) {
            const int j0 = (t - (g >> 1)) & 3;
            float v[4];
#pragma unroll
            for (int q = 0; q < 4; q++) {
                const int jq = (q >> 1) * 4, e = (q & 1) * 2;
                const float x0 = (g & 1) ? d[jq + 0][e + 1] : d[jq + 0][e];
                const float x1 = (g & 1) ? d[jq + 1][e + 1] : d[jq + 1][e];
                const float x2 = (g & 1) ? d[jq + 2][e + 1] : d[jq + 2][e];
                const float x3 = (g & 1) ? d[jq + 3][e + 1] : d[jq + 3][e];
                const float y0 = (j0 & 1) ? x1 : x0, y1 = (j0 & 1) ? x3 : x2;
                v[q] = (j0 & 2) ? y1 : y0;
            }
            const uint32_t r0 = pack_bf16(v[0], v[1]), r1 = pack_bf16(v[2], v[3]);
            const uint32_t s0 = pack_bf16(bf_lo(r0) * SCALE, bf_hi(r0) * SCALE);
            const uint32_t s1 = pack_bf16(bf_lo(r1) * SCALE, bf_hi(r1) * SCALE);
            g_scores[bu * (KEYS / 4) + 4 * g + j0] = make_uint2(s0, s1);
            const float f0 = bf_lo(s0), f1 = bf_hi(s0), f2 = bf_lo(s1), f3 = bf_hi(s1);
            const float m = warp_max(fmaxf(fmaxf(f0, f1), fmaxf(f2, f3)));
            const float l = warp_sum((expsub(f0, m) + expsub(f1, m)) + (expsub(f2, m) + expsub(f3, m)));
            if (lane == 0) g_stats[bu] = make_float2(m, l);
            kpend++;
            if (un / (NUK / 2) != u / (NUK / 2)) {
                __syncwarp();
                if (lane == 0) {
                    red_release_cta_shared(help + 4 * (u / (NUK / 2)), kpend);
                    if (un >= NUK) red_release_cta_shared(help + 8, 1u);
                }
                kpend = 0;
            }
        }
        CLK(c4);
        int unn = NU;
        if (un < NU) {
            unsigned n = 0;
            while (true) {
                if (!have) header(un, bn);
                if (un >= NUK || __all_sync(~0u, (uint32_t)(H0 >> 32) == tag && (uint32_t)(H1 >> 32) == tag)) break;
                if (++n > SPIN_LIMIT) __trap();
                have = false;
            }
            if (un >= NUK) {
                const uint32_t s0 = (uint32_t)H0, s1 = (uint32_t)(H0 >> 32);
                const float mu = __uint_as_float((uint32_t)H1);
                const float m = warp_max(mu);
                const float l = warp_sum(__uint_as_float((uint32_t)(H1 >> 32)) * expsub(mu, m));
                const float inv = 1.0f / l;
                const uint32_t w0 = pack_bf16(expsub(bf_lo(s0), m) * inv, expsub(bf_hi(s0), m) * inv);
                const uint32_t w1 = pack_bf16(expsub(bf_lo(s1), m) * inv, expsub(bf_hi(s1), m) * inv);
#pragma unroll
                for (int j = 0; j < 8; j++) {
                    Q[2 * j] = __shfl_sync(~0u, w0, 4 * j + t) & vmask;
                    Q[2 * j + 1] = __shfl_sync(~0u, w1, 4 * j + t) & vmask;
                }
            } else {
#pragma unroll
                for (int j = 0; j < 8; j++) {
                    const int src = (((j + g) & 7) << 2) + t;
                    Q[j] = __shfl_sync(~0u, (uint32_t)H0, src);
                    Q[8 + j] = __shfl_sync(~0u, (uint32_t)H1, src);
                }
            }
            unn = nstatic + (int)__shfl_sync(~0u, nxt, 0);
            if (FILL && HD < NH && !once && unn >= NU && lane == 0)
                asm volatile("st.relaxed.cta.shared::cta.u32 [%0], %1;" ::"r"(help + 28), "r"((tiss + (FJ - (unn - NU)) * 20) | 1u) : "memory");
        }
        if (u >= NUK && !dir && lane < NREP)
            red_add_u32(vdst,
                        1u + ((__float_as_uint(oret.x) | __float_as_uint(oret.y) | __float_as_uint(oret.z) | __float_as_uint(oret.w)) & zero));
        if (un >= NU) break;
        bu = bn;
        have = !(un < NUK && unn >= NUK && !(un >= NUK / 2 && unn < NUK + NUK / 2));
        bn = unit_block<HD>(unn);
        if (have) header(unn, bn);
        u = un;
        un = unn;
    }
}

__device__ __forceinline__ void k_helper(uint32_t help, unsigned epoch) {
    if ((threadIdx.x & 31) != 0) return;
    unsigned (*ctl)[32] = g_ctl[epoch & 1];
    unsigned sent0 = 0, sent1 = 0, n = 0;
    int seen = 0;
    bool fin = false;
    while (!fin || seen < 2) {
        if (!fin) {
            fin = ld_acquire_cta_shared(help + 8) == NW + XW;
            const unsigned c0 = ld_acquire_cta_shared(help), c1 = ld_acquire_cta_shared(help + 4);
            if (c0 != sent0 || c1 != sent1) {
                fence_gpu();
                if (c0 != sent0) red_add_u32(&ctl[C_KDONE][0], c0 - sent0);
                if (c1 != sent1) red_add_u32(&ctl[C_KDONE + 1][0], c1 - sent1);
                sent0 = c0; sent1 = c1;
            }
        }
        if (seen < 2 && ld_acquire(&ctl[C_KDONE + seen][0]) >= NUK / 2) {
            st_release_cta_shared(help + 12 + 4 * seen, 1u);
            seen++;
        } else {
            __nanosleep(300);
        }
        if (++n > SPIN_LIMIT) __trap();
    }
}

template <int HL>
__device__ __forceinline__ void v_poller(uint32_t sbase, int f, int w) {
    const int lane = threadIdx.x & 31;
    const unsigned (*cp)[32] = &g_vdone[((f * NPOLL + w) % NREP) * NH];
    unsigned n = 0;
    while (ld_acquire_cta_shared(sbase + M_HELP + 12) == 0) { __nanosleep(1000); if (++n > SPIN_LIMIT) __trap(); }
    int h = 0;
    bool fast = false;
    while (h < HL) {
        const unsigned r = __ballot_sync(~0u, ld_acquire(&cp[min(h + (lane & 3), HL - 1)][0]) >= 4 * UPP) & 15u;
        if (r & 1) {
            h = min(HL, h + __ffs(~r) - 1);
            __syncwarp();
            if (lane == 0) asm volatile("red.release.cta.shared::cta.max.u32 [%0], %1;" ::"r"(sbase + M_HELP + 20), "r"(h) : "memory");
        }
        if (h < HL - 4) {
            __nanosleep(h ? 300 : 1000);
        } else if (!fast) {
            fast = true;
            const long long t0 = clock64();
            while (clock64() - t0 < w * PGAP) {}
        }
        if (++n > SPIN_LIMIT) __trap();
    }
}
template <int HL>
__device__ __forceinline__ void finisher(const Params& p, uint32_t sbase, int f) {
    const int lane = threadIdx.x & 31;
    {
        const char* wg = reinterpret_cast<const char*>(p.wo);
        const uint32_t dst = sbase + 4 * SLOT + (16 * (lane & 7) + (lane >> 3)) * 16;
#pragma unroll 1
        for (int h = -FPF - 4; h < HL; h++) {
            if (lane == 0 && (unsigned)(h + FPF) < (unsigned)HL) l2_prefetch(wg + (size_t)(h + FPF) * 147456 + f * 2048, 2048);
            if (h >= 0) {
#pragma unroll
                for (int r = 0; r < 4; r++)
                    asm volatile("cp.async.cg.shared.global [%0], [%1], 16;" ::"r"(dst + h * 2048 + ((r & 1) * 4 + (r >> 1) * 8) * 16),
                                 "l"(wg + (size_t)(h * 128 + r * 32 + lane) * (DM * 2) + f * 16) : "memory");
            }
            __nanosleep(FSLEEP);
        }
        asm volatile("cp.async.wait_all;" ::: "memory");
        __syncwarp();
    }
    TS(11);
    const float4* vec = g_oacc + ((lane >> 2) & 3) * 32 + (lane >> 4) * 16 + (lane & 3);
    float acc[2][2][4];
#pragma unroll
    for (int i = 0; i < 16; i++) acc[i >> 3][(i >> 2) & 1][i & 3] = 0.f;
    uint32_t* outp = reinterpret_cast<uint32_t*>(p.out + (lane >> 2) * (2 * DM) + f * 8 + (lane & 3) * 2);
    uint32_t wa = sbase + 4 * SLOT + lane * 16;
    auto project = [&](const float4 (&x)[4], const uint32_t (&w)[4][4]) {
#pragma unroll
        for (int s = 0; s < 4; s++) {
            const uint32_t a[4] = {pack_bf16(x[s].x, x[s].y), 0u, pack_bf16(x[s].z, x[s].w), 0u};
            mma16816(acc[0][s & 1], a, w[s >> 1][(s & 1) * 2], w[s >> 1][(s & 1) * 2 + 1]);
            mma16816(acc[1][s & 1], a, w[2 + (s >> 1)][(s & 1) * 2], w[2 + (s >> 1)][(s & 1) * 2 + 1]);
        }
    };
    int h = 0;
    unsigned n = 0;
    while (h < HL) {
        uint32_t w[4][4];
#pragma unroll
        for (int q = 0; q < 4; q++) ldsm4t(w[q], wa + q * 512);
        int ready;
        while ((ready = ld_acquire_cta_shared(sbase + M_HELP + 20)) <= h) {
            if (h < HL - 3) __nanosleep(100);
            if (++n > (SPIN_LIMIT << 4)) __trap();
        }
        float4 x[4], y[4];
#pragma unroll
        for (int s = 0; s < 4; s++) x[s] = ld_relaxed16(vec + s * 4);
        const bool two = ready > h + 1;
        if (two) {
#pragma unroll
            for (int s = 0; s < 4; s++) y[s] = ld_relaxed16(vec + 128 + s * 4);
        }
        project(x, w);
        if (two) {
#pragma unroll
            for (int q = 0; q < 4; q++) ldsm4t(w[q], wa + 2048 + q * 512);
            project(y, w);
        }
        const int nr = two ? 2 : 1;
        h += nr;
        vec += nr * 128;
        wa += nr * 2048;
        if (FILL && HL < NH && lane == 0) st_release_cta_shared(sbase + M_HELP + 36, h);
        const float o0 = acc[0][0][0] + acc[0][1][0] + __shfl_down_sync(~0u, acc[1][0][0] + acc[1][1][0], 16);
        const float o1 = acc[0][0][1] + acc[0][1][1] + __shfl_down_sync(~0u, acc[1][0][1] + acc[1][1][1], 16);
        if (HL == NH) {
            asm volatile("{\n.reg .pred p;\nsetp.ne.u32 p, %2, 0;\n@p st.global.u32 [%0], %1;\n}" ::"l"(outp), "r"(pack_bf16(o0, o1)),
                         "r"((uint32_t)(lane < 16 && h == NH)) : "memory");
        } else if (lane < 16 && h == HL) {
            st_relaxed64(&g_base[(lane >> 2) * (DM / 2) + f * 4 + (lane & 3)], not_unset(o0) | ((unsigned long long)not_unset(o1) << 32));
        }
    }
}

__device__ __noinline__ void final_collector(int b, int rank, int hh, uint32_t sbase) {
    const int lane = threadIdx.x & 31, g = lane >> 2, t = lane & 3;
    const float unset = __uint_as_float(UNSET);
    const float4* src = g_part + ((hh * 4 + b) * 8 + rank) * (UPP * 4) + lane;
    const uint32_t rdst = mapa(sbase + L_BF + hh * 256 + rank * 32 + t * 8, g), rbar = mapa(sbase + L_BAR + 8 + hh * 8, g);
    float4 x[4];
#pragma unroll
    for (int i = 0; i < 4; i++) x[i] = make_float4(unset, unset, unset, unset);
    unsigned n = 0;
    while (true) {
        bool e[4];
#pragma unroll
        for (int i = 0; i < 4; i++) e[i] = is_unset(x[i]);
        if (!__any_sync(~0u, e[0] || e[1] || e[2] || e[3])) break;
        float4 u[4];
#pragma unroll
        for (int i = 0; i < 4; i++) u[i] = ld_if16(src + i * 32, e[i]);
#pragma unroll
        for (int i = 0; i < 4; i++)
            if (e[i]) x[i] = u[i];
        if (++n > SPIN_LIMIT) __trap();
    }
    unsigned first = 0;
    if (lane == 0) asm volatile("atom.relaxed.cta.shared::cta.exch.b32 %0, [%1], 1;" : "=r"(first) : "r"(sbase + L_FLAG + hh * 4) : "memory");
    float s[4] = {(x[0].x + x[1].x) + (x[2].x + x[3].x), (x[0].y + x[1].y) + (x[2].y + x[3].y),
                  (x[0].z + x[1].z) + (x[2].z + x[3].z), (x[0].w + x[1].w) + (x[2].w + x[3].w)};
#pragma unroll
    for (int m = 4; m < 32; m <<= 1) {
#pragma unroll
        for (int i = 0; i < 4; i++) s[i] += __shfl_xor_sync(~0u, s[i], m);
    }
    if (__shfl_sync(~0u, first, 0) == 0) {
        asm volatile("st.async.weak.shared::cluster.mbarrier::complete_tx::bytes.v2.b32 [%0], {%1,%2}, [%3];"
                     ::"r"(rdst), "r"(pack_bf16(s[0], s[1])), "r"(pack_bf16(s[2], s[3])), "r"(rbar) : "memory");
        if (hh == NDIR - 1) TS(31);
    }
}

__device__ __forceinline__ void final_projector(const Params& p, int b, int rank, int j, uint32_t sbase) {
    const int lane = threadIdx.x & 31, g = lane >> 2, t = lane & 3;
    const int col = 16 * j + 8 * (t & 1) + g;
    float base = 0.f;
    if (t < 2 && col < 72) {
        unsigned n = 0;
        uint32_t v;
        while ((v = ld_relaxed4(reinterpret_cast<const float*>(g_base) + b * DM + rank * 72 + col)) == UNSET) { if (++n > SPIN_LIMIT) __trap(); }
        base = __uint_as_float(v);
    }
    __syncwarp();
    TS(28);
    float acc[4][4];
#pragma unroll
    for (int i = 0; i < 16; i++) acc[i >> 2][i & 3] = 0.f;
    mbar_wait(sbase + L_BAR, 0);
#pragma unroll 1
    for (int hh = 0; hh < NDIR; hh++) {
        uint32_t a[8][4];
#pragma unroll
        for (int s = 0; s < 8; s++)
            ldsm4t(a[s], sbase + L_W + hh * 18432 + s * 2304 + ((lane & 7) + (lane >> 4) * 8) * 144 + (2 * j + ((lane >> 3) & 1)) * 16);
        mbar_wait_cluster(sbase + L_BAR + 8 + hh * 8, 0);
        if (hh == NDIR - 1) TS(24);
        uint32_t bf[8][2];
#pragma unroll
        for (int s = 0; s < 8; s++)
            asm volatile("ld.shared.v2.u32 {%0,%1}, [%2];" : "=r"(bf[s][0]), "=r"(bf[s][1]) : "r"(sbase + L_BF + hh * 256 + s * 32 + t * 8) : "memory");
#pragma unroll
        for (int s = 0; s < 8; s++) mma16816(acc[s & 3], a[s], bf[s][0], bf[s][1]);
        const float v = ((t & 1) ? (acc[0][2] + acc[1][2]) + (acc[2][2] + acc[3][2]) : (acc[0][0] + acc[1][0]) + (acc[2][0] + acc[3][0])) + base;
        asm volatile("{\n.reg .pred p;\nsetp.ne.u32 p, %2, 0;\n@p st.global.u16 [%0], %1;\n}"
                     ::"l"(p.out + b * 2 * DM + rank * 72 + col), "h"((unsigned short)pack_bf16(v, 0.f)),
                       "r"((uint32_t)(hh == NDIR - 1 && t < 2 && col < 72)) : "memory");
    }
    TS(15);
}

template <int HD>
__device__ __forceinline__ void final_phase(const Params& p, uint32_t sbase, int blk, unsigned epoch, uint64_t pol) {
    const int tid = threadIdx.x, warp = tid >> 5;
    const int b = blk >> 3, rank = blk & 7;
    unsigned (*ctl)[32] = g_ctl[epoch & 1];
    __syncthreads();
    if (tid == 0) {
#pragma unroll 1
        for (int i = 0; i < 1 + NDIR; i++) mbar_init(sbase + L_BAR + i * 8, 1);
#pragma unroll
        for (int i = 0; i < NDIR; i++) asm volatile("st.shared.u32 [%0], 0;" ::"r"(sbase + L_FLAG + i * 4) : "memory");
        asm volatile("fence.mbarrier_init.release.cluster;" ::: "memory");
        mbar_expect_tx(sbase + L_BAR, NDIR * 18432);
#pragma unroll 1
        for (int hh = 0; hh < NDIR; hh++) {
            mbar_expect_tx(sbase + L_BAR + 8 + hh * 8, 256);
            tma3d(sbase + L_W + hh * 18432, &p.tm_wl, rank * 72, (HD + hh) * 16, 0, sbase + L_BAR, pol);
        }
        unsigned n = 0;
        while (ld_acquire(&ctl[C_KDONE][0]) < NUK / 2 || ld_acquire(&ctl[C_KDONE + 1][0]) < NUK / 2) { __nanosleep(500); if (++n > SPIN_LIMIT) __trap(); }
        while (ld_relaxed4(&g_vdone[(blk & (NREP - 1)) * NH + GHEAD][0]) < 4 * UPP) { __nanosleep(200); if (++n > SPIN_LIMIT) __trap(); }
    }
    asm volatile("barrier.cluster.arrive.release.aligned;\nbarrier.cluster.wait.acquire.aligned;" ::: "memory");
    TS(11);
    if (warp >= 3) {
        final_projector(p, b, rank, warp - 3, sbase);
    } else {
        if (warp < NDIR) final_collector(b, rank, warp, sbase);
        if (warp != NDIR - 1) final_collector(b, rank, NDIR - 1, sbase);
    }
}

__device__ __forceinline__ void fill_ctx(uint32_t sbase, int rank, unsigned tag) {
    const int lane = threadIdx.x & 31;
    unsigned n = 0;
    while (ld_acquire_cta_shared(sbase + M_HELP + 20) == 0) { __nanosleep(1000); if (++n > SPIN_LIMIT) __trap(); }
#pragma unroll 1
    for (int i = 0; i < 16;) {
        const ulonglong2 v = ld_tagged2(&g_ctx[rank * 512 + i * 32 + lane]);
        if (__all_sync(~0u, (unsigned)(v.x >> 32) == tag && (unsigned)(v.y >> 32) == tag)) {
            asm volatile("st.shared.v2.u32 [%0], {%1,%2};" ::"r"(sbase + F_CTX + (i * 32 + lane) * 8), "r"((uint32_t)v.x), "r"((uint32_t)v.y) : "memory");
            i++;
        } else {
            __nanosleep(500);
            if (++n > SPIN_LIMIT) __trap();
        }
    }
    __syncwarp();
    if (lane == 0) st_release_cta_shared(sbase + M_HELP + 32, 1u);
}
__device__ __noinline__ void fill_piece(uint32_t sbase, int rank, int w) {
    const int lane = threadIdx.x & 31, g = lane >> 2, t = lane & 3;
    unsigned n = 0;
    while (ld_acquire_cta_shared(sbase + M_HELP + 32) == 0) { if (++n > (SPIN_LIMIT << 4)) __trap(); }
    uint32_t bf[8][2];
#pragma unroll
    for (int s = 0; s < 8; s++)
        asm volatile("ld.shared.v2.u32 {%0,%1}, [%2];" : "=r"(bf[s][0]), "=r"(bf[s][1]) : "r"(sbase + F_CTX + w * 1024 + s * 128 + (lane & 15) * 8) : "memory");
    asm volatile("barrier.cluster.wait.acquire.aligned;" ::: "memory");
    uint32_t rdst[4], rbar[4];
#pragma unroll
    for (int j = 0; j < 4; j++) {
        rdst[j] = mapa(sbase + F_RECV + (rank * 4 + w) * 128 + g * 16 + (t & 1) * 8, 2 * j + (t >> 1));
        rbar[j] = mapa(sbase + F_BAR + 32, 2 * j + (t >> 1));
    }
    const uint32_t wa = sbase + F_W + w * 16384 + ((lane & 7) + (lane >> 4) * 8) * 128;
    uint32_t sw[4];
#pragma unroll
    for (int j = 0; j < 4; j++) sw[j] = wa + (((2 * j + ((lane >> 3) & 1)) ^ (lane & 7)) * 16);
    float acc[2][4][4];
#pragma unroll
    for (int i = 0; i < 32; i++) acc[i >> 4][(i >> 2) & 3][i & 3] = 0.f;
    mbar_wait(sbase + F_BAR + w * 8, 0);
    TS(14);
#pragma unroll
    for (int s = 0; s < 8; s++) {
        uint32_t a[4][4];
#pragma unroll
        for (int j = 0; j < 4; j++) ldsm4t(a[j], sw[j] + s * 2048);
#pragma unroll
        for (int j = 0; j < 4; j++) mma16816(acc[s & 1][j], a[j], bf[s][0], bf[s][1]);
    }
#pragma unroll
    for (int j = 0; j < 4; j++) {
        const float v0 = (t & 2) ? acc[0][j][2] + acc[1][j][2] : acc[0][j][0] + acc[1][j][0];
        const float v1 = (t & 2) ? acc[0][j][3] + acc[1][j][3] : acc[0][j][1] + acc[1][j][1];
        asm volatile("st.async.weak.shared::cluster.mbarrier::complete_tx::bytes.v2.b32 [%0], {%1,%2}, [%3];"
                     ::"r"(rdst[j]), "r"(__float_as_uint(v0)), "r"(__float_as_uint(v1)), "r"(rbar[j]) : "memory");
    }
}
__device__ __forceinline__ void fill_issue_sum(const Params& p, uint32_t sbase, int c, int rank, uint64_t pol) {
    const int lane = threadIdx.x & 31;
    if (lane == 0) {
        unsigned n = 0;
        while (ld_acquire_cta_shared(sbase + M_HELP + 36) < 16) { __nanosleep(500); if (++n > SPIN_LIMIT) __trap(); }
        asm volatile("prefetch.tensormap [%0];" ::"l"(&p.tm_wf) : "memory");
        uint32_t t0;
        while ((t0 = ld_acquire_cta_shared(sbase + M_HELP + 28)) == 0) { __nanosleep(100); if (++n > SPIN_LIMIT) __trap(); }
        while ((int)((uint32_t)clock() - t0) < 0) {}
#pragma unroll 1
        for (int w = 0; w < 4; w++) {
            mbar_expect_tx(sbase + F_BAR + w * 8, 16384);
            tma3d(sbase + F_W + w * 16384, &p.tm_wf, 0, (rank * 4 + w) * 128, c, sbase + F_BAR + w * 8, pol);
        }
    }
    __syncwarp();
    TS(16);
    __nv_bfloat16* dst = p.out + (lane >> 3) * (2 * DM) + DM + c * 64 + rank * 8 + (lane & 7);
    const uint32_t src = sbase + F_RECV + (lane >> 3) * 1024 + (lane & 7) * 16;
    mbar_wait_cluster(sbase + F_BAR + 32, 0);
    float4 x[8];
#pragma unroll
    for (int i = 0; i < 8; i++)
        asm volatile("ld.shared.v4.f32 {%0,%1,%2,%3}, [%4];" : "=f"(x[i].x), "=f"(x[i].y), "=f"(x[i].z), "=f"(x[i].w) : "r"(src + i * 128) : "memory");
#pragma unroll
    for (int m = 1; m < 8; m <<= 1)
#pragma unroll
        for (int i = 0; i < 8; i += 2 * m) { x[i].x += x[i + m].x; x[i].y += x[i + m].y; x[i].z += x[i + m].z; x[i].w += x[i + m].w; }
    const bool up = lane & 16, od = lane & 8;
    const float a = (up ? x[0].z : x[0].x) + __shfl_xor_sync(~0u, up ? x[0].x : x[0].z, 16);
    const float b = (up ? x[0].w : x[0].y) + __shfl_xor_sync(~0u, up ? x[0].y : x[0].w, 16);
    const float v = (od ? b : a) + __shfl_xor_sync(~0u, od ? a : b, 8);
    *dst = __float2bfloat16_rn(v);
    TS(15);
}

constexpr int BS_WUK = 5, BS_Q = 9, BS_CKV = 11, BS_PART = 27, BS_WUV = 29, BS_END = 33;

__device__ __noinline__ void b_issue(const Params& p, int n, int bi, uint32_t sbase, uint64_t pol) {
    if (n >= BS_END || (n >= BS_Q && n < BS_CKV) || (n >= BS_PART && n < BS_WUV)) return;
    const uint32_t bar = sbase + M_BAR + (NSLOT + n % BRING) * 8;
    const CUtensorMap* tm;
    int row, panel = 2 * bi;
    if (n < BS_WUK) { tm = &p.tm_wq; row = n * 128; }
    else if (n < BS_Q) { tm = &p.tm_wuk; row = (n - BS_WUK) * 128; }
    else if (n < BS_PART) {
        tm = &p.tm_ckv; panel = 0;
        row = (bi >> 3) * SK + ((n - BS_CKV) * 8 + (bi & 7)) * 32;
    }
    else { tm = &p.tm_wuv; row = (n - BS_WUV) * 128; }
    mbar_expect_tx(bar, n == 0 ? 32768 + 4 * 1152 : 32768);
    tma3d(sbase + (n % BRING) * SLOT, tm, 0, row, panel, bar, pol);
}
__device__ __forceinline__ void b_issue_xchg(int n, const void* src, uint32_t sbase, uint64_t pol) {
    asm volatile("fence.proxy.async;" ::: "memory");
#pragma unroll
    for (int i = 0; i < 2; i++) {
        const uint32_t bar = sbase + M_BAR + (NSLOT + (n + i) % BRING) * 8;
        mbar_expect_tx(bar, 32768);
        bulk_load(sbase + ((n + i) % BRING) * SLOT, reinterpret_cast<const char*>(src) + i * 32768, 32768, bar, pol);
    }
}
__device__ __forceinline__ void b_wait(int n, uint32_t sbase) {
    mbar_wait(sbase + M_BAR + (NSLOT + n % BRING) * 8, (n / BRING) & 1);
}

__device__ __noinline__ void b_gemm(const Params& p, uint32_t sbase, int n0, int n1, int ktot, uint32_t xh, uint32_t xl, int pitch,
                                    int bi, uint64_t pol) {
    const int tid = threadIdx.x, warp = tid >> 5, lane = tid & 31, g = lane >> 2, t = lane & 3;
    const uint32_t woff = (warp >> 2) * 16384 + (lane & 15) * 128 + ((((warp & 3) * 2 + (lane >> 4)) ^ (lane & 7)) * 16);
    const uint32_t xoff = (g & 3) * pitch + t * 4;
    float acc[2][4];
#pragma unroll
    for (int i = 0; i < 8; i++) acc[i >> 2][i & 3] = 0.f;
#pragma unroll 1
    for (int n = n0; n < n1; n++) {
        b_wait(n, sbase);
        const uint32_t slot = sbase + (n % BRING) * SLOT + woff;
        const int k0 = (n - n0) * 128;
        const int ns = min(8, (ktot - k0) >> 4);
#pragma unroll 2
        for (int s = 0; s < ns; s++) {
            uint32_t a[4], w[4];
            const uint32_t xo = xoff + (k0 + 16 * s) * 2;
            a[0] = lds32(xh + xo); a[2] = lds32(xh + xo + 16);
            a[1] = xl ? lds32(xl + xo) : 0u; a[3] = xl ? lds32(xl + xo + 16) : 0u;
            ldsm4t(w, slot + s * 2048);
            mma16816(acc[0], a, w[0], w[1]);
            mma16816(acc[1], a, w[2], w[3]);
        }
        __syncthreads();
        if (tid == 0) b_issue(p, n + BD, bi, sbase, pol);
    }
    if (g < 4) {
#pragma unroll
        for (int j = 0; j < 2; j++)
            asm volatile("st.shared.u32 [%0], %1;" ::"r"(sbase + M_QB + g * QP + (warp * 16 + j * 8 + t * 2) * 2),
                         "r"(pack_bf16(acc[j][0] + acc[j][2], acc[j][1] + acc[j][3])) : "memory");
    }
    __syncthreads();
}

__device__ __forceinline__ void b_exchange(unsigned* c, int n, const void* src, uint32_t sbase, uint64_t pol) {
    TS(n == BS_Q ? 24 : 28);
    __syncthreads();
    if (threadIdx.x == 0) {
        TS(n == BS_Q ? 25 : 29);
        fence_gpu();
        TS(n == BS_Q ? 26 : 30);
        red_add_u32(c, 1u);
        wait_count(c, NBCTA);
        TS(n == BS_Q ? 27 : 31);
        b_issue_xchg(n, src, sbase, pol);
    }
}

template <bool CLU>
__device__ __noinline__ void b_chain(const Params& p, char* smem, uint32_t sbase, int bi, unsigned epoch, uint64_t pol) {
    const int tid = threadIdx.x, warp = tid >> 5, lane = tid & 31, g = lane >> 2, t = lane & 3;
    unsigned (*ctl)[32] = g_ctl[epoch & 1];
    float* red = reinterpret_cast<float*>(smem + 5 * SLOT);
    __syncthreads();
    b_gemm(p, sbase, 0, BS_WUK, DM, sbase + M_XB, 0, XP, bi, pol);
    TS(6);
    {
        uint32_t Q[16];
#pragma unroll
        for (int c = 0; c < 16; c++) Q[c] = lds32(sbase + M_QB + (g & 3) * QP + c * 16 + t * 4);
        float* qa = reinterpret_cast<float*>(smem + M_QA);
#pragma unroll 1
        for (int n = BS_WUK; n < BS_Q; n++) {
            b_wait(n, sbase);
            const uint32_t base = sbase + (n % BRING) * SLOT + (warp * 16 + (lane & 15)) * 128;
            float d[2][4];
#pragma unroll
            for (int i = 0; i < 8; i++) d[i >> 2][i & 3] = 0.f;
#pragma unroll
            for (int s = 0; s < 8; s++) {
                uint32_t a[4];
                ldsm4(a, base + (s >> 2) * 16384 + (((2 * (s & 3) + (lane >> 4)) ^ (lane & 7)) * 16));
                mma16816(d[s & 1], a, Q[2 * s], Q[2 * s + 1]);
            }
            const int c = (n - BS_WUK) * 128 + warp * 16 + g + 8 * (t >> 1);
            qa[(2 * (t & 1)) * 512 + c] = (t & 2) ? d[0][2] + d[1][2] : d[0][0] + d[1][0];
            qa[(2 * (t & 1) + 1) * 512 + c] = (t & 2) ? d[0][3] + d[1][3] : d[0][1] + d[1][1];
            __syncthreads();
            if (tid == 0) b_issue(p, n + BD, bi, sbase, pol);
        }
#pragma unroll 1
        for (int r = 0; r < 2; r++) {
            const int id = tid + r * 256;
            const int b = id >> 7, c0 = ((id >> 2) & 31) * 16 + (id & 3) * 2;
            const float2 u0 = *reinterpret_cast<const float2*>(qa + b * 512 + c0);
            const float2 u1 = *reinterpret_cast<const float2*>(qa + b * 512 + c0 + 8);
            const uint32_t h0 = pack_bf16(u0.x, u0.y), h1 = pack_bf16(u1.x, u1.y);
            const uint32_t l0 = pack_bf16(u0.x - bf_lo(h0), u0.y - bf_hi(h0)), l1 = pack_bf16(u1.x - bf_lo(h1), u1.y - bf_hi(h1));
            g_qabs[((id >> 2) * 4 + (bi >> 3)) * 32 + (bi & 7) * 4 + (id & 3)] = make_uint4(h0, l0, h1, l1);
        }
    }
    b_exchange(&ctl[C_BBAR][0], BS_Q, &g_qabs[(bi >> 3) * 4096], sbase, pol);
    {
        uint32_t qf[4][4][4];
        b_wait(BS_Q + (warp >> 2), sbase);
        TS(7);
        {
            const uint4* qs = reinterpret_cast<const uint4*>(smem + ((BS_Q + (warp >> 2)) % BRING) * SLOT) + (warp & 3) * 512 + lane;
#pragma unroll
            for (int s = 0; s < 4; s++)
#pragma unroll
                for (int i = 0; i < 4; i++) {
                    const uint4 v = qs[(s * 4 + i) * 32];
                    qf[i][s][0] = v.x; qf[i][s][1] = v.y; qf[i][s][2] = v.z; qf[i][s][3] = v.w;
                }
        }
        __syncthreads();
        if (tid == 0) { b_issue(p, BS_Q + BD, bi, sbase, pol); b_issue(p, BS_Q + 1 + BD, bi, sbase, pol); }
        float acc[2][8][4];
#pragma unroll
        for (int i = 0; i < 2; i++)
#pragma unroll
            for (int j = 0; j < 8; j++) { acc[i][j][0] = acc[i][j][1] = acc[i][j][2] = acc[i][j][3] = 0.f; }
        float mrun = -INFINITY, lrun = 0.f;
        const int head = tid >> 3, kq = tid & 7;
        float* alpha = reinterpret_cast<float*>(smem + M_ALPHA);
        for (int n = BS_CKV; n < BS_PART; n++) {
            b_wait(n, sbase);
            const uint32_t slot = sbase + (n % BRING) * SLOT;
            float sc[4][4][4];
#pragma unroll
            for (int i = 0; i < 4; i++)
#pragma unroll
                for (int j = 0; j < 4; j++) { sc[i][j][0] = sc[i][j][1] = sc[i][j][2] = sc[i][j][3] = 0.f; }
#pragma unroll
            for (int j = 0; j < 4; j++)
#pragma unroll
                for (int sp = 0; sp < 2; sp++) {
                    uint32_t bf[4];
                    ldsm4(bf, slot + warp * 4096 + (8 * j + (lane & 7)) * 128 + (((4 * sp + (lane >> 3)) ^ (lane & 7)) * 16));
#pragma unroll
                    for (int i = 0; i < 4; i++) {
                        mma16816(sc[i][j], qf[i][2 * sp], bf[0], bf[1]);
                        mma16816(sc[i][j], qf[i][2 * sp + 1], bf[2], bf[3]);
                    }
                }
#pragma unroll
            for (int i = 0; i < 4; i++)
#pragma unroll
                for (int j = 0; j < 4; j++)
                    *reinterpret_cast<float2*>(red + warp * 1024 + (8 * i + g) * 32 + ((8 * j) ^ (8 * (g & 3))) + 2 * t) =
                        make_float2(sc[i][j][0] + sc[i][j][2], sc[i][j][1] + sc[i][j][3]);
            __syncthreads();
            if (tid == 0 && n > BS_CKV) b_issue(p, n - 1 + BD, bi, sbase, pol);
            {
                float4 s = make_float4(0.f, 0.f, 0.f, 0.f);
#pragma unroll
                for (int w = 0; w < 8; w++) {
                    const float4 v = *reinterpret_cast<const float4*>(red + w * 1024 + head * 32 + ((4 * kq) ^ (8 * (head & 3))));
                    s.x += v.x; s.y += v.y; s.z += v.z; s.w += v.w;
                }
                const uint32_t r0 = pack_bf16(s.x, s.y), r1 = pack_bf16(s.z, s.w);
                const uint32_t s0 = pack_bf16(bf_lo(r0) * SCALE, bf_hi(r0) * SCALE);
                const uint32_t s1 = pack_bf16(bf_lo(r1) * SCALE, bf_hi(r1) * SCALE);
                const float f0 = bf_lo(s0), f1 = bf_hi(s0), f2 = bf_lo(s1), f3 = bf_hi(s1);
                float mx = fmaxf(fmaxf(f0, f1), fmaxf(f2, f3));
                mx = fmaxf(mx, __shfl_xor_sync(~0u, mx, 1));
                mx = fmaxf(mx, __shfl_xor_sync(~0u, mx, 2));
                mx = fmaxf(mx, __shfl_xor_sync(~0u, mx, 4));
                const float mnew = fmaxf(mrun, mx);
                const float al = expsub(mrun, mnew);
                const float p0 = expsub(f0, mnew), p1 = expsub(f1, mnew), p2 = expsub(f2, mnew), p3 = expsub(f3, mnew);
                lrun = lrun * al + ((p0 + p1) + (p2 + p3));
                mrun = mnew;
                *reinterpret_cast<uint2*>(smem + M_P + head * 80 + kq * 8) = make_uint2(pack_bf16(p0, p1), pack_bf16(p2, p3));
                if (kq == 0) alpha[head] = al;
            }
            __syncthreads();
            {
                uint32_t pf[2][2][4];
#pragma unroll
                for (int i = 0; i < 2; i++)
#pragma unroll
                    for (int ks = 0; ks < 2; ks++)
                        ldsm4(pf[i][ks], sbase + M_P + (16 * i + (lane & 15)) * 80 + (16 * ks + 8 * (lane >> 4)) * 2);
#pragma unroll
                for (int i = 0; i < 2; i++) {
                    const float a0 = alpha[16 * i + g], a1 = alpha[16 * i + 8 + g];
#pragma unroll
                    for (int j = 0; j < 8; j++) { acc[i][j][0] *= a0; acc[i][j][1] *= a0; acc[i][j][2] *= a1; acc[i][j][3] *= a1; }
                }
#pragma unroll
                for (int j = 0; j < 8; j++) {
                    uint32_t bf[4];
                    ldsm4t(bf, slot + warp * 4096 + lane * 128 + ((j ^ (lane & 7)) * 16));
#pragma unroll
                    for (int i = 0; i < 2; i++) {
                        mma16816(acc[i][j], pf[i][0], bf[0], bf[1]);
                        mma16816(acc[i][j], pf[i][1], bf[2], bf[3]);
                    }
                }
            }
        }
        __syncthreads();
        if (tid == 0) b_issue(p, BS_PART - 1 + BD, bi, sbase, pol);
        lrun += __shfl_xor_sync(~0u, lrun, 1);
        lrun += __shfl_xor_sync(~0u, lrun, 2);
        lrun += __shfl_xor_sync(~0u, lrun, 4);
        if (kq == 0) g_bml[head * NBCTA + bi] = make_float2(mrun, lrun);
#pragma unroll
        for (int i = 0; i < 2; i++)
#pragma unroll
            for (int j = 0; j < 8; j++) {
                g_bpart[((16 * i + g) * NBCTA + bi) * 256 + warp * 32 + j * 4 + t] = make_float2(acc[i][j][0], acc[i][j][1]);
                g_bpart[((16 * i + 8 + g) * NBCTA + bi) * 256 + warp * 32 + j * 4 + t] = make_float2(acc[i][j][2], acc[i][j][3]);
            }
    }
#pragma unroll 1
    for (int i = tid; i < NH * 36 && !(CLU && FILL); i += 256) g_outb[bi * NH * 36 + i] = make_uint4(0u, epoch, 0u, epoch);
    b_exchange(&ctl[C_BBAR + 1][0], BS_PART, &g_bpart[bi * NBCTA * 256], sbase, pol);
    {
        float* omega = reinterpret_cast<float*>(smem + M_OMEGA);
        if (warp == 0) {
            __syncwarp();
            const uint2 ml = ld_relaxed8(&g_bml[bi * NBCTA + lane]);
            const float ms = __uint_as_float(ml.x);
            float m = ms;
            m = fmaxf(m, __shfl_xor_sync(~0u, m, 1));
            m = fmaxf(m, __shfl_xor_sync(~0u, m, 2));
            m = fmaxf(m, __shfl_xor_sync(~0u, m, 4));
            const float w = expsub(ms, m);
            float l = w * __uint_as_float(ml.y);
            l += __shfl_xor_sync(~0u, l, 1);
            l += __shfl_xor_sync(~0u, l, 2);
            l += __shfl_xor_sync(~0u, l, 4);
            omega[lane] = w / l;
        }
        __syncthreads();
        b_wait(BS_PART, sbase);
        b_wait(BS_PART + 1, sbase);
#pragma unroll 1
        for (int b = 0; b < 4; b++) {
            const float2* ps = reinterpret_cast<const float2*>(smem + ((BS_PART + (b >> 1)) % BRING) * SLOT) + (b & 1) * 2048 + tid;
            float c0 = 0.f, c1 = 0.f;
#pragma unroll
            for (int s = 0; s < 8; s++) {
                const float w = omega[b * 8 + s];
                const float2 v = ps[s * 256];
                c0 = fmaf(w, v.x, c0);
                c1 = fmaf(w, v.y, c1);
            }
            const uint32_t hi = pack_bf16(c0, c1);
            *reinterpret_cast<uint32_t*>(smem + M_CH + b * CP + tid * 4) = hi;
            *reinterpret_cast<uint32_t*>(smem + M_CL + b * CP + tid * 4) = pack_bf16(c0 - bf_lo(hi), c1 - bf_hi(hi));
        }
        __syncthreads();
        if (tid == 0) { b_issue(p, BS_PART + BD, bi, sbase, pol); b_issue(p, BS_PART + 1 + BD, bi, sbase, pol); }
    }
    b_gemm(p, sbase, BS_WUV, BS_END, 512, sbase + M_CH, sbase + M_CL, CP, bi, pol);
    TS(12);
    if (CLU && FILL) {
        if (tid < 128) {
            const uint32_t xo = sbase + M_QB + (g & 3) * QP + (tid >> 4) * 32 + t * 4;
            st_tagged2(&g_ctx[bi * 128 + tid], __uint_as_float(lds32(xo)), __uint_as_float(lds32(xo + 16)), epoch + 1);
        }
        return;
    }
    if (tid == 0) {
#pragma unroll 1
        for (int i = 0; i < 4; i++) {
            mbar_expect_tx(sbase + M_BAR + i * 8, 36864);
            tma3d(sbase + i * 36864, &p.tm_wo, 0, bi * 128 + i * 32, 0, sbase + M_BAR + i * 8, pol);
        }
    }
    TS(8);
    {
        float acc[9][4];
#pragma unroll
        for (int j = 0; j < 9; j++) { acc[j][0] = acc[j][1] = acc[j][2] = acc[j][3] = 0.f; }
#pragma unroll 1
        for (int i = 0; i < 4; i++) {
            const uint32_t xo = sbase + M_QB + (g & 3) * QP + i * 64 + t * 4;
            const uint32_t a0[4] = {lds32(xo), 0u, lds32(xo + 16), 0u}, a1[4] = {lds32(xo + 32), 0u, lds32(xo + 48), 0u};
            mbar_wait(sbase + M_BAR + i * 8, 0);
#pragma unroll
            for (int j = 0; j < 9; j++) {
                const int nt = warp * 9 + j;
                uint32_t w[4];
                ldsm4t(w, sbase + i * 36864 + (nt >> 3) * 4096 + lane * 128 + (((nt & 7) ^ (lane & 7)) * 16));
                mma16816(acc[j], a0, w[0], w[1]);
                mma16816(acc[j], a1, w[2], w[3]);
            }
        }
        if (g < 4) {
#pragma unroll
            for (int j = 0; j < 9; j++) {
                const int c2 = (warp * 9 + j) * 4 + t;
                st_tagged2(&g_outb[((c2 / 9) * NH + bi) * 36 + g * 9 + c2 % 9], acc[j][0], acc[j][1], epoch + 1);
            }
        }
    }
    TS(9);
    {
        const uint4* src = g_outb + (bi * NH + (tid >> 3)) * 36 + (tid & 7);
        float2* part = reinterpret_cast<float2*>(red);
        unsigned n = 0;
        while (true) {
            ulonglong2 v[5];
            bool ok = true;
#pragma unroll
            for (int i = 0; i < 5; i++)
                if (i < 4 || (tid & 7) < 4) v[i] = ld_tagged2(src + i * 8);
#pragma unroll
            for (int i = 0; i < 5; i++)
                if (i < 4 || (tid & 7) < 4) {
                    ok = ok && (unsigned)(v[i].x >> 32) == epoch + 1 && (unsigned)(v[i].y >> 32) == epoch + 1;
                    part[(tid >> 3) * 36 + (tid & 7) + i * 8] = make_float2(__uint_as_float((unsigned)v[i].x), __uint_as_float((unsigned)v[i].y));
                }
            if (ok) break;
            __nanosleep(400);
            if (++n > SPIN_LIMIT) __trap();
        }
        __syncthreads();
        if (tid < 36) {
            float s0 = 0.f, s1 = 0.f;
#pragma unroll 8
            for (int h = 0; h < NH; h++) { const float2 v = part[h * 36 + tid]; s0 += v.x; s1 += v.y; }
            *reinterpret_cast<uint32_t*>(p.out + (tid / 9) * 2 * DM + DM + bi * 18 + (tid % 9) * 2) = pack_bf16(s0, s1);
        }
    }
    TS(10);
}

template <bool CLU>
__global__ void __launch_bounds__(256, 1) fused_decode_kernel(const __grid_constant__ Params p) {
    constexpr int HL = CLU ? NH - NDIR : NH;
    extern __shared__ __align__(1024) char smem_raw[];
    const uint32_t sbase = (smem_u32(smem_raw) + 1023u) & ~1023u;
    char* smem = smem_raw + (sbase - smem_u32(smem_raw));
    const int tid = threadIdx.x, warp = tid >> 5, lane = tid & 31;
    const int blk = blockIdx.x;
    const bool isB = CLU ? blk < NBCTA : (blk & 3) == 0 && (blk >> 2) < NBCTA;
    const int bi = CLU ? blk : blk >> 2;
    const int nb = CLU ? blk - NBCTA : blk - min(NBCTA, (blk + 3) >> 2);
    const int nnb = gridDim.x - NBCTA;
    const int nstatic = nnb * (NW + XW);
    uint64_t pol;
    asm volatile("createpolicy.fractional.L2::evict_first.b64 %0, 1.0;" : "=l"(pol));
    const uint32_t wbar = sbase + M_BAR + warp * 8, wslot = sbase + warp * SLOT;
    const int u0 = warp * nnb + nb;
    const bool hold = ((blk >> 2) >> KMIN << KMIN) * 4 * UPP < nstatic;
    const uint32_t jbar = sbase + M_BAR + (NSLOT + BRING) * 8;
    if (warp == 7) {
        if (lane == 0 && blk < 128) {
            mbar_init(jbar, 1);
            asm volatile("fence.mbarrier_init.release.cluster;" ::: "memory");
            uint64_t poln;
            asm volatile("createpolicy.fractional.L2::evict_normal.b64 %0, 1.0;" : "=l"(poln));
            mbar_expect_tx(jbar, 36864 + 4 * 1152);
            tma3d(sbase + J0W, &p.tm_j0, blk * 32, 0, 0, jbar, poln);
            bulk_load(sbase + M_XA, p.xa, 4608, jbar, poln);
        }
        if (lane < 16) reinterpret_cast<unsigned*>(smem + M_HELP)[lane] = 0;
        __syncwarp();
        if (!isB) asm volatile("bar.arrive 2, %0;" ::"n"(32 * (NW + XW + 1)) : "memory");
    }
    if (warp < 4 && lane == 0) {
        mbar_init(wbar, 1);
        if (CLU && FILL && warp == 3 && !isB) {
#pragma unroll
            for (int i = 0; i < 5; i++) mbar_init(sbase + F_BAR + i * 8, 1);
            mbar_expect_tx(sbase + F_BAR + 32, 4096);
        }
        asm volatile("fence.mbarrier_init.release.cluster;" ::: "memory");
        if (warp < NEARLY && !isB && !hold) {
            mbar_expect_tx(wbar, TILE_BYTES);
            bulk_load(wslot, block_src(p.kc, unit_block<HL>(u0)), TILE_BYTES, wbar, pol);
        }
    }
    unsigned epoch = 0;
    if (lane == 0) epoch = ld_relaxed4(&g_epoch);
    TS(0);
    if (CLU && FILL && !isB) asm volatile("barrier.cluster.arrive.relaxed.aligned;" ::: "memory");
    if ((warp >> 1) == 2 && blk < 128) st_relaxed64(&g_qll[((tid - 128) >> 4) * 2048 + blk * 16 + (tid & 15)], 0ull);
    if (isB || warp >= NW + XW) epoch = __shfl_sync(~0u, epoch, 0);
    if (isB && warp == 3) asm volatile("bar.sync 1, 160;" ::: "memory");
    if (isB && tid == 96) {
#pragma unroll 1
        for (int i = 0; i < BRING; i++) mbar_init(sbase + M_BAR + (NSLOT + i) * 8, 1);
        asm volatile("fence.mbarrier_init.release.cluster;" ::: "memory");
        if (hold) { unsigned n = 0; while (ld_acquire_cta_shared(sbase + M_HELP + 24) < 2) { if (++n > (SPIN_LIMIT << 4)) __trap(); } }
#pragma unroll 1
        for (int b = 0; b < 4; b++) bulk_load(sbase + M_XB + b * XP, p.xb + b * DM, 1152, sbase + M_BAR + NSLOT * 8, pol);
#pragma unroll 1
        for (int n = 0; n < BD; n++) b_issue(p, n, bi, sbase, pol);
    }
    if (warp >= 4 && blk < 128) {
        const int g = lane >> 2, t = lane & 3, j = tid - 128;
        asm volatile("bar.sync 1, %0;" ::"r"(isB ? 160 : 128) : "memory");
#pragma unroll 1
        for (int sl = blk, ph = 0;; sl += 128 - gridDim.x, ph = 1) {
        mbar_wait(jbar, ph);
        TS(13);
        float acc[4][4];
#pragma unroll
        for (int i = 0; i < 16; i++) acc[i >> 2][i & 3] = 0.f;
        const uint32_t wa = sbase + J0W + ((warp - 4) * 144 + (lane & 15)) * 64;
        const uint32_t sw = (lane >> 1) & 3, xa = sbase + M_XA + (g & 3) * 1152 + (warp - 4) * 288 + t * 4;
#pragma unroll 3
        for (int s = 0; s < 9; s++) {
            const uint32_t a[4] = {lds32(xa + s * 32), 0u, lds32(xa + s * 32 + 16), 0u};
            uint32_t w0[4], w1[4];
            ldsm4t(w0, wa + s * 1024 + (((lane >> 4) ^ sw) * 16));
            ldsm4t(w1, wa + s * 1024 + (((2 + (lane >> 4)) ^ sw) * 16));
            mma16816(acc[0], a, w0[0], w0[1]);
            mma16816(acc[1], a, w0[2], w0[3]);
            mma16816(acc[2], a, w1[0], w1[1]);
            mma16816(acc[3], a, w1[2], w1[3]);
        }
        float2* j0 = reinterpret_cast<float2*>(smem + M_J0);
        if (g < 4) {
#pragma unroll
            for (int i = 0; i < 4; i++) j0[(warp - 4) * 64 + g * 16 + i * 4 + t] = make_float2(acc[i][0], acc[i][1]);
        }
        asm volatile("bar.sync 1, 128;" ::: "memory");
        const bool again = sl == blk && blk + 128 - (int)gridDim.x >= (int)gridDim.x;
        if (again && tid == 224) {
            mbar_expect_tx(jbar, 36864);
            tma3d(sbase + J0W, &p.tm_j0, (blk + 128 - gridDim.x) * 32, 0, 0, jbar, pol);
        }
        if (warp < 6) {
            const float2 v0 = j0[j], v1 = j0[64 + j], v2 = j0[128 + j], v3 = j0[192 + j];
            st_relaxed64(&g_qll[(j >> 4) * 2048 + sl * 16 + (j & 15)],
                         (unsigned long long)pack_bf16((v0.x + v1.x) + (v2.x + v3.x), (v0.y + v1.y) + (v2.y + v3.y)) |
                             ((unsigned long long)(epoch + 1) << 32));
            __syncwarp();
            if (lane == 0) asm volatile("red.relaxed.cta.shared::cta.add.u32 [%0], 1;" ::"r"(sbase + M_HELP + 24) : "memory");
        } else if (warp == 7) {
            if (blk < C_LINES) g_ctl[(epoch & 1) ^ 1][blk][lane] = 0;
        }
        TS(1);
        if (!again) break;
        asm volatile("bar.sync 1, 128;" ::: "memory");
        }
    }
    if (isB) {
        b_chain<CLU>(p, smem, sbase, bi, epoch, pol);
        if (CLU) final_phase<HL>(p, sbase, blk, epoch, pol);
        return;
    }
    if (warp < NW + XW) {
        a_worker<HL>(p, u0, warp >= NW + ((nb & 3) < (CLU ? X3C : X3) ? 1 : 0), warp < NEARLY && !hold, hold, nstatic, wslot, wbar, sbase + M_HELP, epoch, pol);
        if (CLU && FILL && warp == 3 && nb < NFIN) fill_issue_sum(p, sbase, nb >> 3, nb & 7, pol);
        return;
    } else if (warp == 7) {
#pragma unroll 1
        for (int i = nb; i < 4 * HL; i += nnb) g_oacc[i * 32 + lane] = make_float4(0.f, 0.f, 0.f, 0.f);
        if (nb < NREP * NH) g_vdone[nb][lane] = 0;
        if (CLU) {
            const float unset = __uint_as_float(UNSET);
#pragma unroll 1
            for (int i = nb; i < NDIR * 4 * UPP; i += nnb) g_part[i * 32 + lane] = make_float4(unset, unset, unset, unset);
            if (nb * 32 + lane < 4 * DM / 2) g_base[nb * 32 + lane] = make_float2(unset, unset);
        }
        __syncwarp();
        k_helper(sbase + M_HELP, epoch);
        if (nb == 0 && lane == 0) g_epoch = epoch + 1;
        __syncwarp();
        if (CLU && FILL && nb < NFIN) fill_ctx(sbase, nb & 7, epoch + 1);
    } else if (warp == 6 && nb < NFIN) {
        finisher<HL>(p, sbase, nb);
        TS(4);
    } else if (warp >= 6 - NPOLL && nb < NFIN) {
        v_poller<HL>(sbase, nb, warp - (6 - NPOLL));
    }
    if (CLU && FILL && nb < NFIN) fill_piece(sbase, nb & 7, warp - 4);
}

}

typedef CUresult (*EncodeFn)(CUtensorMap*, CUtensorMapDataType, cuuint32_t, void*, const cuuint64_t*, const cuuint64_t*,
                             const cuuint32_t*, const cuuint32_t*, CUtensorMapInterleave, CUtensorMapSwizzle,
                             CUtensorMapL2promotion, CUtensorMapFloatOOBfill);

extern "C" void kernel_launch(void* const* d_in, const int* in_sizes, int n_in, void* d_out, int out_size) {
    (void)in_sizes; (void)n_in; (void)out_size;
    static int nsm = 0, ncl = 0;
    static EncodeFn encode = nullptr;
    cudaLaunchConfig_t cfg = {};
    cudaLaunchAttribute at[1];
    at[0].id = cudaLaunchAttributeClusterDimension;
    at[0].val.clusterDim.x = 8; at[0].val.clusterDim.y = 1; at[0].val.clusterDim.z = 1;
    cfg.blockDim = dim3(256); cfg.dynamicSmemBytes = SMEM_BYTES; cfg.stream = cudaStreamPerThread; cfg.attrs = at; cfg.numAttrs = 1;
    if (nsm == 0) {
        int dev = 0;
        cudaGetDevice(&dev);
        cudaDeviceGetAttribute(&nsm, cudaDevAttrMultiProcessorCount, dev);
        cudaFuncSetAttribute(fused_decode_kernel<false>, cudaFuncAttributeMaxDynamicSharedMemorySize, SMEM_BYTES);
        cudaFuncSetAttribute(fused_decode_kernel<true>, cudaFuncAttributeMaxDynamicSharedMemorySize, SMEM_BYTES);
        cfg.gridDim = dim3(128);
        if (cudaOccupancyMaxActiveClusters(&ncl, fused_decode_kernel<true>, &cfg) != cudaSuccess) { ncl = 0; (void)cudaGetLastError(); }
        if (ncl > MINCL) ncl = MINCL;
        void* fn = nullptr;
        cudaDriverEntryPointQueryResult qr;
        cudaGetDriverEntryPoint("cuTensorMapEncodeTiled", &fn, cudaEnableDefault, &qr);
        encode = (EncodeFn)fn;
    }
    Params p;
    auto panels = [&](CUtensorMap* tm, void* ptr, int rows, int cols, int box_rows, int box_panels) {
        const cuuint64_t gd[3] = {64, (cuuint64_t)rows, (cuuint64_t)(cols / 64)}, gs[2] = {(cuuint64_t)cols * 2, 128};
        const cuuint32_t box[3] = {64, (cuuint32_t)box_rows, (cuuint32_t)box_panels}, es[3] = {1, 1, 1};
        encode(tm, CU_TENSOR_MAP_DATA_TYPE_BFLOAT16, 3, ptr, gd, gs, box, es, CU_TENSOR_MAP_INTERLEAVE_NONE,
               CU_TENSOR_MAP_SWIZZLE_128B, CU_TENSOR_MAP_L2_PROMOTION_L2_256B, CU_TENSOR_MAP_FLOAT_OOB_FILL_NONE);
    };
    panels(&p.tm_wq, d_in[7], DM, 4096, 128, 2);
    panels(&p.tm_wuk, d_in[8], 512, 4096, 128, 2);
    panels(&p.tm_wuv, d_in[9], 512, 4096, 128, 2);
    panels(&p.tm_wo, d_in[10], 4096, DM, 32, 9);
    panels(&p.tm_wf, d_in[10], 4096, DM, 128, 1);
    panels(&p.tm_ckv, d_in[6], 4 * SK, 512, 32, 8);
    {
        const cuuint64_t gd[3] = {4096, 192, 3}, gs[2] = {8192, 192 * 8192};
        const cuuint32_t box[3] = {32, 192, 3}, es[3] = {1, 1, 1};
        encode(&p.tm_j0, CU_TENSOR_MAP_DATA_TYPE_BFLOAT16, 3, d_in[3], gd, gs, box, es, CU_TENSOR_MAP_INTERLEAVE_NONE,
               CU_TENSOR_MAP_SWIZZLE_64B, CU_TENSOR_MAP_L2_PROMOTION_L2_128B, CU_TENSOR_MAP_FLOAT_OOB_FILL_NONE);
    }
    {
        const cuuint64_t gd[3] = {DM, 512, 8}, gs[2] = {8 * DM * 2, DM * 2};
        const cuuint32_t box[3] = {72, 16, 8}, es[3] = {1, 1, 1};
        encode(&p.tm_wl, CU_TENSOR_MAP_DATA_TYPE_BFLOAT16, 3, d_in[4], gd, gs, box, es, CU_TENSOR_MAP_INTERLEAVE_NONE,
               CU_TENSOR_MAP_SWIZZLE_NONE, CU_TENSOR_MAP_L2_PROMOTION_L2_128B, CU_TENSOR_MAP_FLOAT_OOB_FILL_NONE);
    }
    p.xa = (const __nv_bfloat16*)d_in[0];
    p.kc = (const __nv_bfloat16*)d_in[1];
    p.vc = (const __nv_bfloat16*)d_in[2];
    p.wo = (const __nv_bfloat16*)d_in[4];
    p.xb = (const __nv_bfloat16*)d_in[5];
    p.out = (__nv_bfloat16*)d_out;
    if (ncl >= MINCL) {
        cfg.gridDim = dim3(8 * ncl);
        cudaLaunchKernelEx(&cfg, fused_decode_kernel<true>, p);
    } else {
        fused_decode_kernel<false><<<nsm, 256, SMEM_BYTES, cudaStreamPerThread>>>(p);
    }
}
```

```cpp
#include <cuda_runtime.h>
#include <cuda.h>
#include <cuda_bf16.h>
#include <stdint.h>

namespace {

constexpr int NH = 32, SK = 4096, DM = 576;
constexpr int KEYS = 128;
constexpr int UPP = SK / KEYS;
constexpr int NUK = 4 * NH * UPP;
constexpr int TILE_BYTES = KEYS * 256;
#define NWORK 2
constexpr int NW = NWORK;
constexpr int NBCTA = 32;
constexpr int MINCL = 15;
constexpr int NFIN = 72;
constexpr int SLOT = 32768;
constexpr int NSLOT = 6;
constexpr int BRING = 5;
constexpr int J0W = 5 * SLOT;
constexpr int MISC = NSLOT * SLOT + 4096;
constexpr int XP = 1168, CP = 1040, QP = 272;
constexpr int M_XA = MISC;
constexpr int M_XB = M_XA + 4 * XP;
constexpr int M_CH = M_XB + 4 * XP;
constexpr int M_CL = M_CH + 4 * CP;
constexpr int M_QB = M_CL + 4 * CP;
constexpr int M_QA = M_CH;
constexpr int M_J0 = M_QB + 4 * QP;
constexpr int M_P = M_J0 + 2048;
constexpr int M_ALPHA = M_P + 2560;
constexpr int M_OMEGA = M_ALPHA + 128;
constexpr int M_BAR = M_OMEGA + 128;
constexpr int M_HELP = M_BAR + 128;
#define NDIR 3
constexpr int L_W = 0;
constexpr int L_BF = L_W + NDIR * 18432 + 128;
constexpr int L_FLAG = L_BF + NDIR * 256;
constexpr int L_BAR = L_FLAG + 16;
constexpr int F_CTX = M_XB, F_RECV = M_CH, F_BAR = M_P, F_W = 3 * SLOT;
constexpr int SMEM_BYTES = M_HELP + 128 + 1024;
static_assert(L_BAR + 8 + NDIR * 8 <= 5 * SLOT && NDIR >= 2 && NDIR <= 3, "final phase layout");
static_assert(SMEM_BYTES <= 232448 && M_BAR % 8 == 0 && M_QA % 16 == 0 && M_P % 16 == 0, "smem layout");
#define XW 2
#define X3 1
#define X3C 2
#define NEARLY 2
#define BD 4
#define FPF 3
#define FSLEEP 800
#define VS0 24
#define GHEAD 23
#define FILL 1
#define FJ 235
#define FP 700
#define FB 128
#define FD 500
#define FR 128
#define FQ FP
#define FH 24
#define NPOLL 2
#define PGAP 200
static_assert(NH - NDIR >= VS0 && NDIR >= 2 && GHEAD < NH - NDIR, "direct heads");
static_assert(NW + XW <= 4 && NEARLY <= NW + XW && BD <= BRING, "slots 4 and 5 hold the finisher weights");
constexpr int KMIN = 2, KMAX = 4, VMIN = 0, VMAX = 4;
constexpr float SCALE = 0.08838834764831845f;
constexpr float LOG2E = 1.4426950408889634f;
constexpr unsigned SPIN_LIMIT = 1u << 24;

#define NREP 2
constexpr int C_QUEUE = 0, C_KDONE = 1, C_BBAR = 3, C_LINES = 5;
constexpr unsigned UNSET = 0xffffffffu;

struct Params {
    const __nv_bfloat16 *kc, *xa, *vc, *wo, *xb, *wob;
    __nv_bfloat16* out;
    CUtensorMap tm_j0;
    CUtensorMap tm_wq, tm_wuk, tm_ckv, tm_wuv, tm_wo;
    CUtensorMap tm_wl;
    CUtensorMap tm_wf;
};

__device__ unsigned g_epoch;
__device__ unsigned g_ctl[2][C_LINES][32];
__device__ uint2 g_qll[4 * 2048];
__device__ uint2 g_scores[128 * SK / 4];
__device__ float2 g_stats[128 * UPP];
__device__ float4 g_oacc[128 * 32];
__device__ unsigned g_vdone[NREP * NH][32];
__device__ float2 g_base[4 * DM / 2];
__device__ float4 g_part[NDIR * 4 * UPP * 32];
__device__ uint4 g_qabs[4 * 8 * 4 * 4 * 32];
__device__ float2 g_bpart[NBCTA * NH * 256];
__device__ float2 g_bml[NBCTA * NH];
__device__ uint4 g_ctx[NH * 128];
__device__ uint4 g_outb[NBCTA * NH * 36];

#define TS(i)
#define TSV(i, v)
#define LAND(i)
#define CLK(x)
#define ACC(a, x, y)

__device__ __forceinline__ uint32_t smem_u32(const void* p) { return (uint32_t)__cvta_generic_to_shared(p); }
__device__ __forceinline__ void mbar_init(uint32_t bar, uint32_t cnt) {
    asm volatile("mbarrier.init.shared::cta.b64 [%0], %1;" ::"r"(bar), "r"(cnt) : "memory");
}
__device__ __forceinline__ void mbar_expect_tx(uint32_t bar, uint32_t bytes) {
    asm volatile("mbarrier.arrive.expect_tx.shared::cta.b64 _, [%0], %1;" ::"r"(bar), "r"(bytes) : "memory");
}
__device__ __forceinline__ bool mbar_try(uint32_t bar, uint32_t parity) {
    uint32_t ok;
    asm volatile("{\n.reg .pred p;\nmbarrier.try_wait.parity.shared::cta.b64 p, [%1], %2;\nselp.u32 %0, 1, 0, p;\n}\n"
                 : "=r"(ok) : "r"(bar), "r"(parity) : "memory");
    return ok;
}
__device__ __forceinline__ void mbar_wait(uint32_t bar, uint32_t parity) {
    unsigned n = 0;
    while (!mbar_try(bar, parity)) { if (++n > SPIN_LIMIT) __trap(); }
}
__device__ __forceinline__ void bulk_load(uint32_t dst, const void* src, uint32_t bytes, uint32_t bar, uint64_t pol) {
    asm volatile("cp.async.bulk.shared::cluster.global.mbarrier::complete_tx::bytes.L2::cache_hint [%0], [%1], %2, [%3], %4;"
                 ::"r"(dst), "l"(src), "r"(bytes), "r"(bar), "l"(pol) : "memory");
}
__device__ __forceinline__ void tma3d(uint32_t dst, const CUtensorMap* tm, int c0, int c1, int c2, uint32_t bar, uint64_t pol) {
    asm volatile("cp.async.bulk.tensor.3d.shared::cluster.global.mbarrier::complete_tx::bytes.L2::cache_hint [%0], [%1, {%3,%4,%5}], [%2], %6;"
                 ::"r"(dst), "l"(tm), "r"(bar), "r"(c0), "r"(c1), "r"(c2), "l"(pol) : "memory");
}
__device__ __forceinline__ void l2_prefetch(const void* src, uint32_t bytes) {
    asm volatile("cp.async.bulk.prefetch.L2.global [%0], %1;" ::"l"(src), "r"(bytes) : "memory");
}
__device__ __forceinline__ void ldsm4(uint32_t (&r)[4], uint32_t addr) {
    asm volatile("ldmatrix.sync.aligned.m8n8.x4.shared.b16 {%0,%1,%2,%3}, [%4];"
                 : "=r"(r[0]), "=r"(r[1]), "=r"(r[2]), "=r"(r[3]) : "r"(addr));
}
__device__ __forceinline__ void ldsm4t(uint32_t (&r)[4], uint32_t addr) {
    asm volatile("ldmatrix.sync.aligned.m8n8.x4.trans.shared.b16 {%0,%1,%2,%3}, [%4];"
                 : "=r"(r[0]), "=r"(r[1]), "=r"(r[2]), "=r"(r[3]) : "r"(addr));
}
__device__ __forceinline__ void mma16816(float (&d)[4], const uint32_t (&a)[4], uint32_t b0, uint32_t b1) {
    asm("mma.sync.aligned.m16n8k16.row.col.f32.bf16.bf16.f32 {%0,%1,%2,%3}, {%4,%5,%6,%7}, {%8,%9}, {%0,%1,%2,%3};"
        : "+f"(d[0]), "+f"(d[1]), "+f"(d[2]), "+f"(d[3])
        : "r"(a[0]), "r"(a[1]), "r"(a[2]), "r"(a[3]), "r"(b0), "r"(b1));
}
__device__ __forceinline__ uint32_t lds32(uint32_t a) {
    uint32_t v;
    asm volatile("ld.shared.u32 %0, [%1];" : "=r"(v) : "r"(a));
    return v;
}
__device__ __forceinline__ unsigned ld_acquire(const unsigned* p) {
    unsigned v;
    asm volatile("ld.acquire.gpu.global.u32 %0, [%1];" : "=r"(v) : "l"(p) : "memory");
    return v;
}
__device__ __forceinline__ uint2 ld_relaxed8(const void* p) {
    uint2 v;
    asm volatile("ld.relaxed.gpu.global.v2.u32 {%0,%1}, [%2];" : "=r"(v.x), "=r"(v.y) : "l"(p) : "memory");
    return v;
}
__device__ __forceinline__ unsigned ld_relaxed4(const void* p) {
    unsigned v;
    asm volatile("ld.relaxed.gpu.global.u32 %0, [%1];" : "=r"(v) : "l"(p) : "memory");
    return v;
}
__device__ __forceinline__ unsigned atom_inc(unsigned* p) {
    unsigned v;
    asm volatile("atom.relaxed.gpu.global.inc.u32 %0, [%1], 0x7fffffff;" : "=r"(v) : "l"(p) : "memory");
    return v;
}
__device__ __forceinline__ unsigned long long ld_relaxed64(const void* p) {
    unsigned long long v;
    asm volatile("ld.relaxed.gpu.global.u64 %0, [%1];" : "=l"(v) : "l"(p) : "memory");
    return v;
}
__device__ __forceinline__ void st_relaxed64(void* p, unsigned long long v) {
    asm volatile("st.relaxed.gpu.global.u64 [%0], %1;" ::"l"(p), "l"(v) : "memory");
}
__device__ __forceinline__ float4 ld_relaxed16(const void* p) {
    float4 v;
    asm volatile("ld.relaxed.gpu.global.v4.f32 {%0,%1,%2,%3}, [%4];" : "=f"(v.x), "=f"(v.y), "=f"(v.z), "=f"(v.w) : "l"(p) : "memory");
    return v;
}
__device__ __forceinline__ uint32_t not_unset(float v) { return min(__float_as_uint(v), UNSET - 1); }
__device__ __forceinline__ void st_relaxed16(void* p, uint32_t a, uint32_t b, uint32_t c, uint32_t d) {
    asm volatile("st.relaxed.gpu.global.v4.u32 [%0], {%1,%2,%3,%4};" ::"l"(p), "r"(a), "r"(b), "r"(c), "r"(d) : "memory");
}
__device__ __forceinline__ bool is_unset(const float4& v) {
    return max(max(__float_as_uint(v.x), __float_as_uint(v.y)), max(__float_as_uint(v.z), __float_as_uint(v.w))) == UNSET;
}
__device__ __forceinline__ float4 ld_if16(const float4* src, bool c) {
    float4 v;
    asm volatile("{\n.reg .pred p;\nsetp.ne.u32 p, %5, 0;\n@p ld.relaxed.gpu.global.v4.f32 {%0,%1,%2,%3}, [%4];\n}"
                 : "=f"(v.x), "=f"(v.y), "=f"(v.z), "=f"(v.w) : "l"(src), "r"((uint32_t)c) : "memory");
    return v;
}
__device__ __forceinline__ uint32_t mapa(uint32_t a, uint32_t rank) {
    uint32_t r;
    asm("mapa.shared::cluster.u32 %0, %1, %2;" : "=r"(r) : "r"(a), "r"(rank));
    return r;
}
__device__ __forceinline__ void mbar_wait_cluster(uint32_t bar, uint32_t parity) {
    unsigned n = 0;
    while (true) {
        uint32_t ok;
        asm volatile("{\n.reg .pred p;\nmbarrier.test_wait.parity.relaxed.cluster.shared::cta.b64 p, [%1], %2;\nselp.u32 %0, 1, 0, p;\n}\n"
                     : "=r"(ok) : "r"(bar), "r"(parity) : "memory");
        if (ok) break;
        if (++n > SPIN_LIMIT) __trap();
    }
    asm volatile("fence.acquire.sync_restrict::shared::cluster.cluster;" ::: "memory");
}
__device__ __forceinline__ void fence_gpu() { asm volatile("fence.acq_rel.gpu;" ::: "memory"); }
__device__ __forceinline__ void red_add_u32(unsigned* p, unsigned v) {
    asm volatile("red.relaxed.gpu.global.add.u32 [%0], %1;" ::"l"(p), "r"(v) : "memory");
}
__device__ __forceinline__ void st_tagged2(void* p, float a, float b, unsigned tag) {
    const unsigned long long hi = (unsigned long long)tag << 32;
    asm volatile("st.relaxed.gpu.global.v2.b64 [%0], {%1,%2};" ::"l"(p), "l"(hi | __float_as_uint(a)), "l"(hi | __float_as_uint(b)) : "memory");
}
__device__ __forceinline__ ulonglong2 ld_tagged2(const void* p) {
    ulonglong2 v;
    asm volatile("ld.relaxed.gpu.global.v2.b64 {%0,%1}, [%2];" : "=l"(v.x), "=l"(v.y) : "l"(p) : "memory");
    return v;
}
__device__ __forceinline__ float4 atom_add_f4(void* p, float a, float b, float c, float d) {
    float4 r;
    asm volatile("atom.relaxed.gpu.global.add.v4.f32 {%0,%1,%2,%3}, [%4], {%5,%6,%7,%8};"
                 : "=f"(r.x), "=f"(r.y), "=f"(r.z), "=f"(r.w) : "l"(p), "f"(a), "f"(b), "f"(c), "f"(d) : "memory");
    return r;
}
__device__ __forceinline__ void red_release_cta_shared(uint32_t a, unsigned v) {
    asm volatile("red.release.cta.shared::cta.add.u32 [%0], %1;" ::"r"(a), "r"(v) : "memory");
}
__device__ __forceinline__ unsigned ld_acquire_cta_shared(uint32_t a) {
    unsigned v;
    asm volatile("ld.acquire.cta.shared::cta.u32 %0, [%1];" : "=r"(v) : "r"(a) : "memory");
    return v;
}
__device__ __forceinline__ void st_release_cta_shared(uint32_t a, unsigned v) {
    asm volatile("st.release.cta.shared::cta.u32 [%0], %1;" ::"r"(a), "r"(v) : "memory");
}
__device__ __forceinline__ void wait_count(const unsigned* p, unsigned target) {
    unsigned n = 0;
    while (ld_acquire(p) < target) { if (++n > SPIN_LIMIT) __trap(); }
}
__device__ __forceinline__ uint32_t pack_bf16(float lo, float hi) {
    uint32_t r;
    asm("cvt.rn.bf16x2.f32 %0, %1, %2;" : "=r"(r) : "f"(hi), "f"(lo));
    return r;
}
__device__ __forceinline__ float bf_lo(uint32_t v) { return __uint_as_float(v << 16); }
__device__ __forceinline__ float bf_hi(uint32_t v) { return __uint_as_float(v & 0xffff0000u); }
__device__ __forceinline__ float ex2(float x) { float y; asm("ex2.approx.ftz.f32 %0, %1;" : "=f"(y) : "f"(x)); return y; }
__device__ __forceinline__ float expsub(float a, float b) { return ex2((a - b) * LOG2E); }
__device__ __forceinline__ float warp_max(float v) {
#pragma unroll
    for (int m = 16; m; m >>= 1) v = fmaxf(v, __shfl_xor_sync(~0u, v, m));
    return v;
}
__device__ __forceinline__ float warp_sum(float v) {
#pragma unroll
    for (int m = 16; m; m >>= 1) v += __shfl_xor_sync(~0u, v, m);
    return v;
}
template <int HL>
__device__ __forceinline__ unsigned unit_block(int u) {
    const unsigned x = ((unsigned)u & (NUK - 1)) / UPP;
    const int lg = u < NUK ? min(KMAX, max(KMIN, 29 - __clz(x | 1))) : (HL < NH && (int)x >= 4 * VS0 ? 0 : min(VMAX, max(VMIN, 29 - __clz((127 - x) | 1))));
    const unsigned r = x & ((4u << lg) - 1);
    return ((x - r + (r & ((1u << lg) - 1)) * 4 + (r >> lg)) * UPP) | ((unsigned)u & (UPP - 1));
}
__device__ __forceinline__ const char* block_src(const void* base, unsigned blk) {
    const unsigned po = blk / UPP;
    return reinterpret_cast<const char*>(base) + (size_t)(((po & 3) * NH + (po >> 2)) * UPP + blk % UPP) * TILE_BYTES;
}

template <int HD>
__device__ __forceinline__ void a_worker(const Params& p, int un, bool once, bool pre, bool hold, int nstatic, uint32_t slot, uint32_t bar,
                                         uint32_t help, unsigned epoch, uint64_t pol) {
    constexpr int NU = 2 * NUK;
    const int lane = threadIdx.x & 31, g = lane >> 2, t = lane & 3;
    const int li = lane & 7;
    uint32_t kaddr[4], vaddr[8];
    {
        const int e = (lane >> 3) & 1, kk = lane >> 4;
#pragma unroll
        for (int s = 0; s < 4; s++) kaddr[s] = slot + (16 * li + e) * 256 + ((2 * s + kk + li) & 7) * 16;
        const int vrow = 4 * (li >> 1) + (li & 1) + 2 * kk;
#pragma unroll
        for (int c = 0; c < 8; c++) vaddr[c] = slot + vrow * 256 + e * 128 + ((c + li) & 7) * 16;
#pragma unroll
        for (int c = 0; c < 8; c++) asm volatile("" : "+r"(vaddr[c]));
    }
    const uint32_t vmask = (g >> 1) != t ? 0u : ((g & 1) ? 0xffff0000u : 0xffffu);
    int kseen = -1;
    unsigned long long H0 = 0, H1 = 0;
    auto header = [&](int v, unsigned vb) {
        if (v >= NU) return;
        const void *a0, *a1;
        if (v < NUK) {
            const unsigned po = vb / UPP;
            a0 = g_qll + (po & 3) * 2048 + (po >> 2) * 64 + lane;
            a1 = reinterpret_cast<const uint2*>(a0) + 32;
        } else {
            const int half = vb / (NUK / 2);
            if (half > kseen) {
                unsigned n = 0;
                while (ld_acquire_cta_shared(help + 12 + 4 * half) == 0) { if (++n > (SPIN_LIMIT << 4)) __trap(); }
                kseen = half;
            }
            a0 = &g_scores[vb * (KEYS / 4) + lane];
            a1 = &g_stats[(vb / UPP) * UPP + lane];
        }
        H0 = ld_relaxed64(a0);
        H1 = ld_relaxed64(a1);
    };
    asm volatile("bar.sync 2, %0;" ::"n"(32 * (NW + XW + 1)) : "memory");
    epoch = __shfl_sync(~0u, epoch, 0);
    if (hold) { unsigned n = 0; while (ld_acquire_cta_shared(help + 24) < 2) { if (++n > (SPIN_LIMIT << 4)) __trap(); } }
    unsigned (*ctl)[32] = g_ctl[epoch & 1];
    const unsigned tag = epoch + 1;
    unsigned nxt = once ? NU : 0;
    int u = -1;
    unsigned bu = 0, bn = unit_block<HD>(un);
    bool have = false;
    uint32_t phase = 0;
    unsigned kpend = 0;
    const unsigned zero = gridDim.x >> 24;
    uint32_t Q[16];
    float4 oret = make_float4(0.f, 0.f, 0.f, 0.f);
    while (true) {
        const char* nsrc = block_src(un < NUK ? p.kc : p.vc, bn);
        float4* odst = &g_oacc[(bu / UPP) * 32 + lane];
        unsigned* vdst = &g_vdone[(lane & (NREP - 1)) * NH + bu / (4 * UPP)][0];
        float d[8][4];
        CLK(c1);
        const bool dir = HD < NH && u >= NUK && bu >= HD * 4 * UPP;
        if (dir) odst = &g_part[((bu / UPP - HD * 4) * 8 + g) * (UPP * 4) + (bu % UPP) * 4 + t];
        asm volatile("" : "+l"(odst));
        if (u >= NUK) {
#pragma unroll
            for (int j = 0; j < 8; j++) { d[j][0] = d[j][1] = d[j][2] = d[j][3] = 0.f; }
            mbar_wait(bar, phase);
            LAND(NUK + bu);
            uint32_t a[2][8][4];
#pragma unroll
            for (int c = 0; c < 8; c++) ldsm4t(a[0][c], vaddr[c]);
#pragma unroll
            for (int j = 0; j < 8; j++) {
                if (j < 7) {
#pragma unroll
                    for (int c = 0; c < 8; c++) ldsm4t(a[(j + 1) & 1][c], vaddr[c] + (j + 1) * 4096);
                }
#pragma unroll
                for (int c = 0; c < 8; c++) mma16816(d[c], a[j & 1][c], Q[2 * j], Q[2 * j + 1]);
            }
            float o[4];
#pragma unroll
            for (int r = 0; r < 2; r++) {
                o[2 * r] = d[0][2 * r] + d[7][2 * r + 1];
                o[2 * r + 1] = d[0][2 * r + 1] + d[1][2 * r];
#pragma unroll
                for (int k = 1; k < 4; k++) {
                    const int src = (lane & 28) | ((t - k) & 3);
                    o[2 * r] += __shfl_sync(~0u, d[2 * k][2 * r] + d[2 * k - 1][2 * r + 1], src);
                    o[2 * r + 1] += __shfl_sync(~0u, d[2 * k][2 * r + 1] + d[2 * k + 1][2 * r], src);
                }
            }
            if (dir) {
                st_relaxed16(odst, not_unset(o[0]), not_unset(o[1]), not_unset(o[2]), not_unset(o[3]));
            } else {
                oret = atom_add_f4(odst, o[0], o[1], o[2], o[3]);
            }
        } else if (u >= 0) {
#pragma unroll
            for (int j = 0; j < 8; j++) { d[j][0] = d[j][1] = d[j][2] = d[j][3] = 0.f; }
            mbar_wait(bar, phase);
            LAND(bu);
            uint32_t a[2][8][4];
#pragma unroll
            for (int j = 0; j < 8; j++) ldsm4(a[0][j], kaddr[0] + (4 * (j & 3) + 2 * (j >> 2)) * 256);
#pragma unroll
            for (int s = 0; s < 8; s++) {
                if (s < 7) {
#pragma unroll
                    for (int j = 0; j < 8; j++)
                        ldsm4(a[(s + 1) & 1][j], kaddr[(s + 1) & 3] + (4 * (j & 3) + 2 * (j >> 2)) * 256 + ((s + 1) >> 2) * 128);
                }
#pragma unroll
                for (int j = 0; j < 8; j++)
                    mma16816(d[j], a[s & 1][j], Q[(s & 4) * 2 + ((2 * s - 2 * j) & 7)], Q[(s & 4) * 2 + ((2 * s + 1 - 2 * j) & 7)]);
            }
        }
        if (u >= 0) phase ^= 1;
        CLK(c2b);
        if (un < NU && lane == 0) {
            if (!once) nxt = atom_inc(&ctl[C_QUEUE][0]);
            if (u >= 0 || !pre) {
                mbar_expect_tx(bar, TILE_BYTES);
                bulk_load(slot, nsrc, TILE_BYTES, bar, pol);
            }
        }
        const uint32_t tiss = (uint32_t)clock();
        CLK(c3);
        if ((unsigned)u < (unsigned)NUK) {
            const int j0 = (t - (g >> 1)) & 3;
            float v[4];
#pragma unroll
            for (int q = 0; q < 4; q++) {
                const int jq = (q >> 1) * 4, e = (q & 1) * 2;
                const float x0 = (g & 1) ? d[jq + 0][e + 1] : d[jq + 0][e];
                const float x1 = (g & 1) ? d[jq + 1][e + 1] : d[jq + 1][e];
                const float x2 = (g & 1) ? d[jq + 2][e + 1] : d[jq + 2][e];
                const float x3 = (g & 1) ? d[jq + 3][e + 1] : d[jq + 3][e];
                const float y0 = (j0 & 1) ? x1 : x0, y1 = (j0 & 1) ? x3 : x2;
                v[q] = (j0 & 2) ? y1 : y0;
            }
            const uint32_t r0 = pack_bf16(v[0], v[1]), r1 = pack_bf16(v[2], v[3]);
            const uint32_t s0 = pack_bf16(bf_lo(r0) * SCALE, bf_hi(r0) * SCALE);
            const uint32_t s1 = pack_bf16(bf_lo(r1) * SCALE, bf_hi(r1) * SCALE);
            g_scores[bu * (KEYS / 4) + 4 * g + j0] = make_uint2(s0, s1);
            const float f0 = bf_lo(s0), f1 = bf_hi(s0), f2 = bf_lo(s1), f3 = bf_hi(s1);
            const float m = warp_max(fmaxf(fmaxf(f0, f1), fmaxf(f2, f3)));
            const float l = warp_sum((expsub(f0, m) + expsub(f1, m)) + (expsub(f2, m) + expsub(f3, m)));
            if (lane == 0) g_stats[bu] = make_float2(m, l);
            kpend++;
            if (un / (NUK / 2) != u / (NUK / 2)) {
                __syncwarp();
                if (lane == 0) {
                    red_release_cta_shared(help + 4 * (u / (NUK / 2)), kpend);
                    if (un >= NUK) red_release_cta_shared(help + 8, 1u);
                }
                kpend = 0;
            }
        }
        CLK(c4);
        int unn = NU;
        if (un < NU) {
            unsigned n = 0;
            while (true) {
                if (!have) header(un, bn);
                if (un >= NUK || __all_sync(~0u, (uint32_t)(H0 >> 32) == tag && (uint32_t)(H1 >> 32) == tag)) break;
                if (++n > SPIN_LIMIT) __trap();
                have = false;
            }
            if (un >= NUK) {
                const uint32_t s0 = (uint32_t)H0, s1 = (uint32_t)(H0 >> 32);
                const float mu = __uint_as_float((uint32_t)H1);
                const float m = warp_max(mu);
                const float l = warp_sum(__uint_as_float((uint32_t)(H1 >> 32)) * expsub(mu, m));
                const float inv = 1.0f / l;
                const uint32_t w0 = pack_bf16(expsub(bf_lo(s0), m) * inv, expsub(bf_hi(s0), m) * inv);
                const uint32_t w1 = pack_bf16(expsub(bf_lo(s1), m) * inv, expsub(bf_hi(s1), m) * inv);
#pragma unroll
                for (int j = 0; j < 8; j++) {
                    Q[2 * j] = __shfl_sync(~0u, w0, 4 * j + t) & vmask;
                    Q[2 * j + 1] = __shfl_sync(~0u, w1, 4 * j + t) & vmask;
                }
            } else {
#pragma unroll
                for (int j = 0; j < 8; j++) {
                    const int src = (((j + g) & 7) << 2) + t;
                    Q[j] = __shfl_sync(~0u, (uint32_t)H0, src);
                    Q[8 + j] = __shfl_sync(~0u, (uint32_t)H1, src);
                }
            }
            unn = nstatic + (int)__shfl_sync(~0u, nxt, 0);
            if (FILL && HD < NH && !once && unn >= NU && lane == 0)
                asm volatile("st.relaxed.cta.shared::cta.u32 [%0], %1;" ::"r"(help + 28), "r"((tiss + (FJ - (unn - NU)) * 20) | 1u) : "memory");
        }
        if (u >= NUK && !dir && lane < NREP)
            red_add_u32(vdst,
                        1u + ((__float_as_uint(oret.x) | __float_as_uint(oret.y) | __float_as_uint(oret.z) | __float_as_uint(oret.w)) & zero));
        if (un >= NU) break;
        bu = bn;
        have = !(un < NUK && unn >= NUK && !(un >= NUK / 2 && unn < NUK + NUK / 2));
        bn = unit_block<HD>(unn);
        if (have) header(unn, bn);
        u = un;
        un = unn;
    }
}

__device__ __forceinline__ void k_helper(uint32_t help, unsigned epoch) {
    if ((threadIdx.x & 31) != 0) return;
    unsigned (*ctl)[32] = g_ctl[epoch & 1];
    unsigned sent0 = 0, sent1 = 0, n = 0;
    int seen = 0;
    bool fin = false;
    while (!fin || seen < 2) {
        if (!fin) {
            fin = ld_acquire_cta_shared(help + 8) == NW + XW;
            const unsigned c0 = ld_acquire_cta_shared(help), c1 = ld_acquire_cta_shared(help + 4);
            if (c0 != sent0 || c1 != sent1) {
                fence_gpu();
                if (c0 != sent0) red_add_u32(&ctl[C_KDONE][0], c0 - sent0);
                if (c1 != sent1) red_add_u32(&ctl[C_KDONE + 1][0], c1 - sent1);
                sent0 = c0; sent1 = c1;
            }
        }
        if (seen < 2 && ld_acquire(&ctl[C_KDONE + seen][0]) >= NUK / 2) {
            st_release_cta_shared(help + 12 + 4 * seen, 1u);
            seen++;
        } else {
            __nanosleep(300);
        }
        if (++n > SPIN_LIMIT) __trap();
    }
}

template <int HL>
__device__ __forceinline__ void v_poller(uint32_t sbase, int f, int w) {
    const int lane = threadIdx.x & 31;
    const unsigned (*cp)[32] = &g_vdone[((f * NPOLL + w) % NREP) * NH];
    unsigned n = 0;
    while (ld_acquire_cta_shared(sbase + M_HELP + 12) == 0) { __nanosleep(1000); if (++n > SPIN_LIMIT) __trap(); }
    int h = 0;
    bool fast = false;
    while (h < HL) {
        const unsigned r = __ballot_sync(~0u, ld_acquire(&cp[min(h + (lane & 3), HL - 1)][0]) >= 4 * UPP) & 15u;
        if (r & 1) {
            h = min(HL, h + __ffs(~r) - 1);
            __syncwarp();
            if (lane == 0) asm volatile("red.release.cta.shared::cta.max.u32 [%0], %1;" ::"r"(sbase + M_HELP + 20), "r"(h) : "memory");
        }
        if (h < HL - 4) {
            __nanosleep(h ? 300 : 1000);
        } else if (!fast) {
            fast = true;
            const long long t0 = clock64();
            while (clock64() - t0 < w * PGAP) {}
        }
        if (++n > SPIN_LIMIT) __trap();
    }
}
template <int HL>
__device__ __forceinline__ void finisher(const Params& p, uint32_t sbase, int f) {
    const int lane = threadIdx.x & 31;
    {
        const char* wg = reinterpret_cast<const char*>(p.wo);
        const uint32_t dst = sbase + 4 * SLOT + (16 * (lane & 7) + (lane >> 3)) * 16;
#pragma unroll 1
        for (int h = -FPF - 4; h < HL; h++) {
            if (lane == 0 && (unsigned)(h + FPF) < (unsigned)HL) l2_prefetch(wg + (size_t)(h + FPF) * 147456 + f * 2048, 2048);
            if (h >= 0) {
#pragma unroll
                for (int r = 0; r < 4; r++)
                    asm volatile("cp.async.cg.shared.global [%0], [%1], 16;" ::"r"(dst + h * 2048 + ((r & 1) * 4 + (r >> 1) * 8) * 16),
                                 "l"(wg + (size_t)(h * 128 + r * 32 + lane) * (DM * 2) + f * 16) : "memory");
            }
            __nanosleep(FSLEEP);
        }
        asm volatile("cp.async.wait_all;" ::: "memory");
        __syncwarp();
    }
    TS(11);
    const float4* vec = g_oacc + ((lane >> 2) & 3) * 32 + (lane >> 4) * 16 + (lane & 3);
    float acc[2][2][4];
#pragma unroll
    for (int i = 0; i < 16; i++) acc[i >> 3][(i >> 2) & 1][i & 3] = 0.f;
    uint32_t* outp = reinterpret_cast<uint32_t*>(p.out + (lane >> 2) * (2 * DM) + f * 8 + (lane & 3) * 2);
    uint32_t wa = sbase + 4 * SLOT + lane * 16;
    auto project = [&](const float4 (&x)[4], const uint32_t (&w)[4][4]) {
#pragma unroll
        for (int s = 0; s < 4; s++) {
            const uint32_t a[4] = {pack_bf16(x[s].x, x[s].y), 0u, pack_bf16(x[s].z, x[s].w), 0u};
            mma16816(acc[0][s & 1], a, w[s >> 1][(s & 1) * 2], w[s >> 1][(s & 1) * 2 + 1]);
            mma16816(acc[1][s & 1], a, w[2 + (s >> 1)][(s & 1) * 2], w[2 + (s >> 1)][(s & 1) * 2 + 1]);
        }
    };
    int h = 0;
    unsigned n = 0;
    while (h < HL) {
        uint32_t w[4][4];
#pragma unroll
        for (int q = 0; q < 4; q++) ldsm4t(w[q], wa + q * 512);
        int ready;
        while ((ready = ld_acquire_cta_shared(sbase + M_HELP + 20)) <= h) {
            if (h < HL - 3) __nanosleep(100);
            if (++n > (SPIN_LIMIT << 4)) __trap();
        }
        float4 x[4], y[4];
#pragma unroll
        for (int s = 0; s < 4; s++) x[s] = ld_relaxed16(vec + s * 4);
        const bool two = ready > h + 1;
        if (two) {
#pragma unroll
            for (int s = 0; s < 4; s++) y[s] = ld_relaxed16(vec + 128 + s * 4);
        }
        project(x, w);
        if (two) {
#pragma unroll
            for (int q = 0; q < 4; q++) ldsm4t(w[q], wa + 2048 + q * 512);
            project(y, w);
        }
        const int nr = two ? 2 : 1;
        h += nr;
        vec += nr * 128;
        wa += nr * 2048;
        if (FILL && HL < NH && h >= FH && h - nr < FH && lane == 0) st_release_cta_shared(sbase + M_HELP + 36, h);
        const float o0 = acc[0][0][0] + acc[0][1][0] + __shfl_down_sync(~0u, acc[1][0][0] + acc[1][1][0], 16);
        const float o1 = acc[0][0][1] + acc[0][1][1] + __shfl_down_sync(~0u, acc[1][0][1] + acc[1][1][1], 16);
        if (HL == NH) {
            asm volatile("{\n.reg .pred p;\nsetp.ne.u32 p, %2, 0;\n@p st.global.u32 [%0], %1;\n}" ::"l"(outp), "r"(pack_bf16(o0, o1)),
                         "r"((uint32_t)(lane < 16 && h == NH)) : "memory");
        } else if (lane < 16 && h == HL) {
            st_relaxed64(&g_base[(lane >> 2) * (DM / 2) + f * 4 + (lane & 3)], not_unset(o0) | ((unsigned long long)not_unset(o1) << 32));
        }
    }
}

__device__ __noinline__ void final_collector(int b, int rank, int hh, uint32_t sbase) {
    const int lane = threadIdx.x & 31, g = lane >> 2, t = lane & 3;
    const float unset = __uint_as_float(UNSET);
    const float4* src = g_part + ((hh * 4 + b) * 8 + rank) * (UPP * 4) + lane;
    const uint32_t rdst = mapa(sbase + L_BF + hh * 256 + rank * 32 + t * 8, g), rbar = mapa(sbase + L_BAR + 8 + hh * 8, g);
    float4 x[4];
#pragma unroll
    for (int i = 0; i < 4; i++) x[i] = make_float4(unset, unset, unset, unset);
    unsigned n = 0;
    while (true) {
        bool e[4];
#pragma unroll
        for (int i = 0; i < 4; i++) e[i] = is_unset(x[i]);
        if (!__any_sync(~0u, e[0] || e[1] || e[2] || e[3])) break;
        float4 u[4];
#pragma unroll
        for (int i = 0; i < 4; i++) u[i] = ld_if16(src + i * 32, e[i]);
#pragma unroll
        for (int i = 0; i < 4; i++)
            if (e[i]) x[i] = u[i];
        if (++n > SPIN_LIMIT) __trap();
    }
    unsigned first = 0;
    if (lane == 0) asm volatile("atom.relaxed.cta.shared::cta.exch.b32 %0, [%1], 1;" : "=r"(first) : "r"(sbase + L_FLAG + hh * 4) : "memory");
    float s[4] = {(x[0].x + x[1].x) + (x[2].x + x[3].x), (x[0].y + x[1].y) + (x[2].y + x[3].y),
                  (x[0].z + x[1].z) + (x[2].z + x[3].z), (x[0].w + x[1].w) + (x[2].w + x[3].w)};
#pragma unroll
    for (int m = 4; m < 32; m <<= 1) {
#pragma unroll
        for (int i = 0; i < 4; i++) s[i] += __shfl_xor_sync(~0u, s[i], m);
    }
    if (__shfl_sync(~0u, first, 0) == 0) {
        asm volatile("st.async.weak.shared::cluster.mbarrier::complete_tx::bytes.v2.b32 [%0], {%1,%2}, [%3];"
                     ::"r"(rdst), "r"(pack_bf16(s[0], s[1])), "r"(pack_bf16(s[2], s[3])), "r"(rbar) : "memory");
        if (hh == NDIR - 1) TS(31);
    }
}

__device__ __forceinline__ void final_projector(const Params& p, int b, int rank, int j, uint32_t sbase) {
    const int lane = threadIdx.x & 31, g = lane >> 2, t = lane & 3;
    const int col = 16 * j + 8 * (t & 1) + g;
    float base = 0.f;
    if (t < 2 && col < 72) {
        unsigned n = 0;
        uint32_t v;
        while ((v = ld_relaxed4(reinterpret_cast<const float*>(g_base) + b * DM + rank * 72 + col)) == UNSET) { if (++n > SPIN_LIMIT) __trap(); }
        base = __uint_as_float(v);
    }
    __syncwarp();
    TS(28);
    float acc[4][4];
#pragma unroll
    for (int i = 0; i < 16; i++) acc[i >> 2][i & 3] = 0.f;
    mbar_wait(sbase + L_BAR, 0);
#pragma unroll 1
    for (int hh = 0; hh < NDIR; hh++) {
        uint32_t a[8][4];
#pragma unroll
        for (int s = 0; s < 8; s++)
            ldsm4t(a[s], sbase + L_W + hh * 18432 + s * 2304 + ((lane & 7) + (lane >> 4) * 8) * 144 + (2 * j + ((lane >> 3) & 1)) * 16);
        mbar_wait_cluster(sbase + L_BAR + 8 + hh * 8, 0);
        if (hh == NDIR - 1) TS(24);
        uint32_t bf[8][2];
#pragma unroll
        for (int s = 0; s < 8; s++)
            asm volatile("ld.shared.v2.u32 {%0,%1}, [%2];" : "=r"(bf[s][0]), "=r"(bf[s][1]) : "r"(sbase + L_BF + hh * 256 + s * 32 + t * 8) : "memory");
#pragma unroll
        for (int s = 0; s < 8; s++) mma16816(acc[s & 3], a[s], bf[s][0], bf[s][1]);
        const float v = ((t & 1) ? (acc[0][2] + acc[1][2]) + (acc[2][2] + acc[3][2]) : (acc[0][0] + acc[1][0]) + (acc[2][0] + acc[3][0])) + base;
        asm volatile("{\n.reg .pred p;\nsetp.ne.u32 p, %2, 0;\n@p st.global.u16 [%0], %1;\n}"
                     ::"l"(p.out + b * 2 * DM + rank * 72 + col), "h"((unsigned short)pack_bf16(v, 0.f)),
                       "r"((uint32_t)(hh == NDIR - 1 && t < 2 && col < 72)) : "memory");
    }
    TS(15);
}

template <int HD>
__device__ __forceinline__ void final_phase(const Params& p, uint32_t sbase, int blk, unsigned epoch, uint64_t pol) {
    const int tid = threadIdx.x, warp = tid >> 5;
    const int b = blk >> 3, rank = blk & 7;
    unsigned (*ctl)[32] = g_ctl[epoch & 1];
    __syncthreads();
    if (tid == 0) {
#pragma unroll 1
        for (int i = 0; i < 1 + NDIR; i++) mbar_init(sbase + L_BAR + i * 8, 1);
#pragma unroll
        for (int i = 0; i < NDIR; i++) asm volatile("st.shared.u32 [%0], 0;" ::"r"(sbase + L_FLAG + i * 4) : "memory");
        asm volatile("fence.mbarrier_init.release.cluster;" ::: "memory");
        mbar_expect_tx(sbase + L_BAR, NDIR * 18432);
#pragma unroll 1
        for (int hh = 0; hh < NDIR; hh++) {
            mbar_expect_tx(sbase + L_BAR + 8 + hh * 8, 256);
            tma3d(sbase + L_W + hh * 18432, &p.tm_wl, rank * 72, (HD + hh) * 16, 0, sbase + L_BAR, pol);
        }
        unsigned n = 0;
        while (ld_acquire(&ctl[C_KDONE][0]) < NUK / 2 || ld_acquire(&ctl[C_KDONE + 1][0]) < NUK / 2) { __nanosleep(500); if (++n > SPIN_LIMIT) __trap(); }
        while (ld_relaxed4(&g_vdone[(blk & (NREP - 1)) * NH + GHEAD][0]) < 4 * UPP) { __nanosleep(200); if (++n > SPIN_LIMIT) __trap(); }
    }
    asm volatile("barrier.cluster.arrive.release.aligned;\nbarrier.cluster.wait.acquire.aligned;" ::: "memory");
    TS(11);
    if (warp >= 3) {
        final_projector(p, b, rank, warp - 3, sbase);
    } else {
        if (warp < NDIR) final_collector(b, rank, warp, sbase);
        if (warp != NDIR - 1) final_collector(b, rank, NDIR - 1, sbase);
    }
}

__device__ __forceinline__ void fill_ctx(const char* w, uint32_t sbase, int c, int rank, unsigned tag) {
    const int lane = threadIdx.x & 31;
    unsigned n = 0;
    if (lane < 16) {
        mbar_init(sbase + F_BAR + 8 + lane * 8, 1);
        mbar_expect_tx(sbase + F_BAR + 8 + lane * 8, FR * 128);
    }
    asm volatile("fence.mbarrier_init.release.cluster;" ::: "memory");
    while (ld_acquire_cta_shared(sbase + M_HELP + 20) == 0) { __nanosleep(1000); if (++n > SPIN_LIMIT) __trap(); }
#pragma unroll 1
    for (int i = 0; i < 16;) {
        const ulonglong2 v = ld_tagged2(&g_ctx[rank * 512 + i * 32 + lane]);
        if (__all_sync(~0u, (unsigned)(v.x >> 32) == tag && (unsigned)(v.y >> 32) == tag)) {
            asm volatile("st.shared.v2.u32 [%0], {%1,%2};" ::"r"(sbase + F_CTX + (i * 32 + lane) * 8), "r"((uint32_t)v.x), "r"((uint32_t)v.y) : "memory");
            i++;
        } else {
            __nanosleep(500);
            if (++n > SPIN_LIMIT) __trap();
        }
    }
    __syncwarp();
    if (lane == 0) {
        st_release_cta_shared(sbase + M_HELP + 32, 1u);
        uint32_t t0;
        while ((t0 = ld_acquire_cta_shared(sbase + M_HELP + 28)) == 0) { __nanosleep(100); if (++n > SPIN_LIMIT) __trap(); }
#pragma unroll 1
        for (int i = 0; i < 512 / FB; i++) {
            while ((int)((uint32_t)clock() - t0) < 0) {}
            if (i == 0) TS(16);
            l2_prefetch(w + (rank * 512 + i * FB) * 1152 + c * FB * 128, FB * 128);
            t0 += FP * FB / 128;
        }
    }
    __syncwarp();
}
__device__ __noinline__ void fill_piece(uint32_t sbase, int rank, int w) {
    const int lane = threadIdx.x & 31, g = lane >> 2, t = lane & 3;
    unsigned n = 0;
    while (ld_acquire_cta_shared(sbase + M_HELP + 32) == 0) { if (++n > (SPIN_LIMIT << 4)) __trap(); }
    asm volatile("barrier.cluster.wait.acquire.aligned;" ::: "memory");
    uint32_t rdst[4], rbar[4], sw[4];
#pragma unroll
    for (int j = 0; j < 4; j++) {
        rdst[j] = mapa(sbase + F_RECV + (rank * 4 + w) * 128 + g * 16 + (t & 1) * 8, 2 * j + (t >> 1));
        rbar[j] = mapa(sbase + F_BAR, 2 * j + (t >> 1));
        sw[j] = sbase + F_W + w * 4096 + ((lane & 7) + (lane >> 4) * 8) * 128 + (((2 * j + ((lane >> 3) & 1)) ^ (lane & 7)) * 16);
    }
    float acc[2][4][4];
#pragma unroll
    for (int i = 0; i < 32; i++) acc[i >> 4][(i >> 2) & 3][i & 3] = 0.f;
#pragma unroll 1
    for (int i = 0; i < 4; i++) {
        uint32_t bf[2][2], a[2][4][4];
#pragma unroll
        for (int s = 0; s < 2; s++)
            asm volatile("ld.shared.v2.u32 {%0,%1}, [%2];" : "=r"(bf[s][0]), "=r"(bf[s][1])
                         : "r"(sbase + F_CTX + (i * 4 + w) * 256 + s * 128 + (lane & 15) * 8) : "memory");
        mbar_wait_cluster(sbase + F_BAR + 8 + ((i * 4 + w) * 32 / FR) * 8, 0);
#pragma unroll
        for (int s = 0; s < 2; s++)
#pragma unroll
            for (int j = 0; j < 4; j++) ldsm4t(a[s][j], sw[j] + i * 16384 + s * 2048);
#pragma unroll
        for (int j = 0; j < 4; j++) {
            mma16816(acc[0][j], a[0][j], bf[0][0], bf[0][1]);
            mma16816(acc[1][j], a[1][j], bf[1][0], bf[1][1]);
        }
        float v[4][2];
#pragma unroll
        for (int j = 0; j < 4; j++) {
            v[j][0] = (t & 2) ? acc[0][j][2] + acc[1][j][2] : acc[0][j][0] + acc[1][j][0];
            v[j][1] = (t & 2) ? acc[0][j][3] + acc[1][j][3] : acc[0][j][1] + acc[1][j][1];
        }
        asm volatile("{\n.reg .pred p;\nsetp.eq.u32 p, %16, 3;\n"
                     "@p st.async.weak.shared::cluster.mbarrier::complete_tx::bytes.v2.f32 [%0], {%1,%2}, [%3];\n"
                     "@p st.async.weak.shared::cluster.mbarrier::complete_tx::bytes.v2.f32 [%4], {%5,%6}, [%7];\n"
                     "@p st.async.weak.shared::cluster.mbarrier::complete_tx::bytes.v2.f32 [%8], {%9,%10}, [%11];\n"
                     "@p st.async.weak.shared::cluster.mbarrier::complete_tx::bytes.v2.f32 [%12], {%13,%14}, [%15];\n}"
                     ::"r"(rdst[0]), "f"(v[0][0]), "f"(v[0][1]), "r"(rbar[0]), "r"(rdst[1]), "f"(v[1][0]), "f"(v[1][1]), "r"(rbar[1]),
                       "r"(rdst[2]), "f"(v[2][0]), "f"(v[2][1]), "r"(rbar[2]), "r"(rdst[3]), "f"(v[3][0]), "f"(v[3][1]), "r"(rbar[3]),
                       "r"(i) : "memory");
    }
}
__device__ __forceinline__ void fill_issue_sum(const Params& p, uint32_t sbase, int c, int rank, uint64_t pol) {
    const int lane = threadIdx.x & 31;
    __nv_bfloat16* dst = p.out + (lane >> 3) * (2 * DM) + DM + c * 64 + rank * 8 + (lane & 7);
    const uint32_t src = sbase + F_RECV + (lane >> 3) * 1024 + (lane & 7) * 16;
#pragma unroll 1
    for (int r = 0; r < 2; r++) {
        if (r) mbar_wait_cluster(sbase + F_BAR, 0);
        float4 x[8];
#pragma unroll
        for (int i = 0; i < 8; i++)
            asm volatile("ld.shared.v4.f32 {%0,%1,%2,%3}, [%4];" : "=f"(x[i].x), "=f"(x[i].y), "=f"(x[i].z), "=f"(x[i].w) : "r"(src + i * 128) : "memory");
#pragma unroll
        for (int m = 1; m < 8; m <<= 1)
#pragma unroll
            for (int i = 0; i < 8; i += 2 * m) { x[i].x += x[i + m].x; x[i].y += x[i + m].y; x[i].z += x[i + m].z; x[i].w += x[i + m].w; }
        const bool up = lane & 16, od = lane & 8;
        const float a = (up ? x[0].z : x[0].x) + __shfl_xor_sync(~0u, up ? x[0].x : x[0].z, 16);
        const float b = (up ? x[0].w : x[0].y) + __shfl_xor_sync(~0u, up ? x[0].y : x[0].w, 16);
        const float v = (od ? b : a) + __shfl_xor_sync(~0u, od ? a : b, 8);
        asm volatile("{\n.reg .pred p;\nsetp.ne.u32 p, %2, 0;\n@p st.global.u16 [%0], %1;\n}"
                     ::"l"(dst), "h"((unsigned short)pack_bf16(v, 0.f)), "r"(r) : "memory");
        if (r) break;
        if (lane == 0) {
            unsigned n = 0;
            uint32_t t0;
            while ((t0 = ld_acquire_cta_shared(sbase + M_HELP + 28)) == 0) { __nanosleep(100); if (++n > SPIN_LIMIT) __trap(); }
            t0 += FD;
#pragma unroll 1
            for (int i = 0; i < 512 / FR; i++) {
                while ((int)((uint32_t)clock() - t0) < 0) {}
                if (!FB && i == 0) TS(16);
                tma3d(sbase + F_W + i * FR * 128, &p.tm_wf, 0, rank * 512 + i * FR, c, sbase + F_BAR + 8 + i * 8, pol);
                t0 += FQ * FR / 128;
            }
            TS(17);
        }
        __syncwarp();
    }
    TS(15);
}

constexpr int BS_WUK = 5, BS_Q = 9, BS_CKV = 11, BS_PART = 27, BS_WUV = 29, BS_END = 33;

__device__ __noinline__ void b_issue(const Params& p, int n, int bi, uint32_t sbase, uint64_t pol) {
    if (n >= BS_END || (n >= BS_Q && n < BS_CKV) || (n >= BS_PART && n < BS_WUV)) return;
    const uint32_t bar = sbase + M_BAR + (NSLOT + n % BRING) * 8;
    const CUtensorMap* tm;
    int row, panel = 2 * bi;
    if (n < BS_WUK) { tm = &p.tm_wq; row = n * 128; }
    else if (n < BS_Q) { tm = &p.tm_wuk; row = (n - BS_WUK) * 128; }
    else if (n < BS_PART) {
        tm = &p.tm_ckv; panel = 0;
        row = (bi >> 3) * SK + ((n - BS_CKV) * 8 + (bi & 7)) * 32;
    }
    else { tm = &p.tm_wuv; row = (n - BS_WUV) * 128; }
    mbar_expect_tx(bar, n == 0 ? 32768 + 4 * 1152 : 32768);
    tma3d(sbase + (n % BRING) * SLOT, tm, 0, row, panel, bar, pol);
}
__device__ __forceinline__ void b_issue_xchg(int n, const void* src, uint32_t sbase, uint64_t pol) {
    asm volatile("fence.proxy.async;" ::: "memory");
#pragma unroll
    for (int i = 0; i < 2; i++) {
        const uint32_t bar = sbase + M_BAR + (NSLOT + (n + i) % BRING) * 8;
        mbar_expect_tx(bar, 32768);
        bulk_load(sbase + ((n + i) % BRING) * SLOT, reinterpret_cast<const char*>(src) + i * 32768, 32768, bar, pol);
    }
}
__device__ __forceinline__ void b_wait(int n, uint32_t sbase) {
    mbar_wait(sbase + M_BAR + (NSLOT + n % BRING) * 8, (n / BRING) & 1);
}

__device__ __noinline__ void b_gemm(const Params& p, uint32_t sbase, int n0, int n1, int ktot, uint32_t xh, uint32_t xl, int pitch,
                                    int bi, uint64_t pol) {
    const int tid = threadIdx.x, warp = tid >> 5, lane = tid & 31, g = lane >> 2, t = lane & 3;
    const uint32_t woff = (warp >> 2) * 16384 + (lane & 15) * 128 + ((((warp & 3) * 2 + (lane >> 4)) ^ (lane & 7)) * 16);
    const uint32_t xoff = (g & 3) * pitch + t * 4;
    float acc[2][4];
#pragma unroll
    for (int i = 0; i < 8; i++) acc[i >> 2][i & 3] = 0.f;
#pragma unroll 1
    for (int n = n0; n < n1; n++) {
        b_wait(n, sbase);
        const uint32_t slot = sbase + (n % BRING) * SLOT + woff;
        const int k0 = (n - n0) * 128;
        const int ns = min(8, (ktot - k0) >> 4);
#pragma unroll 2
        for (int s = 0; s < ns; s++) {
            uint32_t a[4], w[4];
            const uint32_t xo = xoff + (k0 + 16 * s) * 2;
            a[0] = lds32(xh + xo); a[2] = lds32(xh + xo + 16);
            a[1] = xl ? lds32(xl + xo) : 0u; a[3] = xl ? lds32(xl + xo + 16) : 0u;
            ldsm4t(w, slot + s * 2048);
            mma16816(acc[0], a, w[0], w[1]);
            mma16816(acc[1], a, w[2], w[3]);
        }
        __syncthreads();
        if (tid == 0) b_issue(p, n + BD, bi, sbase, pol);
    }
    if (g < 4) {
#pragma unroll
        for (int j = 0; j < 2; j++)
            asm volatile("st.shared.u32 [%0], %1;" ::"r"(sbase + M_QB + g * QP + (warp * 16 + j * 8 + t * 2) * 2),
                         "r"(pack_bf16(acc[j][0] + acc[j][2], acc[j][1] + acc[j][3])) : "memory");
    }
    __syncthreads();
}

__device__ __forceinline__ void b_exchange(unsigned* c, int n, const void* src, uint32_t sbase, uint64_t pol) {
    TS(n == BS_Q ? 24 : 28);
    __syncthreads();
    if (threadIdx.x == 0) {
        TS(n == BS_Q ? 25 : 29);
        fence_gpu();
        TS(n == BS_Q ? 26 : 30);
        red_add_u32(c, 1u);
        wait_count(c, NBCTA);
        TS(n == BS_Q ? 27 : 31);
        b_issue_xchg(n, src, sbase, pol);
    }
}

template <bool CLU>
__device__ __noinline__ void b_chain(const Params& p, char* smem, uint32_t sbase, int bi, unsigned epoch, uint64_t pol) {
    const int tid = threadIdx.x, warp = tid >> 5, lane = tid & 31, g = lane >> 2, t = lane & 3;
    unsigned (*ctl)[32] = g_ctl[epoch & 1];
    float* red = reinterpret_cast<float*>(smem + 5 * SLOT);
    __syncthreads();
    b_gemm(p, sbase, 0, BS_WUK, DM, sbase + M_XB, 0, XP, bi, pol);
    TS(6);
    {
        uint32_t Q[16];
#pragma unroll
        for (int c = 0; c < 16; c++) Q[c] = lds32(sbase + M_QB + (g & 3) * QP + c * 16 + t * 4);
        float* qa = reinterpret_cast<float*>(smem + M_QA);
#pragma unroll 1
        for (int n = BS_WUK; n < BS_Q; n++) {
            b_wait(n, sbase);
            const uint32_t base = sbase + (n % BRING) * SLOT + (warp * 16 + (lane & 15)) * 128;
            float d[2][4];
#pragma unroll
            for (int i = 0; i < 8; i++) d[i >> 2][i & 3] = 0.f;
#pragma unroll
            for (int s = 0; s < 8; s++) {
                uint32_t a[4];
                ldsm4(a, base + (s >> 2) * 16384 + (((2 * (s & 3) + (lane >> 4)) ^ (lane & 7)) * 16));
                mma16816(d[s & 1], a, Q[2 * s], Q[2 * s + 1]);
            }
            const int c = (n - BS_WUK) * 128 + warp * 16 + g + 8 * (t >> 1);
            qa[(2 * (t & 1)) * 512 + c] = (t & 2) ? d[0][2] + d[1][2] : d[0][0] + d[1][0];
            qa[(2 * (t & 1) + 1) * 512 + c] = (t & 2) ? d[0][3] + d[1][3] : d[0][1] + d[1][1];
            __syncthreads();
            if (tid == 0) b_issue(p, n + BD, bi, sbase, pol);
        }
#pragma unroll 1
        for (int r = 0; r < 2; r++) {
            const int id = tid + r * 256;
            const int b = id >> 7, c0 = ((id >> 2) & 31) * 16 + (id & 3) * 2;
            const float2 u0 = *reinterpret_cast<const float2*>(qa + b * 512 + c0);
            const float2 u1 = *reinterpret_cast<const float2*>(qa + b * 512 + c0 + 8);
            const uint32_t h0 = pack_bf16(u0.x, u0.y), h1 = pack_bf16(u1.x, u1.y);
            const uint32_t l0 = pack_bf16(u0.x - bf_lo(h0), u0.y - bf_hi(h0)), l1 = pack_bf16(u1.x - bf_lo(h1), u1.y - bf_hi(h1));
            g_qabs[((id >> 2) * 4 + (bi >> 3)) * 32 + (bi & 7) * 4 + (id & 3)] = make_uint4(h0, l0, h1, l1);
        }
    }
    b_exchange(&ctl[C_BBAR][0], BS_Q, &g_qabs[(bi >> 3) * 4096], sbase, pol);
    {
        uint32_t qf[4][4][4];
        b_wait(BS_Q + (warp >> 2), sbase);
        TS(7);
        {
            const uint4* qs = reinterpret_cast<const uint4*>(smem + ((BS_Q + (warp >> 2)) % BRING) * SLOT) + (warp & 3) * 512 + lane;
#pragma unroll
            for (int s = 0; s < 4; s++)
#pragma unroll
                for (int i = 0; i < 4; i++) {
                    const uint4 v = qs[(s * 4 + i) * 32];
                    qf[i][s][0] = v.x; qf[i][s][1] = v.y; qf[i][s][2] = v.z; qf[i][s][3] = v.w;
                }
        }
        __syncthreads();
        if (tid == 0) { b_issue(p, BS_Q + BD, bi, sbase, pol); b_issue(p, BS_Q + 1 + BD, bi, sbase, pol); }
        float acc[2][8][4];
#pragma unroll
        for (int i = 0; i < 2; i++)
#pragma unroll
            for (int j = 0; j < 8; j++) { acc[i][j][0] = acc[i][j][1] = acc[i][j][2] = acc[i][j][3] = 0.f; }
        float mrun = -INFINITY, lrun = 0.f;
        const int head = tid >> 3, kq = tid & 7;
        float* alpha = reinterpret_cast<float*>(smem + M_ALPHA);
        for (int n = BS_CKV; n < BS_PART; n++) {
            b_wait(n, sbase);
            const uint32_t slot = sbase + (n % BRING) * SLOT;
            float sc[4][4][4];
#pragma unroll
            for (int i = 0; i < 4; i++)
#pragma unroll
                for (int j = 0; j < 4; j++) { sc[i][j][0] = sc[i][j][1] = sc[i][j][2] = sc[i][j][3] = 0.f; }
#pragma unroll
            for (int j = 0; j < 4; j++)
#pragma unroll
                for (int sp = 0; sp < 2; sp++) {
                    uint32_t bf[4];
                    ldsm4(bf, slot + warp * 4096 + (8 * j + (lane & 7)) * 128 + (((4 * sp + (lane >> 3)) ^ (lane & 7)) * 16));
#pragma unroll
                    for (int i = 0; i < 4; i++) {
                        mma16816(sc[i][j], qf[i][2 * sp], bf[0], bf[1]);
                        mma16816(sc[i][j], qf[i][2 * sp + 1], bf[2], bf[3]);
                    }
                }
#pragma unroll
            for (int i = 0; i < 4; i++)
#pragma unroll
                for (int j = 0; j < 4; j++)
                    *reinterpret_cast<float2*>(red + warp * 1024 + (8 * i + g) * 32 + ((8 * j) ^ (8 * (g & 3))) + 2 * t) =
                        make_float2(sc[i][j][0] + sc[i][j][2], sc[i][j][1] + sc[i][j][3]);
            __syncthreads();
            if (tid == 0 && n > BS_CKV) b_issue(p, n - 1 + BD, bi, sbase, pol);
            {
                float4 s = make_float4(0.f, 0.f, 0.f, 0.f);
#pragma unroll
                for (int w = 0; w < 8; w++) {
                    const float4 v = *reinterpret_cast<const float4*>(red + w * 1024 + head * 32 + ((4 * kq) ^ (8 * (head & 3))));
                    s.x += v.x; s.y += v.y; s.z += v.z; s.w += v.w;
                }
                const uint32_t r0 = pack_bf16(s.x, s.y), r1 = pack_bf16(s.z, s.w);
                const uint32_t s0 = pack_bf16(bf_lo(r0) * SCALE, bf_hi(r0) * SCALE);
                const uint32_t s1 = pack_bf16(bf_lo(r1) * SCALE, bf_hi(r1) * SCALE);
                const float f0 = bf_lo(s0), f1 = bf_hi(s0), f2 = bf_lo(s1), f3 = bf_hi(s1);
                float mx = fmaxf(fmaxf(f0, f1), fmaxf(f2, f3));
                mx = fmaxf(mx, __shfl_xor_sync(~0u, mx, 1));
                mx = fmaxf(mx, __shfl_xor_sync(~0u, mx, 2));
                mx = fmaxf(mx, __shfl_xor_sync(~0u, mx, 4));
                const float mnew = fmaxf(mrun, mx);
                const float al = expsub(mrun, mnew);
                const float p0 = expsub(f0, mnew), p1 = expsub(f1, mnew), p2 = expsub(f2, mnew), p3 = expsub(f3, mnew);
                lrun = lrun * al + ((p0 + p1) + (p2 + p3));
                mrun = mnew;
                *reinterpret_cast<uint2*>(smem + M_P + head * 80 + kq * 8) = make_uint2(pack_bf16(p0, p1), pack_bf16(p2, p3));
                if (kq == 0) alpha[head] = al;
            }
            __syncthreads();
            {
                uint32_t pf[2][2][4];
#pragma unroll
                for (int i = 0; i < 2; i++)
#pragma unroll
                    for (int ks = 0; ks < 2; ks++)
                        ldsm4(pf[i][ks], sbase + M_P + (16 * i + (lane & 15)) * 80 + (16 * ks + 8 * (lane >> 4)) * 2);
#pragma unroll
                for (int i = 0; i < 2; i++) {
                    const float a0 = alpha[16 * i + g], a1 = alpha[16 * i + 8 + g];
#pragma unroll
                    for (int j = 0; j < 8; j++) { acc[i][j][0] *= a0; acc[i][j][1] *= a0; acc[i][j][2] *= a1; acc[i][j][3] *= a1; }
                }
#pragma unroll
                for (int j = 0; j < 8; j++) {
                    uint32_t bf[4];
                    ldsm4t(bf, slot + warp * 4096 + lane * 128 + ((j ^ (lane & 7)) * 16));
#pragma unroll
                    for (int i = 0; i < 2; i++) {
                        mma16816(acc[i][j], pf[i][0], bf[0], bf[1]);
                        mma16816(acc[i][j], pf[i][1], bf[2], bf[3]);
                    }
                }
            }
        }
        __syncthreads();
        if (tid == 0) b_issue(p, BS_PART - 1 + BD, bi, sbase, pol);
        lrun += __shfl_xor_sync(~0u, lrun, 1);
        lrun += __shfl_xor_sync(~0u, lrun, 2);
        lrun += __shfl_xor_sync(~0u, lrun, 4);
        if (kq == 0) g_bml[head * NBCTA + bi] = make_float2(mrun, lrun);
#pragma unroll
        for (int i = 0; i < 2; i++)
#pragma unroll
            for (int j = 0; j < 8; j++) {
                g_bpart[((16 * i + g) * NBCTA + bi) * 256 + warp * 32 + j * 4 + t] = make_float2(acc[i][j][0], acc[i][j][1]);
                g_bpart[((16 * i + 8 + g) * NBCTA + bi) * 256 + warp * 32 + j * 4 + t] = make_float2(acc[i][j][2], acc[i][j][3]);
            }
    }
#pragma unroll 1
    for (int i = tid; i < NH * 36 && !(CLU && FILL); i += 256) g_outb[bi * NH * 36 + i] = make_uint4(0u, epoch, 0u, epoch);
    b_exchange(&ctl[C_BBAR + 1][0], BS_PART, &g_bpart[bi * NBCTA * 256], sbase, pol);
    {
        float* omega = reinterpret_cast<float*>(smem + M_OMEGA);
        if (warp == 0) {
            __syncwarp();
            const uint2 ml = ld_relaxed8(&g_bml[bi * NBCTA + lane]);
            const float ms = __uint_as_float(ml.x);
            float m = ms;
            m = fmaxf(m, __shfl_xor_sync(~0u, m, 1));
            m = fmaxf(m, __shfl_xor_sync(~0u, m, 2));
            m = fmaxf(m, __shfl_xor_sync(~0u, m, 4));
            const float w = expsub(ms, m);
            float l = w * __uint_as_float(ml.y);
            l += __shfl_xor_sync(~0u, l, 1);
            l += __shfl_xor_sync(~0u, l, 2);
            l += __shfl_xor_sync(~0u, l, 4);
            omega[lane] = w / l;
        }
        __syncthreads();
        b_wait(BS_PART, sbase);
        b_wait(BS_PART + 1, sbase);
#pragma unroll 1
        for (int b = 0; b < 4; b++) {
            const float2* ps = reinterpret_cast<const float2*>(smem + ((BS_PART + (b >> 1)) % BRING) * SLOT) + (b & 1) * 2048 + tid;
            float c0 = 0.f, c1 = 0.f;
#pragma unroll
            for (int s = 0; s < 8; s++) {
                const float w = omega[b * 8 + s];
                const float2 v = ps[s * 256];
                c0 = fmaf(w, v.x, c0);
                c1 = fmaf(w, v.y, c1);
            }
            const uint32_t hi = pack_bf16(c0, c1);
            *reinterpret_cast<uint32_t*>(smem + M_CH + b * CP + tid * 4) = hi;
            *reinterpret_cast<uint32_t*>(smem + M_CL + b * CP + tid * 4) = pack_bf16(c0 - bf_lo(hi), c1 - bf_hi(hi));
        }
        __syncthreads();
        if (tid == 0) { b_issue(p, BS_PART + BD, bi, sbase, pol); b_issue(p, BS_PART + 1 + BD, bi, sbase, pol); }
    }
    b_gemm(p, sbase, BS_WUV, BS_END, 512, sbase + M_CH, sbase + M_CL, CP, bi, pol);
    TS(12);
    if (CLU && FILL) {
        if (tid < 128) {
            const uint32_t xo = sbase + M_QB + (g & 3) * QP + (tid >> 4) * 32 + t * 4;
            st_tagged2(&g_ctx[bi * 128 + tid], __uint_as_float(lds32(xo)), __uint_as_float(lds32(xo + 16)), epoch + 1);
        }
        return;
    }
    if (tid == 0) {
#pragma unroll 1
        for (int i = 0; i < 4; i++) {
            mbar_expect_tx(sbase + M_BAR + i * 8, 36864);
            tma3d(sbase + i * 36864, &p.tm_wo, 0, bi * 128 + i * 32, 0, sbase + M_BAR + i * 8, pol);
        }
    }
    TS(8);
    {
        float acc[9][4];
#pragma unroll
        for (int j = 0; j < 9; j++) { acc[j][0] = acc[j][1] = acc[j][2] = acc[j][3] = 0.f; }
#pragma unroll 1
        for (int i = 0; i < 4; i++) {
            const uint32_t xo = sbase + M_QB + (g & 3) * QP + i * 64 + t * 4;
            const uint32_t a0[4] = {lds32(xo), 0u, lds32(xo + 16), 0u}, a1[4] = {lds32(xo + 32), 0u, lds32(xo + 48), 0u};
            mbar_wait(sbase + M_BAR + i * 8, 0);
#pragma unroll
            for (int j = 0; j < 9; j++) {
                const int nt = warp * 9 + j;
                uint32_t w[4];
                ldsm4t(w, sbase + i * 36864 + (nt >> 3) * 4096 + lane * 128 + (((nt & 7) ^ (lane & 7)) * 16));
                mma16816(acc[j], a0, w[0], w[1]);
                mma16816(acc[j], a1, w[2], w[3]);
            }
        }
        if (g < 4) {
#pragma unroll
            for (int j = 0; j < 9; j++) {
                const int c2 = (warp * 9 + j) * 4 + t;
                st_tagged2(&g_outb[((c2 / 9) * NH + bi) * 36 + g * 9 + c2 % 9], acc[j][0], acc[j][1], epoch + 1);
            }
        }
    }
    TS(9);
    {
        const uint4* src = g_outb + (bi * NH + (tid >> 3)) * 36 + (tid & 7);
        float2* part = reinterpret_cast<float2*>(red);
        unsigned n = 0;
        while (true) {
            ulonglong2 v[5];
            bool ok = true;
#pragma unroll
            for (int i = 0; i < 5; i++)
                if (i < 4 || (tid & 7) < 4) v[i] = ld_tagged2(src + i * 8);
#pragma unroll
            for (int i = 0; i < 5; i++)
                if (i < 4 || (tid & 7) < 4) {
                    ok = ok && (unsigned)(v[i].x >> 32) == epoch + 1 && (unsigned)(v[i].y >> 32) == epoch + 1;
                    part[(tid >> 3) * 36 + (tid & 7) + i * 8] = make_float2(__uint_as_float((unsigned)v[i].x), __uint_as_float((unsigned)v[i].y));
                }
            if (ok) break;
            __nanosleep(400);
            if (++n > SPIN_LIMIT) __trap();
        }
        __syncthreads();
        if (tid < 36) {
            float s0 = 0.f, s1 = 0.f;
#pragma unroll 8
            for (int h = 0; h < NH; h++) { const float2 v = part[h * 36 + tid]; s0 += v.x; s1 += v.y; }
            *reinterpret_cast<uint32_t*>(p.out + (tid / 9) * 2 * DM + DM + bi * 18 + (tid % 9) * 2) = pack_bf16(s0, s1);
        }
    }
    TS(10);
}

template <bool CLU>
__global__ void __launch_bounds__(256, 1) fused_decode_kernel(const __grid_constant__ Params p) {
    constexpr int HL = CLU ? NH - NDIR : NH;
    extern __shared__ __align__(1024) char smem_raw[];
    const uint32_t sbase = (smem_u32(smem_raw) + 1023u) & ~1023u;
    char* smem = smem_raw + (sbase - smem_u32(smem_raw));
    const int tid = threadIdx.x, warp = tid >> 5, lane = tid & 31;
    const int blk = blockIdx.x;
    const bool isB = CLU ? blk < NBCTA : (blk & 3) == 0 && (blk >> 2) < NBCTA;
    const int bi = CLU ? blk : blk >> 2;
    const int nb = CLU ? blk - NBCTA : blk - min(NBCTA, (blk + 3) >> 2);
    const int nnb = gridDim.x - NBCTA;
    const int nstatic = nnb * (NW + XW);
    uint64_t pol;
    asm volatile("createpolicy.fractional.L2::evict_first.b64 %0, 1.0;" : "=l"(pol));
    const uint32_t wbar = sbase + M_BAR + warp * 8, wslot = sbase + warp * SLOT;
    const int u0 = warp * nnb + nb;
    const bool hold = ((blk >> 2) >> KMIN << KMIN) * 4 * UPP < nstatic;
    const uint32_t jbar = sbase + M_BAR + (NSLOT + BRING) * 8;
    if (warp == 7) {
        if (lane == 0 && blk < 128) {
            mbar_init(jbar, 1);
            asm volatile("fence.mbarrier_init.release.cluster;" ::: "memory");
            uint64_t poln;
            asm volatile("createpolicy.fractional.L2::evict_normal.b64 %0, 1.0;" : "=l"(poln));
            mbar_expect_tx(jbar, 36864 + 4 * 1152);
            tma3d(sbase + J0W, &p.tm_j0, blk * 32, 0, 0, jbar, poln);
            bulk_load(sbase + M_XA, p.xa, 4608, jbar, poln);
        }
        if (lane < 16) reinterpret_cast<unsigned*>(smem + M_HELP)[lane] = 0;
        __syncwarp();
        if (!isB) asm volatile("bar.arrive 2, %0;" ::"n"(32 * (NW + XW + 1)) : "memory");
    }
    if (warp < 4 && lane == 0) {
        mbar_init(wbar, 1);
        if (CLU && FILL && warp == 3 && !isB) {
            mbar_init(sbase + F_BAR, 1);
            mbar_expect_tx(sbase + F_BAR, 4096);
        }
        asm volatile("fence.mbarrier_init.release.cluster;" ::: "memory");
        if (warp < NEARLY && !isB && !hold) {
            mbar_expect_tx(wbar, TILE_BYTES);
            bulk_load(wslot, block_src(p.kc, unit_block<HL>(u0)), TILE_BYTES, wbar, pol);
        }
    }
    unsigned epoch = 0;
    if (lane == 0) epoch = ld_relaxed4(&g_epoch);
    TS(0);
    if (CLU && FILL && !isB) asm volatile("barrier.cluster.arrive.relaxed.aligned;" ::: "memory");
    if ((warp >> 1) == 2 && blk < 128) st_relaxed64(&g_qll[((tid - 128) >> 4) * 2048 + blk * 16 + (tid & 15)], 0ull);
    if (isB || warp >= NW + XW) epoch = __shfl_sync(~0u, epoch, 0);
    if (isB && warp == 3) asm volatile("bar.sync 1, 160;" ::: "memory");
    if (isB && tid == 96) {
#pragma unroll 1
        for (int i = 0; i < BRING; i++) mbar_init(sbase + M_BAR + (NSLOT + i) * 8, 1);
        asm volatile("fence.mbarrier_init.release.cluster;" ::: "memory");
        if (hold) { unsigned n = 0; while (ld_acquire_cta_shared(sbase + M_HELP + 24) < 2) { if (++n > (SPIN_LIMIT << 4)) __trap(); } }
#pragma unroll 1
        for (int b = 0; b < 4; b++) bulk_load(sbase + M_XB + b * XP, p.xb + b * DM, 1152, sbase + M_BAR + NSLOT * 8, pol);
#pragma unroll 1
        for (int n = 0; n < BD; n++) b_issue(p, n, bi, sbase, pol);
    }
    if (warp >= 4 && blk < 128) {
        const int g = lane >> 2, t = lane & 3, j = tid - 128;
        asm volatile("bar.sync 1, %0;" ::"r"(isB ? 160 : 128) : "memory");
#pragma unroll 1
        for (int sl = blk, ph = 0;; sl += 128 - gridDim.x, ph = 1) {
        mbar_wait(jbar, ph);
        TS(13);
        float acc[4][4];
#pragma unroll
        for (int i = 0; i < 16; i++) acc[i >> 2][i & 3] = 0.f;
        const uint32_t wa = sbase + J0W + ((warp - 4) * 144 + (lane & 15)) * 64;
        const uint32_t sw = (lane >> 1) & 3, xa = sbase + M_XA + (g & 3) * 1152 + (warp - 4) * 288 + t * 4;
#pragma unroll 3
        for (int s = 0; s < 9; s++) {
            const uint32_t a[4] = {lds32(xa + s * 32), 0u, lds32(xa + s * 32 + 16), 0u};
            uint32_t w0[4], w1[4];
            ldsm4t(w0, wa + s * 1024 + (((lane >> 4) ^ sw) * 16));
            ldsm4t(w1, wa + s * 1024 + (((2 + (lane >> 4)) ^ sw) * 16));
            mma16816(acc[0], a, w0[0], w0[1]);
            mma16816(acc[1], a, w0[2], w0[3]);
            mma16816(acc[2], a, w1[0], w1[1]);
            mma16816(acc[3], a, w1[2], w1[3]);
        }
        float2* j0 = reinterpret_cast<float2*>(smem + M_J0);
        if (g < 4) {
#pragma unroll
            for (int i = 0; i < 4; i++) j0[(warp - 4) * 64 + g * 16 + i * 4 + t] = make_float2(acc[i][0], acc[i][1]);
        }
        asm volatile("bar.sync 1, 128;" ::: "memory");
        const bool again = sl == blk && blk + 128 - (int)gridDim.x >= (int)gridDim.x;
        if (again && tid == 224) {
            mbar_expect_tx(jbar, 36864);
            tma3d(sbase + J0W, &p.tm_j0, (blk + 128 - gridDim.x) * 32, 0, 0, jbar, pol);
        }
        if (warp < 6) {
            const float2 v0 = j0[j], v1 = j0[64 + j], v2 = j0[128 + j], v3 = j0[192 + j];
            st_relaxed64(&g_qll[(j >> 4) * 2048 + sl * 16 + (j & 15)],
                         (unsigned long long)pack_bf16((v0.x + v1.x) + (v2.x + v3.x), (v0.y + v1.y) + (v2.y + v3.y)) |
                             ((unsigned long long)(epoch + 1) << 32));
            __syncwarp();
            if (lane == 0) asm volatile("red.relaxed.cta.shared::cta.add.u32 [%0], 1;" ::"r"(sbase + M_HELP + 24) : "memory");
        } else if (warp == 7) {
            if (blk < C_LINES) g_ctl[(epoch & 1) ^ 1][blk][lane] = 0;
        }
        TS(1);
        if (!again) break;
        asm volatile("bar.sync 1, 128;" ::: "memory");
        }
    }
    if (isB) {
        b_chain<CLU>(p, smem, sbase, bi, epoch, pol);
        if (CLU) final_phase<HL>(p, sbase, blk, epoch, pol);
        return;
    }
    if (warp < NW + XW) {
        a_worker<HL>(p, u0, warp >= NW + ((nb & 3) < (CLU ? X3C : X3) ? 1 : 0), warp < NEARLY && !hold, hold, nstatic, wslot, wbar, sbase + M_HELP, epoch, pol);
        if (CLU && FILL && warp == 3 && nb < NFIN) {
            unsigned n = 0;
            while (ld_acquire_cta_shared(sbase + M_HELP + 36) < FH || ld_acquire_cta_shared(sbase + M_HELP + 32) == 0) {
                __nanosleep(500);
                if (++n > SPIN_LIMIT) __trap();
            }
            if (lane == 0) asm volatile("prefetch.tensormap [%0];" ::"l"(&p.tm_wf) : "memory");
            fill_issue_sum(p, sbase, nb >> 3, nb & 7, pol);
        }
        return;
    } else if (warp == 7) {
#pragma unroll 1
        for (int i = nb; i < 4 * HL; i += nnb) g_oacc[i * 32 + lane] = make_float4(0.f, 0.f, 0.f, 0.f);
        if (nb < NREP * NH) g_vdone[nb][lane] = 0;
        if (CLU) {
            const float unset = __uint_as_float(UNSET);
#pragma unroll 1
            for (int i = nb; i < NDIR * 4 * UPP; i += nnb) g_part[i * 32 + lane] = make_float4(unset, unset, unset, unset);
            if (nb * 32 + lane < 4 * DM / 2) g_base[nb * 32 + lane] = make_float2(unset, unset);
        }
        __syncwarp();
        k_helper(sbase + M_HELP, epoch);
        if (nb == 0 && lane == 0) g_epoch = epoch + 1;
        __syncwarp();
        if (CLU && FILL && nb < NFIN) fill_ctx(reinterpret_cast<const char*>(p.wob), sbase, nb >> 3, nb & 7, epoch + 1);
    } else if (warp == 6 && nb < NFIN) {
        finisher<HL>(p, sbase, nb);
        TS(4);
    } else if (warp >= 6 - NPOLL && nb < NFIN) {
        v_poller<HL>(sbase, nb, warp - (6 - NPOLL));
    }
    if (CLU && FILL && nb < NFIN) fill_piece(sbase, nb & 7, warp - 4);
}

}

typedef CUresult (*EncodeFn)(CUtensorMap*, CUtensorMapDataType, cuuint32_t, void*, const cuuint64_t*, const cuuint64_t*,
                             const cuuint32_t*, const cuuint32_t*, CUtensorMapInterleave, CUtensorMapSwizzle,
                             CUtensorMapL2promotion, CUtensorMapFloatOOBfill);

extern "C" void kernel_launch(void* const* d_in, const int* in_sizes, int n_in, void* d_out, int out_size) {
    (void)in_sizes; (void)n_in; (void)out_size;
    static int nsm = 0, ncl = 0;
    static EncodeFn encode = nullptr;
    cudaLaunchConfig_t cfg = {};
    cudaLaunchAttribute at[1];
    at[0].id = cudaLaunchAttributeClusterDimension;
    at[0].val.clusterDim.x = 8; at[0].val.clusterDim.y = 1; at[0].val.clusterDim.z = 1;
    cfg.blockDim = dim3(256); cfg.dynamicSmemBytes = SMEM_BYTES; cfg.stream = cudaStreamPerThread; cfg.attrs = at; cfg.numAttrs = 1;
    if (nsm == 0) {
        int dev = 0;
        cudaGetDevice(&dev);
        cudaDeviceGetAttribute(&nsm, cudaDevAttrMultiProcessorCount, dev);
        cudaFuncSetAttribute(fused_decode_kernel<false>, cudaFuncAttributeMaxDynamicSharedMemorySize, SMEM_BYTES);
        cudaFuncSetAttribute(fused_decode_kernel<true>, cudaFuncAttributeMaxDynamicSharedMemorySize, SMEM_BYTES);
        cfg.gridDim = dim3(128);
        if (cudaOccupancyMaxActiveClusters(&ncl, fused_decode_kernel<true>, &cfg) != cudaSuccess) { ncl = 0; (void)cudaGetLastError(); }
        if (ncl > MINCL) ncl = MINCL;
        void* fn = nullptr;
        cudaDriverEntryPointQueryResult qr;
        cudaGetDriverEntryPoint("cuTensorMapEncodeTiled", &fn, cudaEnableDefault, &qr);
        encode = (EncodeFn)fn;
    }
    Params p;
    auto panels = [&](CUtensorMap* tm, void* ptr, int rows, int cols, int box_rows, int box_panels) {
        const cuuint64_t gd[3] = {64, (cuuint64_t)rows, (cuuint64_t)(cols / 64)}, gs[2] = {(cuuint64_t)cols * 2, 128};
        const cuuint32_t box[3] = {64, (cuuint32_t)box_rows, (cuuint32_t)box_panels}, es[3] = {1, 1, 1};
        encode(tm, CU_TENSOR_MAP_DATA_TYPE_BFLOAT16, 3, ptr, gd, gs, box, es, CU_TENSOR_MAP_INTERLEAVE_NONE,
               CU_TENSOR_MAP_SWIZZLE_128B, CU_TENSOR_MAP_L2_PROMOTION_L2_256B, CU_TENSOR_MAP_FLOAT_OOB_FILL_NONE);
    };
    panels(&p.tm_wq, d_in[7], DM, 4096, 128, 2);
    panels(&p.tm_wuk, d_in[8], 512, 4096, 128, 2);
    panels(&p.tm_wuv, d_in[9], 512, 4096, 128, 2);
    panels(&p.tm_wo, d_in[10], 4096, DM, 32, 9);
    panels(&p.tm_wf, d_in[10], 4096, DM, FR, 1);
    panels(&p.tm_ckv, d_in[6], 4 * SK, 512, 32, 8);
    {
        const cuuint64_t gd[3] = {4096, 192, 3}, gs[2] = {8192, 192 * 8192};
        const cuuint32_t box[3] = {32, 192, 3}, es[3] = {1, 1, 1};
        encode(&p.tm_j0, CU_TENSOR_MAP_DATA_TYPE_BFLOAT16, 3, d_in[3], gd, gs, box, es, CU_TENSOR_MAP_INTERLEAVE_NONE,
               CU_TENSOR_MAP_SWIZZLE_64B, CU_TENSOR_MAP_L2_PROMOTION_L2_128B, CU_TENSOR_MAP_FLOAT_OOB_FILL_NONE);
    }
    {
        const cuuint64_t gd[3] = {DM, 512, 8}, gs[2] = {8 * DM * 2, DM * 2};
        const cuuint32_t box[3] = {72, 16, 8}, es[3] = {1, 1, 1};
        encode(&p.tm_wl, CU_TENSOR_MAP_DATA_TYPE_BFLOAT16, 3, d_in[4], gd, gs, box, es, CU_TENSOR_MAP_INTERLEAVE_NONE,
               CU_TENSOR_MAP_SWIZZLE_NONE, CU_TENSOR_MAP_L2_PROMOTION_L2_128B, CU_TENSOR_MAP_FLOAT_OOB_FILL_NONE);
    }
    p.xa = (const __nv_bfloat16*)d_in[0];
    p.kc = (const __nv_bfloat16*)d_in[1];
    p.vc = (const __nv_bfloat16*)d_in[2];
    p.wo = (const __nv_bfloat16*)d_in[4];
    p.xb = (const __nv_bfloat16*)d_in[5];
    p.wob = (const __nv_bfloat16*)d_in[10];
    p.out = (__nv_bfloat16*)d_out;
    if (ncl >= MINCL) {
        cfg.gridDim = dim3(8 * ncl);
        cudaLaunchKernelEx(&cfg, fused_decode_kernel<true>, p);
    } else {
        fused_decode_kernel<false><<<nsm, 256, SMEM_BYTES, cudaStreamPerThread>>>(p);
    }
}
```

```cpp
#include <cuda_runtime.h>
#include <cuda.h>
#include <cuda_bf16.h>
#include <stdint.h>

namespace {

constexpr int NH = 32, SK = 4096, DM = 576;
constexpr int KEYS = 128;
constexpr int UPP = SK / KEYS;
constexpr int NUK = 4 * NH * UPP;
constexpr int TILE_BYTES = KEYS * 256;
#define NWORK 2
constexpr int NW = NWORK;
constexpr int NBCTA = 32;
constexpr int MINCL = 15;
constexpr int NFIN = 72;
constexpr int SLOT = 32768;
constexpr int NSLOT = 6;
constexpr int BRING = 5;
constexpr int J0W = 5 * SLOT;
constexpr int MISC = NSLOT * SLOT + 4096;
constexpr int XP = 1168, CP = 1040, QP = 272;
constexpr int M_XA = MISC;
constexpr int M_XB = M_XA + 4 * XP;
constexpr int M_CH = M_XB + 4 * XP;
constexpr int M_CL = M_CH + 4 * CP;
constexpr int M_QB = M_CL + 4 * CP;
constexpr int M_QA = M_CH;
constexpr int M_J0 = M_QB + 4 * QP;
constexpr int M_P = M_J0 + 2048;
constexpr int M_ALPHA = M_P + 2560;
constexpr int M_OMEGA = M_ALPHA + 128;
constexpr int M_BAR = M_OMEGA + 128;
constexpr int M_HELP = M_BAR + 128;
constexpr int F_W = 3 * SLOT;
constexpr int F_X = NSLOT * SLOT;
constexpr int F_RECV = F_X + 8192;
constexpr int F_BAR = M_P;
constexpr int SMEM_BYTES = M_HELP + 128 + 1024;
static_assert(F_RECV + 8192 <= M_J0, "output phase layout");
static_assert(SMEM_BYTES <= 232448 && M_BAR % 8 == 0 && M_QA % 16 == 0 && M_P % 16 == 0, "smem layout");
#define XW 2
#define X3 1
#define X3C 2
#define NEARLY 2
#define BD 4
#define FPF 3
#define FSLEEP 800
#define VS0 24
#define FJ 220
#define FP 700
#define FS 1
#define NPOLL 2
#define PGAP 200
static_assert(NW + XW <= 4 && NEARLY <= NW + XW && BD <= BRING, "slots 4 and 5 hold the finisher weights");
constexpr int KMIN = 2, KMAX = 4, VMIN = 0, VMAX = 4;
constexpr float SCALE = 0.08838834764831845f;
constexpr float LOG2E = 1.4426950408889634f;
constexpr unsigned SPIN_LIMIT = 1u << 24;

#define NREP 2
constexpr int C_QUEUE = 0, C_KDONE = 1, C_BBAR = 3, C_LINES = 5;

struct Params {
    const __nv_bfloat16 *kc, *xa, *vc, *wo, *xb;
    __nv_bfloat16* out;
    CUtensorMap tm_j0;
    CUtensorMap tm_wq, tm_wuk, tm_ckv, tm_wuv, tm_wo;
    CUtensorMap tm_wl;
    CUtensorMap tm_wf;
};

__device__ unsigned g_epoch;
__device__ unsigned g_ctl[2][C_LINES][32];
__device__ uint2 g_qll[4 * 2048];
__device__ uint2 g_scores[128 * SK / 4];
__device__ float2 g_stats[128 * UPP];
__device__ float4 g_oacc[128 * 32];
__device__ unsigned g_vdone[NREP * NH][32];
__device__ uint4 g_qabs[4 * 8 * 4 * 4 * 32];
__device__ float2 g_bpart[NBCTA * NH * 256];
__device__ float2 g_bml[NBCTA * NH];
__device__ uint4 g_ctx[NH * 128];
__device__ uint4 g_outb[NBCTA * NH * 36];

#define TS(i)
#define TSV(i, v)
#define LAND(i)
#define CLK(x)
#define ACC(a, x, y)

__device__ __forceinline__ uint32_t smem_u32(const void* p) { return (uint32_t)__cvta_generic_to_shared(p); }
__device__ __forceinline__ void mbar_init(uint32_t bar, uint32_t cnt) {
    asm volatile("mbarrier.init.shared::cta.b64 [%0], %1;" ::"r"(bar), "r"(cnt) : "memory");
}
__device__ __forceinline__ void mbar_expect_tx(uint32_t bar, uint32_t bytes) {
    asm volatile("mbarrier.arrive.expect_tx.shared::cta.b64 _, [%0], %1;" ::"r"(bar), "r"(bytes) : "memory");
}
__device__ __forceinline__ bool mbar_try(uint32_t bar, uint32_t parity) {
    uint32_t ok;
    asm volatile("{\n.reg .pred p;\nmbarrier.try_wait.parity.shared::cta.b64 p, [%1], %2;\nselp.u32 %0, 1, 0, p;\n}\n"
                 : "=r"(ok) : "r"(bar), "r"(parity) : "memory");
    return ok;
}
__device__ __forceinline__ void mbar_wait(uint32_t bar, uint32_t parity) {
    unsigned n = 0;
    while (!mbar_try(bar, parity)) { if (++n > SPIN_LIMIT) __trap(); }
}
__device__ __forceinline__ void bulk_load(uint32_t dst, const void* src, uint32_t bytes, uint32_t bar, uint64_t pol) {
    asm volatile("cp.async.bulk.shared::cluster.global.mbarrier::complete_tx::bytes.L2::cache_hint [%0], [%1], %2, [%3], %4;"
                 ::"r"(dst), "l"(src), "r"(bytes), "r"(bar), "l"(pol) : "memory");
}
__device__ __forceinline__ void tma3d(uint32_t dst, const CUtensorMap* tm, int c0, int c1, int c2, uint32_t bar, uint64_t pol) {
    asm volatile("cp.async.bulk.tensor.3d.shared::cluster.global.mbarrier::complete_tx::bytes.L2::cache_hint [%0], [%1, {%3,%4,%5}], [%2], %6;"
                 ::"r"(dst), "l"(tm), "r"(bar), "r"(c0), "r"(c1), "r"(c2), "l"(pol) : "memory");
}
__device__ __forceinline__ void l2_prefetch(const void* src, uint32_t bytes) {
    asm volatile("cp.async.bulk.prefetch.L2.global [%0], %1;" ::"l"(src), "r"(bytes) : "memory");
}
__device__ __forceinline__ void ldsm4(uint32_t (&r)[4], uint32_t addr) {
    asm volatile("ldmatrix.sync.aligned.m8n8.x4.shared.b16 {%0,%1,%2,%3}, [%4];"
                 : "=r"(r[0]), "=r"(r[1]), "=r"(r[2]), "=r"(r[3]) : "r"(addr));
}
__device__ __forceinline__ void ldsm4t(uint32_t (&r)[4], uint32_t addr) {
    asm volatile("ldmatrix.sync.aligned.m8n8.x4.trans.shared.b16 {%0,%1,%2,%3}, [%4];"
                 : "=r"(r[0]), "=r"(r[1]), "=r"(r[2]), "=r"(r[3]) : "r"(addr));
}
__device__ __forceinline__ void mma16816(float (&d)[4], const uint32_t (&a)[4], uint32_t b0, uint32_t b1) {
    asm("mma.sync.aligned.m16n8k16.row.col.f32.bf16.bf16.f32 {%0,%1,%2,%3}, {%4,%5,%6,%7}, {%8,%9}, {%0,%1,%2,%3};"
        : "+f"(d[0]), "+f"(d[1]), "+f"(d[2]), "+f"(d[3])
        : "r"(a[0]), "r"(a[1]), "r"(a[2]), "r"(a[3]), "r"(b0), "r"(b1));
}
__device__ __forceinline__ uint32_t lds32(uint32_t a) {
    uint32_t v;
    asm volatile("ld.shared.u32 %0, [%1];" : "=r"(v) : "r"(a));
    return v;
}
__device__ __forceinline__ unsigned ld_acquire(const unsigned* p) {
    unsigned v;
    asm volatile("ld.acquire.gpu.global.u32 %0, [%1];" : "=r"(v) : "l"(p) : "memory");
    return v;
}
__device__ __forceinline__ uint2 ld_relaxed8(const void* p) {
    uint2 v;
    asm volatile("ld.relaxed.gpu.global.v2.u32 {%0,%1}, [%2];" : "=r"(v.x), "=r"(v.y) : "l"(p) : "memory");
    return v;
}
__device__ __forceinline__ unsigned ld_relaxed4(const void* p) {
    unsigned v;
    asm volatile("ld.relaxed.gpu.global.u32 %0, [%1];" : "=r"(v) : "l"(p) : "memory");
    return v;
}
__device__ __forceinline__ unsigned atom_inc(unsigned* p) {
    unsigned v;
    asm volatile("atom.relaxed.gpu.global.inc.u32 %0, [%1], 0x7fffffff;" : "=r"(v) : "l"(p) : "memory");
    return v;
}
__device__ __forceinline__ unsigned long long ld_relaxed64(const void* p) {
    unsigned long long v;
    asm volatile("ld.relaxed.gpu.global.u64 %0, [%1];" : "=l"(v) : "l"(p) : "memory");
    return v;
}
__device__ __forceinline__ void st_relaxed64(void* p, unsigned long long v) {
    asm volatile("st.relaxed.gpu.global.u64 [%0], %1;" ::"l"(p), "l"(v) : "memory");
}
__device__ __forceinline__ float4 ld_relaxed16(const void* p) {
    float4 v;
    asm volatile("ld.relaxed.gpu.global.v4.f32 {%0,%1,%2,%3}, [%4];" : "=f"(v.x), "=f"(v.y), "=f"(v.z), "=f"(v.w) : "l"(p) : "memory");
    return v;
}
__device__ __forceinline__ uint32_t mapa(uint32_t a, uint32_t rank) {
    uint32_t r;
    asm("mapa.shared::cluster.u32 %0, %1, %2;" : "=r"(r) : "r"(a), "r"(rank));
    return r;
}
__device__ __forceinline__ void mbar_wait_cluster(uint32_t bar, uint32_t parity) {
    unsigned n = 0;
    while (true) {
        uint32_t ok;
        asm volatile("{\n.reg .pred p;\nmbarrier.test_wait.parity.relaxed.cluster.shared::cta.b64 p, [%1], %2;\nselp.u32 %0, 1, 0, p;\n}\n"
                     : "=r"(ok) : "r"(bar), "r"(parity) : "memory");
        if (ok) break;
        if (++n > SPIN_LIMIT) __trap();
    }
    asm volatile("fence.acquire.sync_restrict::shared::cluster.cluster;" ::: "memory");
}
__device__ __forceinline__ void mbar_spin(uint32_t bar) {
    unsigned n = 0;
    while (true) {
        uint32_t ok;
        asm volatile("{\n.reg .pred p;\nmbarrier.test_wait.parity.shared::cta.b64 p, [%1], 0;\nselp.u32 %0, 1, 0, p;\n}\n"
                     : "=r"(ok) : "r"(bar) : "memory");
        if (ok) break;
        if (++n > (SPIN_LIMIT << 2)) __trap();
    }
}
__device__ __forceinline__ void fence_gpu() { asm volatile("fence.acq_rel.gpu;" ::: "memory"); }
__device__ __forceinline__ void red_add_u32(unsigned* p, unsigned v) {
    asm volatile("red.relaxed.gpu.global.add.u32 [%0], %1;" ::"l"(p), "r"(v) : "memory");
}
__device__ __forceinline__ void st_tagged2(void* p, float a, float b, unsigned tag) {
    const unsigned long long hi = (unsigned long long)tag << 32;
    asm volatile("st.relaxed.gpu.global.v2.b64 [%0], {%1,%2};" ::"l"(p), "l"(hi | __float_as_uint(a)), "l"(hi | __float_as_uint(b)) : "memory");
}
__device__ __forceinline__ ulonglong2 ld_tagged2(const void* p) {
    ulonglong2 v;
    asm volatile("ld.relaxed.gpu.global.v2.b64 {%0,%1}, [%2];" : "=l"(v.x), "=l"(v.y) : "l"(p) : "memory");
    return v;
}
__device__ __forceinline__ float4 atom_add_f4(void* p, float a, float b, float c, float d) {
    float4 r;
    asm volatile("atom.relaxed.gpu.global.add.v4.f32 {%0,%1,%2,%3}, [%4], {%5,%6,%7,%8};"
                 : "=f"(r.x), "=f"(r.y), "=f"(r.z), "=f"(r.w) : "l"(p), "f"(a), "f"(b), "f"(c), "f"(d) : "memory");
    return r;
}
__device__ __forceinline__ void red_release_cta_shared(uint32_t a, unsigned v) {
    asm volatile("red.release.cta.shared::cta.add.u32 [%0], %1;" ::"r"(a), "r"(v) : "memory");
}
__device__ __forceinline__ unsigned ld_acquire_cta_shared(uint32_t a) {
    unsigned v;
    asm volatile("ld.acquire.cta.shared::cta.u32 %0, [%1];" : "=r"(v) : "r"(a) : "memory");
    return v;
}
__device__ __forceinline__ void st_release_cta_shared(uint32_t a, unsigned v) {
    asm volatile("st.release.cta.shared::cta.u32 [%0], %1;" ::"r"(a), "r"(v) : "memory");
}
__device__ __forceinline__ void wait_count(const unsigned* p, unsigned target) {
    unsigned n = 0;
    while (ld_acquire(p) < target) { if (++n > SPIN_LIMIT) __trap(); }
}
__device__ __forceinline__ uint32_t pack_bf16(float lo, float hi) {
    uint32_t r;
    asm("cvt.rn.bf16x2.f32 %0, %1, %2;" : "=r"(r) : "f"(hi), "f"(lo));
    return r;
}
__device__ __forceinline__ float bf_lo(uint32_t v) { return __uint_as_float(v << 16); }
__device__ __forceinline__ float bf_hi(uint32_t v) { return __uint_as_float(v & 0xffff0000u); }
__device__ __forceinline__ float ex2(float x) { float y; asm("ex2.approx.ftz.f32 %0, %1;" : "=f"(y) : "f"(x)); return y; }
__device__ __forceinline__ float expsub(float a, float b) { return ex2((a - b) * LOG2E); }
__device__ __forceinline__ float warp_max(float v) {
#pragma unroll
    for (int m = 16; m; m >>= 1) v = fmaxf(v, __shfl_xor_sync(~0u, v, m));
    return v;
}
__device__ __forceinline__ float warp_sum(float v) {
#pragma unroll
    for (int m = 16; m; m >>= 1) v += __shfl_xor_sync(~0u, v, m);
    return v;
}
template <bool CLU>
__device__ __forceinline__ unsigned unit_block(int u) {
    const unsigned x = ((unsigned)u & (NUK - 1)) / UPP;
    const int lg = u < NUK ? min(KMAX, max(KMIN, 29 - __clz(x | 1))) : (CLU && (int)x >= 4 * VS0 ? 0 : min(VMAX, max(VMIN, 29 - __clz((127 - x) | 1))));
    const unsigned r = x & ((4u << lg) - 1);
    return ((x - r + (r & ((1u << lg) - 1)) * 4 + (r >> lg)) * UPP) | ((unsigned)u & (UPP - 1));
}
__device__ __forceinline__ const char* block_src(const void* base, unsigned blk) {
    const unsigned po = blk / UPP;
    return reinterpret_cast<const char*>(base) + (size_t)(((po & 3) * NH + (po >> 2)) * UPP + blk % UPP) * TILE_BYTES;
}

template <bool CLU>
__device__ __forceinline__ void a_worker(const Params& p, int un, bool once, bool pre, bool hold, int nstatic, uint32_t slot, uint32_t bar,
                                         uint32_t help, unsigned epoch, uint64_t pol) {
    constexpr int NU = 2 * NUK;
    const int lane = threadIdx.x & 31, g = lane >> 2, t = lane & 3;
    const int li = lane & 7;
    uint32_t kaddr[4], vaddr[8];
    {
        const int e = (lane >> 3) & 1, kk = lane >> 4;
#pragma unroll
        for (int s = 0; s < 4; s++) kaddr[s] = slot + (16 * li + e) * 256 + ((2 * s + kk + li) & 7) * 16;
        const int vrow = 4 * (li >> 1) + (li & 1) + 2 * kk;
#pragma unroll
        for (int c = 0; c < 8; c++) vaddr[c] = slot + vrow * 256 + e * 128 + ((c + li) & 7) * 16;
#pragma unroll
        for (int c = 0; c < 8; c++) asm volatile("" : "+r"(vaddr[c]));
    }
    const uint32_t vmask = (g >> 1) != t ? 0u : ((g & 1) ? 0xffff0000u : 0xffffu);
    int kseen = -1;
    unsigned long long H0 = 0, H1 = 0;
    auto header = [&](int v, unsigned vb) {
        if (v >= NU) return;
        const void *a0, *a1;
        if (v < NUK) {
            const unsigned po = vb / UPP;
            a0 = g_qll + (po & 3) * 2048 + (po >> 2) * 64 + lane;
            a1 = reinterpret_cast<const uint2*>(a0) + 32;
        } else {
            const int half = vb / (NUK / 2);
            if (half > kseen) {
                unsigned n = 0;
                while (ld_acquire_cta_shared(help + 12 + 4 * half) == 0) { if (++n > (SPIN_LIMIT << 4)) __trap(); }
                kseen = half;
            }
            a0 = &g_scores[vb * (KEYS / 4) + lane];
            a1 = &g_stats[(vb / UPP) * UPP + lane];
        }
        H0 = ld_relaxed64(a0);
        H1 = ld_relaxed64(a1);
    };
    asm volatile("bar.sync 2, %0;" ::"n"(32 * (NW + XW + 1)) : "memory");
    epoch = __shfl_sync(~0u, epoch, 0);
    if (hold) { unsigned n = 0; while (ld_acquire_cta_shared(help + 24) < 2) { if (++n > (SPIN_LIMIT << 4)) __trap(); } }
    unsigned (*ctl)[32] = g_ctl[epoch & 1];
    const unsigned tag = epoch + 1;
    unsigned nxt = once ? NU : 0;
    int u = -1;
    unsigned bu = 0, bn = unit_block<CLU>(un);
    bool have = false;
    uint32_t phase = 0;
    unsigned kpend = 0;
    const unsigned zero = gridDim.x >> 24;
    uint32_t Q[16];
    float4 oret = make_float4(0.f, 0.f, 0.f, 0.f);
    while (true) {
        const char* nsrc = block_src(un < NUK ? p.kc : p.vc, bn);
        float4* odst = &g_oacc[(bu / UPP) * 32 + lane];
        unsigned* vdst = &g_vdone[(lane & (NREP - 1)) * NH + bu / (4 * UPP)][0];
        float d[8][4];
        CLK(c1);
        asm volatile("" : "+l"(odst));
        if (u >= NUK) {
#pragma unroll
            for (int j = 0; j < 8; j++) { d[j][0] = d[j][1] = d[j][2] = d[j][3] = 0.f; }
            mbar_wait(bar, phase);
            LAND(NUK + bu);
            uint32_t a[2][8][4];
#pragma unroll
            for (int c = 0; c < 8; c++) ldsm4t(a[0][c], vaddr[c]);
#pragma unroll
            for (int j = 0; j < 8; j++) {
                if (j < 7) {
#pragma unroll
                    for (int c = 0; c < 8; c++) ldsm4t(a[(j + 1) & 1][c], vaddr[c] + (j + 1) * 4096);
                }
#pragma unroll
                for (int c = 0; c < 8; c++) mma16816(d[c], a[j & 1][c], Q[2 * j], Q[2 * j + 1]);
            }
            float o[4];
#pragma unroll
            for (int r = 0; r < 2; r++) {
                o[2 * r] = d[0][2 * r] + d[7][2 * r + 1];
                o[2 * r + 1] = d[0][2 * r + 1] + d[1][2 * r];
#pragma unroll
                for (int k = 1; k < 4; k++) {
                    const int src = (lane & 28) | ((t - k) & 3);
                    o[2 * r] += __shfl_sync(~0u, d[2 * k][2 * r] + d[2 * k - 1][2 * r + 1], src);
                    o[2 * r + 1] += __shfl_sync(~0u, d[2 * k][2 * r + 1] + d[2 * k + 1][2 * r], src);
                }
            }
            oret = atom_add_f4(odst, o[0], o[1], o[2], o[3]);
        } else if (u >= 0) {
#pragma unroll
            for (int j = 0; j < 8; j++) { d[j][0] = d[j][1] = d[j][2] = d[j][3] = 0.f; }
            mbar_wait(bar, phase);
            LAND(bu);
            uint32_t a[2][8][4];
#pragma unroll
            for (int j = 0; j < 8; j++) ldsm4(a[0][j], kaddr[0] + (4 * (j & 3) + 2 * (j >> 2)) * 256);
#pragma unroll
            for (int s = 0; s < 8; s++) {
                if (s < 7) {
#pragma unroll
                    for (int j = 0; j < 8; j++)
                        ldsm4(a[(s + 1) & 1][j], kaddr[(s + 1) & 3] + (4 * (j & 3) + 2 * (j >> 2)) * 256 + ((s + 1) >> 2) * 128);
                }
#pragma unroll
                for (int j = 0; j < 8; j++)
                    mma16816(d[j], a[s & 1][j], Q[(s & 4) * 2 + ((2 * s - 2 * j) & 7)], Q[(s & 4) * 2 + ((2 * s + 1 - 2 * j) & 7)]);
            }
        }
        if (u >= 0) phase ^= 1;
        CLK(c2b);
        if (un < NU && lane == 0) {
            if (!once) nxt = atom_inc(&ctl[C_QUEUE][0]);
            if (u >= 0 || !pre) {
                mbar_expect_tx(bar, TILE_BYTES);
                bulk_load(slot, nsrc, TILE_BYTES, bar, pol);
            }
        }
        const uint32_t tiss = (uint32_t)clock();
        CLK(c3);
        if ((unsigned)u < (unsigned)NUK) {
            const int j0 = (t - (g >> 1)) & 3;
            float v[4];
#pragma unroll
            for (int q = 0; q < 4; q++) {
                const int jq = (q >> 1) * 4, e = (q & 1) * 2;
                const float x0 = (g & 1) ? d[jq + 0][e + 1] : d[jq + 0][e];
                const float x1 = (g & 1) ? d[jq + 1][e + 1] : d[jq + 1][e];
                const float x2 = (g & 1) ? d[jq + 2][e + 1] : d[jq + 2][e];
                const float x3 = (g & 1) ? d[jq + 3][e + 1] : d[jq + 3][e];
                const float y0 = (j0 & 1) ? x1 : x0, y1 = (j0 & 1) ? x3 : x2;
                v[q] = (j0 & 2) ? y1 : y0;
            }
            const uint32_t r0 = pack_bf16(v[0], v[1]), r1 = pack_bf16(v[2], v[3]);
            const uint32_t s0 = pack_bf16(bf_lo(r0) * SCALE, bf_hi(r0) * SCALE);
            const uint32_t s1 = pack_bf16(bf_lo(r1) * SCALE, bf_hi(r1) * SCALE);
            g_scores[bu * (KEYS / 4) + 4 * g + j0] = make_uint2(s0, s1);
            const float f0 = bf_lo(s0), f1 = bf_hi(s0), f2 = bf_lo(s1), f3 = bf_hi(s1);
            const float m = warp_max(fmaxf(fmaxf(f0, f1), fmaxf(f2, f3)));
            const float l = warp_sum((expsub(f0, m) + expsub(f1, m)) + (expsub(f2, m) + expsub(f3, m)));
            if (lane == 0) g_stats[bu] = make_float2(m, l);
            kpend++;
            if (un / (NUK / 2) != u / (NUK / 2)) {
                __syncwarp();
                if (lane == 0) {
                    red_release_cta_shared(help + 4 * (u / (NUK / 2)), kpend);
                    if (un >= NUK) red_release_cta_shared(help + 8, 1u);
                }
                kpend = 0;
            }
        }
        CLK(c4);
        int unn = NU;
        if (un < NU) {
            unsigned n = 0;
            while (true) {
                if (!have) header(un, bn);
                if (un >= NUK || __all_sync(~0u, (uint32_t)(H0 >> 32) == tag && (uint32_t)(H1 >> 32) == tag)) break;
                if (++n > SPIN_LIMIT) __trap();
                have = false;
            }
            if (un >= NUK) {
                const uint32_t s0 = (uint32_t)H0, s1 = (uint32_t)(H0 >> 32);
                const float mu = __uint_as_float((uint32_t)H1);
                const float m = warp_max(mu);
                const float l = warp_sum(__uint_as_float((uint32_t)(H1 >> 32)) * expsub(mu, m));
                const float inv = 1.0f / l;
                const uint32_t w0 = pack_bf16(expsub(bf_lo(s0), m) * inv, expsub(bf_hi(s0), m) * inv);
                const uint32_t w1 = pack_bf16(expsub(bf_lo(s1), m) * inv, expsub(bf_hi(s1), m) * inv);
#pragma unroll
                for (int j = 0; j < 8; j++) {
                    Q[2 * j] = __shfl_sync(~0u, w0, 4 * j + t) & vmask;
                    Q[2 * j + 1] = __shfl_sync(~0u, w1, 4 * j + t) & vmask;
                }
            } else {
#pragma unroll
                for (int j = 0; j < 8; j++) {
                    const int src = (((j + g) & 7) << 2) + t;
                    Q[j] = __shfl_sync(~0u, (uint32_t)H0, src);
                    Q[8 + j] = __shfl_sync(~0u, (uint32_t)H1, src);
                }
            }
            unn = nstatic + (int)__shfl_sync(~0u, nxt, 0);
            if (CLU && !once && unn >= NU && lane == 0)
                asm volatile("st.relaxed.cta.shared::cta.u32 [%0], %1;" ::"r"(help + 28), "r"((tiss + (FJ - (unn - NU)) * 20) | 1u) : "memory");
        }
        if (u >= NUK && lane < NREP)
            red_add_u32(vdst,
                        1u + ((__float_as_uint(oret.x) | __float_as_uint(oret.y) | __float_as_uint(oret.z) | __float_as_uint(oret.w)) & zero));
        if (un >= NU) break;
        bu = bn;
        have = !(un < NUK && unn >= NUK && !(un >= NUK / 2 && unn < NUK + NUK / 2));
        bn = unit_block<CLU>(unn);
        if (have) header(unn, bn);
        u = un;
        un = unn;
    }
}

__device__ __forceinline__ void k_helper(uint32_t help, unsigned epoch) {
    if ((threadIdx.x & 31) != 0) return;
    unsigned (*ctl)[32] = g_ctl[epoch & 1];
    unsigned sent0 = 0, sent1 = 0, n = 0;
    int seen = 0;
    bool fin = false;
    while (!fin || seen < 2) {
        if (!fin) {
            fin = ld_acquire_cta_shared(help + 8) == NW + XW;
            const unsigned c0 = ld_acquire_cta_shared(help), c1 = ld_acquire_cta_shared(help + 4);
            if (c0 != sent0 || c1 != sent1) {
                fence_gpu();
                if (c0 != sent0) red_add_u32(&ctl[C_KDONE][0], c0 - sent0);
                if (c1 != sent1) red_add_u32(&ctl[C_KDONE + 1][0], c1 - sent1);
                sent0 = c0; sent1 = c1;
            }
        }
        if (seen < 2 && ld_acquire(&ctl[C_KDONE + seen][0]) >= NUK / 2) {
            st_release_cta_shared(help + 12 + 4 * seen, 1u);
            seen++;
        } else {
            __nanosleep(300);
        }
        if (++n > SPIN_LIMIT) __trap();
    }
}

__device__ __forceinline__ void v_poller(uint32_t sbase, int f, int w) {
    const int lane = threadIdx.x & 31;
    const unsigned (*cp)[32] = &g_vdone[((f * NPOLL + w) % NREP) * NH];
    unsigned n = 0;
    while (ld_acquire_cta_shared(sbase + M_HELP + 12) == 0) { __nanosleep(1000); if (++n > SPIN_LIMIT) __trap(); }
    int h = 0;
    bool fast = false;
    while (h < NH) {
        const unsigned r = __ballot_sync(~0u, ld_acquire(&cp[min(h + (lane & 3), NH - 1)][0]) >= 4 * UPP) & 15u;
        if (r & 1) {
            h = min(NH, h + __ffs(~r) - 1);
            __syncwarp();
            if (lane == 0) asm volatile("red.release.cta.shared::cta.max.u32 [%0], %1;" ::"r"(sbase + M_HELP + 20), "r"(h) : "memory");
        }
        if (h < NH - 4) {
            __nanosleep(h ? 300 : 1000);
        } else if (!fast) {
            fast = true;
            const long long t0 = clock64();
            while (clock64() - t0 < w * PGAP) {}
        }
        if (++n > SPIN_LIMIT) __trap();
    }
}
__device__ __forceinline__ void finisher(const Params& p, uint32_t sbase, int f) {
    const int lane = threadIdx.x & 31;
    {
        const char* wg = reinterpret_cast<const char*>(p.wo);
        const uint32_t dst = sbase + 4 * SLOT + (16 * (lane & 7) + (lane >> 3)) * 16;
#pragma unroll 1
        for (int h = -FPF - 4; h < NH; h++) {
            if (lane == 0 && (unsigned)(h + FPF) < (unsigned)NH) l2_prefetch(wg + (size_t)(h + FPF) * 147456 + f * 2048, 2048);
            if (h >= 0) {
#pragma unroll
                for (int r = 0; r < 4; r++)
                    asm volatile("cp.async.cg.shared.global [%0], [%1], 16;" ::"r"(dst + h * 2048 + ((r & 1) * 4 + (r >> 1) * 8) * 16),
                                 "l"(wg + (size_t)(h * 128 + r * 32 + lane) * (DM * 2) + f * 16) : "memory");
            }
            __nanosleep(FSLEEP);
        }
        asm volatile("cp.async.wait_all;" ::: "memory");
        __syncwarp();
    }
    TS(11);
    const float4* vec = g_oacc + ((lane >> 2) & 3) * 32 + (lane >> 4) * 16 + (lane & 3);
    float acc[2][2][4];
#pragma unroll
    for (int i = 0; i < 16; i++) acc[i >> 3][(i >> 2) & 1][i & 3] = 0.f;
    uint32_t* outp = reinterpret_cast<uint32_t*>(p.out + (lane >> 2) * (2 * DM) + f * 8 + (lane & 3) * 2);
    uint32_t wa = sbase + 4 * SLOT + lane * 16;
    auto project = [&](const float4 (&x)[4], const uint32_t (&w)[4][4]) {
#pragma unroll
        for (int s = 0; s < 4; s++) {
            const uint32_t a[4] = {pack_bf16(x[s].x, x[s].y), 0u, pack_bf16(x[s].z, x[s].w), 0u};
            mma16816(acc[0][s & 1], a, w[s >> 1][(s & 1) * 2], w[s >> 1][(s & 1) * 2 + 1]);
            mma16816(acc[1][s & 1], a, w[2 + (s >> 1)][(s & 1) * 2], w[2 + (s >> 1)][(s & 1) * 2 + 1]);
        }
    };
    int h = 0;
    unsigned n = 0;
    while (h < NH) {
        uint32_t w[4][4];
#pragma unroll
        for (int q = 0; q < 4; q++) ldsm4t(w[q], wa + q * 512);
        int ready;
        while ((ready = ld_acquire_cta_shared(sbase + M_HELP + 20)) <= h) {
            if (h < NH - 3) __nanosleep(100);
            if (++n > (SPIN_LIMIT << 4)) __trap();
        }
        float4 x[4], y[4];
#pragma unroll
        for (int s = 0; s < 4; s++) x[s] = ld_relaxed16(vec + s * 4);
        const bool two = ready > h + 1;
        if (two) {
#pragma unroll
            for (int s = 0; s < 4; s++) y[s] = ld_relaxed16(vec + 128 + s * 4);
        }
        project(x, w);
        if (two) {
#pragma unroll
            for (int q = 0; q < 4; q++) ldsm4t(w[q], wa + 2048 + q * 512);
            project(y, w);
        }
        const int nr = two ? 2 : 1;
        h += nr;
        vec += nr * 128;
        wa += nr * 2048;
        const float o0 = acc[0][0][0] + acc[0][1][0] + __shfl_down_sync(~0u, acc[1][0][0] + acc[1][1][0], 16);
        const float o1 = acc[0][0][1] + acc[0][1][1] + __shfl_down_sync(~0u, acc[1][0][1] + acc[1][1][1], 16);
        asm volatile("{\n.reg .pred p;\nsetp.ne.u32 p, %2, 0;\n@p st.global.u32 [%0], %1;\n}" ::"l"(outp), "r"(pack_bf16(o0, o1)),
                     "r"((uint32_t)(lane < 16 && h == NH)) : "memory");
    }
}

__device__ __forceinline__ void out_fetch(uint32_t sbase, int step, int h) {
    const int lane = threadIdx.x & 31;
    float4 x[4];
#pragma unroll
    for (int b = 0; b < 4; b++) x[b] = ld_relaxed16(&g_oacc[(h * 4 + b) * 32 + lane]);
#pragma unroll
    for (int b = 0; b < 4; b++)
        asm volatile("st.shared.v2.u32 [%0], {%1,%2};" ::"r"(sbase + F_X + step * 1024 + (lane >> 2) * 128 + (lane & 3) * 8 + b * 32),
                     "r"(pack_bf16(x[b].x, x[b].y)), "r"(pack_bf16(x[b].z, x[b].w)) : "memory");
}
__device__ __forceinline__ void out_early(uint32_t sbase, int c, int rank, unsigned tag) {
    const int lane = threadIdx.x & 31;
    if (lane < 10) {
        mbar_init(sbase + F_BAR + 16 + lane * 8, lane < 8 ? 1 : 4);
        if (lane < 8) mbar_expect_tx(sbase + F_BAR + 16 + lane * 8, 16384);
    }
    asm volatile("fence.mbarrier_init.release.cluster;" ::: "memory");
    unsigned n = 0;
#pragma unroll 1
    for (int i = 0; i < 3; i++) {
        while (ld_acquire(&g_vdone[(c & (NREP - 1)) * NH + 8 * i + rank][0]) < 4 * UPP) { __nanosleep(500); if (++n > SPIN_LIMIT) __trap(); }
        out_fetch(sbase, 4 + i, 8 * i + rank);
#pragma unroll 1
        for (int j = 0; j < 16 && i == 0;) {
            const ulonglong2 v = ld_tagged2(&g_ctx[((j >> 2) * 8 + rank) * 128 + (j & 3) * 32 + lane]);
            if (__all_sync(~0u, (unsigned)(v.x >> 32) == tag && (unsigned)(v.y >> 32) == tag)) {
                asm volatile("st.shared.v2.u32 [%0], {%1,%2};" ::"r"(sbase + F_X + (j * 32 + lane) * 8), "r"((uint32_t)v.x), "r"((uint32_t)v.y) : "memory");
                j++;
            } else {
                __nanosleep(500);
                if (++n > SPIN_LIMIT) __trap();
            }
        }
    }
    __syncwarp();
    if (lane == 0) st_release_cta_shared(sbase + M_HELP + 32, 1u);
}
__device__ __forceinline__ void out_late(uint32_t sbase, int rank, int w) {
    unsigned n = 0;
    while (ld_acquire_cta_shared(sbase + M_HELP + 16) == 0) { if (++n > (SPIN_LIMIT << 4)) __trap(); }
    while (ld_acquire(&g_vdone[(w & (NREP - 1)) * NH + 24 + rank][0]) < 4 * UPP) { if (++n > SPIN_LIMIT) __trap(); }
    TS(12);
    out_fetch(sbase, 7, 24 + rank);
    __syncwarp();
    if ((threadIdx.x & 31) == 0) st_release_cta_shared(sbase + M_HELP + 36, 1u);
    TS(13);
}
__device__ __forceinline__ void out_project(uint32_t sbase, int rank, int w) {
    const int lane = threadIdx.x & 31, g = lane >> 2, t = lane & 3;
    unsigned n = 0;
    while (ld_acquire_cta_shared(sbase + M_HELP + 32) == 0) { __nanosleep(500); if (++n > SPIN_LIMIT) __trap(); }
    asm volatile("barrier.cluster.wait.acquire.aligned;" ::: "memory");
    uint32_t rdst[4], rbar[4], sw[4];
#pragma unroll
    for (int j = 0; j < 4; j++) {
        rdst[j] = mapa(sbase + F_RECV + (rank * 4 + w) * 128 + g * 16 + (t & 1) * 8, 2 * j + (t >> 1));
        rbar[j] = mapa(sbase + F_BAR, 2 * j + (t >> 1));
        sw[j] = sbase + F_W + w * 4096 + ((lane & 7) + (lane >> 4) * 8) * 128 + (((2 * j + ((lane >> 3) & 1)) ^ (lane & 7)) * 16);
    }
#pragma unroll 1
    for (int r = 0; r < 2; r++) {
        float acc[2][4][4];
#pragma unroll
        for (int i = 0; i < 32; i++) acc[i >> 4][(i >> 2) & 3][i & 3] = 0.f;
#pragma unroll 1
        for (int i = 4 * r; i < 4 * r + 4; i++) {
            if (i == 7) while (ld_acquire_cta_shared(sbase + M_HELP + 36) == 0) { if (++n > (SPIN_LIMIT << 4)) __trap(); }
            uint32_t bf[2][2], a[2][4][4];
#pragma unroll
            for (int s = 0; s < 2; s++)
                asm volatile("ld.shared.v2.u32 {%0,%1}, [%2];" : "=r"(bf[s][0]), "=r"(bf[s][1])
                             : "r"(sbase + F_X + (i * 4 + w) * 256 + s * 128 + (lane & 15) * 8) : "memory");
            const uint32_t ro = (i < 6 ? i : i - 6) * 16384;
            if (i < FS) mbar_wait(sbase + F_BAR + 16 + i * 8, 0);
            mbar_spin(sbase + F_BAR + 16 + i * 8);
#pragma unroll
            for (int s = 0; s < 2; s++)
#pragma unroll
                for (int j = 0; j < 4; j++) ldsm4t(a[s][j], sw[j] + ro + s * 2048);
#pragma unroll
            for (int j = 0; j < 4; j++) {
                mma16816(acc[0][j], a[0][j], bf[0][0], bf[0][1]);
                mma16816(acc[1][j], a[1][j], bf[1][0], bf[1][1]);
            }
            if (i < 2) {
                __syncwarp();
                if (lane == 0) asm volatile("mbarrier.arrive.shared::cta.b64 _, [%0];" ::"r"(sbase + F_BAR + 80 + i * 8) : "memory");
            }
        }
#pragma unroll
        for (int j = 0; j < 4; j++) {
            const float v0 = (t & 2) ? acc[0][j][2] + acc[1][j][2] : acc[0][j][0] + acc[1][j][0];
            const float v1 = (t & 2) ? acc[0][j][3] + acc[1][j][3] : acc[0][j][1] + acc[1][j][1];
            asm volatile("st.async.weak.shared::cluster.mbarrier::complete_tx::bytes.v2.f32 [%0], {%1,%2}, [%3];"
                         ::"r"(rdst[j] + r * 4096), "f"(v0), "f"(v1), "r"(rbar[j] + r * 8) : "memory");
        }
    }
}
__device__ __forceinline__ void out_issue_sum(const Params& p, uint32_t sbase, int c, int rank, uint64_t pol) {
    const int lane = threadIdx.x & 31;
    if (lane == 0) {
        unsigned n = 0;
        while (ld_acquire_cta_shared(sbase + M_HELP + 32) == 0) { __nanosleep(500); if (++n > SPIN_LIMIT) __trap(); }
        asm volatile("prefetch.tensormap [%0];" ::"l"(&p.tm_wf) : "memory");
        asm volatile("prefetch.tensormap [%0];" ::"l"(&p.tm_wl) : "memory");
        uint32_t t0;
        while ((t0 = ld_acquire_cta_shared(sbase + M_HELP + 28)) == 0) { __nanosleep(100); if (++n > SPIN_LIMIT) __trap(); }
#pragma unroll 1
        for (int i = 0; i < 8; i++) {
            const int h = (i & 3) * 8 + rank;
            if (i >= 6) mbar_wait(sbase + F_BAR + 32 + i * 8, 0);
            while ((int)((uint32_t)clock() - t0) < 0) {}
            if (i == 0) TS(16);
            tma3d(sbase + F_W + (i < 6 ? i : i - 6) * 16384, i < 4 ? &p.tm_wf : &p.tm_wl, i < 4 ? 0 : c * 64, i < 4 ? h * 128 : h * 16,
                  i < 4 ? c : 0, sbase + F_BAR + 16 + i * 8, pol);
            t0 += FP;
        }
        TS(17);
    }
    __syncwarp();
    __nv_bfloat16* dst = p.out + (lane >> 3) * (2 * DM) + DM + c * 64 + rank * 8 + (lane & 7);
    const uint32_t src = sbase + F_RECV + (lane >> 3) * 1024 + (lane & 7) * 16;
#pragma unroll 1
    for (int r = 0; r < 2; r++) {
        mbar_wait_cluster(sbase + F_BAR + r * 8, 0);
        float4 x[8];
#pragma unroll
        for (int i = 0; i < 8; i++)
            asm volatile("ld.shared.v4.f32 {%0,%1,%2,%3}, [%4];" : "=f"(x[i].x), "=f"(x[i].y), "=f"(x[i].z), "=f"(x[i].w)
                         : "r"(src + r * 4096 + i * 128) : "memory");
#pragma unroll
        for (int m = 1; m < 8; m <<= 1)
#pragma unroll
            for (int i = 0; i < 8; i += 2 * m) { x[i].x += x[i + m].x; x[i].y += x[i + m].y; x[i].z += x[i + m].z; x[i].w += x[i + m].w; }
        const bool up = lane & 16, od = lane & 8;
        const float a = (up ? x[0].z : x[0].x) + __shfl_xor_sync(~0u, up ? x[0].x : x[0].z, 16);
        const float b = (up ? x[0].w : x[0].y) + __shfl_xor_sync(~0u, up ? x[0].y : x[0].w, 16);
        dst[-r * DM] = __float2bfloat16_rn((od ? b : a) + __shfl_xor_sync(~0u, od ? a : b, 8));
        TS(14 + r);
    }
}

constexpr int BS_WUK = 5, BS_Q = 9, BS_CKV = 11, BS_PART = 27, BS_WUV = 29, BS_END = 33;

__device__ __noinline__ void b_issue(const Params& p, int n, int bi, uint32_t sbase, uint64_t pol) {
    if (n >= BS_END || (n >= BS_Q && n < BS_CKV) || (n >= BS_PART && n < BS_WUV)) return;
    const uint32_t bar = sbase + M_BAR + (NSLOT + n % BRING) * 8;
    const CUtensorMap* tm;
    int row, panel = 2 * bi;
    if (n < BS_WUK) { tm = &p.tm_wq; row = n * 128; }
    else if (n < BS_Q) { tm = &p.tm_wuk; row = (n - BS_WUK) * 128; }
    else if (n < BS_PART) {
        tm = &p.tm_ckv; panel = 0;
        row = (bi >> 3) * SK + ((n - BS_CKV) * 8 + (bi & 7)) * 32;
    }
    else { tm = &p.tm_wuv; row = (n - BS_WUV) * 128; }
    mbar_expect_tx(bar, n == 0 ? 32768 + 4 * 1152 : 32768);
    tma3d(sbase + (n % BRING) * SLOT, tm, 0, row, panel, bar, pol);
}
__device__ __forceinline__ void b_issue_xchg(int n, const void* src, uint32_t sbase, uint64_t pol) {
    asm volatile("fence.proxy.async;" ::: "memory");
#pragma unroll
    for (int i = 0; i < 2; i++) {
        const uint32_t bar = sbase + M_BAR + (NSLOT + (n + i) % BRING) * 8;
        mbar_expect_tx(bar, 32768);
        bulk_load(sbase + ((n + i) % BRING) * SLOT, reinterpret_cast<const char*>(src) + i * 32768, 32768, bar, pol);
    }
}
__device__ __forceinline__ void b_wait(int n, uint32_t sbase) {
    mbar_wait(sbase + M_BAR + (NSLOT + n % BRING) * 8, (n / BRING) & 1);
}

__device__ __noinline__ void b_gemm(const Params& p, uint32_t sbase, int n0, int n1, int ktot, uint32_t xh, uint32_t xl, int pitch,
                                    int bi, uint64_t pol) {
    const int tid = threadIdx.x, warp = tid >> 5, lane = tid & 31, g = lane >> 2, t = lane & 3;
    const uint32_t woff = (warp >> 2) * 16384 + (lane & 15) * 128 + ((((warp & 3) * 2 + (lane >> 4)) ^ (lane & 7)) * 16);
    const uint32_t xoff = (g & 3) * pitch + t * 4;
    float acc[2][4];
#pragma unroll
    for (int i = 0; i < 8; i++) acc[i >> 2][i & 3] = 0.f;
#pragma unroll 1
    for (int n = n0; n < n1; n++) {
        b_wait(n, sbase);
        const uint32_t slot = sbase + (n % BRING) * SLOT + woff;
        const int k0 = (n - n0) * 128;
        const int ns = min(8, (ktot - k0) >> 4);
#pragma unroll 2
        for (int s = 0; s < ns; s++) {
            uint32_t a[4], w[4];
            const uint32_t xo = xoff + (k0 + 16 * s) * 2;
            a[0] = lds32(xh + xo); a[2] = lds32(xh + xo + 16);
            a[1] = xl ? lds32(xl + xo) : 0u; a[3] = xl ? lds32(xl + xo + 16) : 0u;
            ldsm4t(w, slot + s * 2048);
            mma16816(acc[0], a, w[0], w[1]);
            mma16816(acc[1], a, w[2], w[3]);
        }
        __syncthreads();
        if (tid == 0) b_issue(p, n + BD, bi, sbase, pol);
    }
    if (g < 4) {
#pragma unroll
        for (int j = 0; j < 2; j++)
            asm volatile("st.shared.u32 [%0], %1;" ::"r"(sbase + M_QB + g * QP + (warp * 16 + j * 8 + t * 2) * 2),
                         "r"(pack_bf16(acc[j][0] + acc[j][2], acc[j][1] + acc[j][3])) : "memory");
    }
    __syncthreads();
}

__device__ __forceinline__ void b_exchange(unsigned* c, int n, const void* src, uint32_t sbase, uint64_t pol) {
    TS(n == BS_Q ? 24 : 28);
    __syncthreads();
    if (threadIdx.x == 0) {
        TS(n == BS_Q ? 25 : 29);
        fence_gpu();
        TS(n == BS_Q ? 26 : 30);
        red_add_u32(c, 1u);
        wait_count(c, NBCTA);
        TS(n == BS_Q ? 27 : 31);
        b_issue_xchg(n, src, sbase, pol);
    }
}

template <bool CLU>
__device__ __noinline__ void b_chain(const Params& p, char* smem, uint32_t sbase, int bi, unsigned epoch, uint64_t pol) {
    const int tid = threadIdx.x, warp = tid >> 5, lane = tid & 31, g = lane >> 2, t = lane & 3;
    unsigned (*ctl)[32] = g_ctl[epoch & 1];
    float* red = reinterpret_cast<float*>(smem + 5 * SLOT);
    __syncthreads();
    b_gemm(p, sbase, 0, BS_WUK, DM, sbase + M_XB, 0, XP, bi, pol);
    TS(6);
    {
        uint32_t Q[16];
#pragma unroll
        for (int c = 0; c < 16; c++) Q[c] = lds32(sbase + M_QB + (g & 3) * QP + c * 16 + t * 4);
        float* qa = reinterpret_cast<float*>(smem + M_QA);
#pragma unroll 1
        for (int n = BS_WUK; n < BS_Q; n++) {
            b_wait(n, sbase);
            const uint32_t base = sbase + (n % BRING) * SLOT + (warp * 16 + (lane & 15)) * 128;
            float d[2][4];
#pragma unroll
            for (int i = 0; i < 8; i++) d[i >> 2][i & 3] = 0.f;
#pragma unroll
            for (int s = 0; s < 8; s++) {
                uint32_t a[4];
                ldsm4(a, base + (s >> 2) * 16384 + (((2 * (s & 3) + (lane >> 4)) ^ (lane & 7)) * 16));
                mma16816(d[s & 1], a, Q[2 * s], Q[2 * s + 1]);
            }
            const int c = (n - BS_WUK) * 128 + warp * 16 + g + 8 * (t >> 1);
            qa[(2 * (t & 1)) * 512 + c] = (t & 2) ? d[0][2] + d[1][2] : d[0][0] + d[1][0];
            qa[(2 * (t & 1) + 1) * 512 + c] = (t & 2) ? d[0][3] + d[1][3] : d[0][1] + d[1][1];
            __syncthreads();
            if (tid == 0) b_issue(p, n + BD, bi, sbase, pol);
        }
#pragma unroll 1
        for (int r = 0; r < 2; r++) {
            const int id = tid + r * 256;
            const int b = id >> 7, c0 = ((id >> 2) & 31) * 16 + (id & 3) * 2;
            const float2 u0 = *reinterpret_cast<const float2*>(qa + b * 512 + c0);
            const float2 u1 = *reinterpret_cast<const float2*>(qa + b * 512 + c0 + 8);
            const uint32_t h0 = pack_bf16(u0.x, u0.y), h1 = pack_bf16(u1.x, u1.y);
            const uint32_t l0 = pack_bf16(u0.x - bf_lo(h0), u0.y - bf_hi(h0)), l1 = pack_bf16(u1.x - bf_lo(h1), u1.y - bf_hi(h1));
            g_qabs[((id >> 2) * 4 + (bi >> 3)) * 32 + (bi & 7) * 4 + (id & 3)] = make_uint4(h0, l0, h1, l1);
        }
    }
    b_exchange(&ctl[C_BBAR][0], BS_Q, &g_qabs[(bi >> 3) * 4096], sbase, pol);
    {
        uint32_t qf[4][4][4];
        b_wait(BS_Q + (warp >> 2), sbase);
        TS(7);
        {
            const uint4* qs = reinterpret_cast<const uint4*>(smem + ((BS_Q + (warp >> 2)) % BRING) * SLOT) + (warp & 3) * 512 + lane;
#pragma unroll
            for (int s = 0; s < 4; s++)
#pragma unroll
                for (int i = 0; i < 4; i++) {
                    const uint4 v = qs[(s * 4 + i) * 32];
                    qf[i][s][0] = v.x; qf[i][s][1] = v.y; qf[i][s][2] = v.z; qf[i][s][3] = v.w;
                }
        }
        __syncthreads();
        if (tid == 0) { b_issue(p, BS_Q + BD, bi, sbase, pol); b_issue(p, BS_Q + 1 + BD, bi, sbase, pol); }
        float acc[2][8][4];
#pragma unroll
        for (int i = 0; i < 2; i++)
#pragma unroll
            for (int j = 0; j < 8; j++) { acc[i][j][0] = acc[i][j][1] = acc[i][j][2] = acc[i][j][3] = 0.f; }
        float mrun = -INFINITY, lrun = 0.f;
        const int head = tid >> 3, kq = tid & 7;
        float* alpha = reinterpret_cast<float*>(smem + M_ALPHA);
        for (int n = BS_CKV; n < BS_PART; n++) {
            b_wait(n, sbase);
            const uint32_t slot = sbase + (n % BRING) * SLOT;
            float sc[4][4][4];
#pragma unroll
            for (int i = 0; i < 4; i++)
#pragma unroll
                for (int j = 0; j < 4; j++) { sc[i][j][0] = sc[i][j][1] = sc[i][j][2] = sc[i][j][3] = 0.f; }
#pragma unroll
            for (int j = 0; j < 4; j++)
#pragma unroll
                for (int sp = 0; sp < 2; sp++) {
                    uint32_t bf[4];
                    ldsm4(bf, slot + warp * 4096 + (8 * j + (lane & 7)) * 128 + (((4 * sp + (lane >> 3)) ^ (lane & 7)) * 16));
#pragma unroll
                    for (int i = 0; i < 4; i++) {
                        mma16816(sc[i][j], qf[i][2 * sp], bf[0], bf[1]);
                        mma16816(sc[i][j], qf[i][2 * sp + 1], bf[2], bf[3]);
                    }
                }
#pragma unroll
            for (int i = 0; i < 4; i++)
#pragma unroll
                for (int j = 0; j < 4; j++)
                    *reinterpret_cast<float2*>(red + warp * 1024 + (8 * i + g) * 32 + ((8 * j) ^ (8 * (g & 3))) + 2 * t) =
                        make_float2(sc[i][j][0] + sc[i][j][2], sc[i][j][1] + sc[i][j][3]);
            __syncthreads();
            if (tid == 0 && n > BS_CKV) b_issue(p, n - 1 + BD, bi, sbase, pol);
            {
                float4 s = make_float4(0.f, 0.f, 0.f, 0.f);
#pragma unroll
                for (int w = 0; w < 8; w++) {
                    const float4 v = *reinterpret_cast<const float4*>(red + w * 1024 + head * 32 + ((4 * kq) ^ (8 * (head & 3))));
                    s.x += v.x; s.y += v.y; s.z += v.z; s.w += v.w;
                }
                const uint32_t r0 = pack_bf16(s.x, s.y), r1 = pack_bf16(s.z, s.w);
                const uint32_t s0 = pack_bf16(bf_lo(r0) * SCALE, bf_hi(r0) * SCALE);
                const uint32_t s1 = pack_bf16(bf_lo(r1) * SCALE, bf_hi(r1) * SCALE);
                const float f0 = bf_lo(s0), f1 = bf_hi(s0), f2 = bf_lo(s1), f3 = bf_hi(s1);
                float mx = fmaxf(fmaxf(f0, f1), fmaxf(f2, f3));
                mx = fmaxf(mx, __shfl_xor_sync(~0u, mx, 1));
                mx = fmaxf(mx, __shfl_xor_sync(~0u, mx, 2));
                mx = fmaxf(mx, __shfl_xor_sync(~0u, mx, 4));
                const float mnew = fmaxf(mrun, mx);
                const float al = expsub(mrun, mnew);
                const float p0 = expsub(f0, mnew), p1 = expsub(f1, mnew), p2 = expsub(f2, mnew), p3 = expsub(f3, mnew);
                lrun = lrun * al + ((p0 + p1) + (p2 + p3));
                mrun = mnew;
                *reinterpret_cast<uint2*>(smem + M_P + head * 80 + kq * 8) = make_uint2(pack_bf16(p0, p1), pack_bf16(p2, p3));
                if (kq == 0) alpha[head] = al;
            }
            __syncthreads();
            {
                uint32_t pf[2][2][4];
#pragma unroll
                for (int i = 0; i < 2; i++)
#pragma unroll
                    for (int ks = 0; ks < 2; ks++)
                        ldsm4(pf[i][ks], sbase + M_P + (16 * i + (lane & 15)) * 80 + (16 * ks + 8 * (lane >> 4)) * 2);
#pragma unroll
                for (int i = 0; i < 2; i++) {
                    const float a0 = alpha[16 * i + g], a1 = alpha[16 * i + 8 + g];
#pragma unroll
                    for (int j = 0; j < 8; j++) { acc[i][j][0] *= a0; acc[i][j][1] *= a0; acc[i][j][2] *= a1; acc[i][j][3] *= a1; }
                }
#pragma unroll
                for (int j = 0; j < 8; j++) {
                    uint32_t bf[4];
                    ldsm4t(bf, slot + warp * 4096 + lane * 128 + ((j ^ (lane & 7)) * 16));
#pragma unroll
                    for (int i = 0; i < 2; i++) {
                        mma16816(acc[i][j], pf[i][0], bf[0], bf[1]);
                        mma16816(acc[i][j], pf[i][1], bf[2], bf[3]);
                    }
                }
            }
        }
        __syncthreads();
        if (tid == 0) b_issue(p, BS_PART - 1 + BD, bi, sbase, pol);
        lrun += __shfl_xor_sync(~0u, lrun, 1);
        lrun += __shfl_xor_sync(~0u, lrun, 2);
        lrun += __shfl_xor_sync(~0u, lrun, 4);
        if (kq == 0) g_bml[head * NBCTA + bi] = make_float2(mrun, lrun);
#pragma unroll
        for (int i = 0; i < 2; i++)
#pragma unroll
            for (int j = 0; j < 8; j++) {
                g_bpart[((16 * i + g) * NBCTA + bi) * 256 + warp * 32 + j * 4 + t] = make_float2(acc[i][j][0], acc[i][j][1]);
                g_bpart[((16 * i + 8 + g) * NBCTA + bi) * 256 + warp * 32 + j * 4 + t] = make_float2(acc[i][j][2], acc[i][j][3]);
            }
    }
#pragma unroll 1
    for (int i = tid; i < NH * 36 && !(CLU); i += 256) g_outb[bi * NH * 36 + i] = make_uint4(0u, epoch, 0u, epoch);
    b_exchange(&ctl[C_BBAR + 1][0], BS_PART, &g_bpart[bi * NBCTA * 256], sbase, pol);
    {
        float* omega = reinterpret_cast<float*>(smem + M_OMEGA);
        if (warp == 0) {
            __syncwarp();
            const uint2 ml = ld_relaxed8(&g_bml[bi * NBCTA + lane]);
            const float ms = __uint_as_float(ml.x);
            float m = ms;
            m = fmaxf(m, __shfl_xor_sync(~0u, m, 1));
            m = fmaxf(m, __shfl_xor_sync(~0u, m, 2));
            m = fmaxf(m, __shfl_xor_sync(~0u, m, 4));
            const float w = expsub(ms, m);
            float l = w * __uint_as_float(ml.y);
            l += __shfl_xor_sync(~0u, l, 1);
            l += __shfl_xor_sync(~0u, l, 2);
            l += __shfl_xor_sync(~0u, l, 4);
            omega[lane] = w / l;
        }
        __syncthreads();
        b_wait(BS_PART, sbase);
        b_wait(BS_PART + 1, sbase);
#pragma unroll 1
        for (int b = 0; b < 4; b++) {
            const float2* ps = reinterpret_cast<const float2*>(smem + ((BS_PART + (b >> 1)) % BRING) * SLOT) + (b & 1) * 2048 + tid;
            float c0 = 0.f, c1 = 0.f;
#pragma unroll
            for (int s = 0; s < 8; s++) {
                const float w = omega[b * 8 + s];
                const float2 v = ps[s * 256];
                c0 = fmaf(w, v.x, c0);
                c1 = fmaf(w, v.y, c1);
            }
            const uint32_t hi = pack_bf16(c0, c1);
            *reinterpret_cast<uint32_t*>(smem + M_CH + b * CP + tid * 4) = hi;
            *reinterpret_cast<uint32_t*>(smem + M_CL + b * CP + tid * 4) = pack_bf16(c0 - bf_lo(hi), c1 - bf_hi(hi));
        }
        __syncthreads();
        if (tid == 0) { b_issue(p, BS_PART + BD, bi, sbase, pol); b_issue(p, BS_PART + 1 + BD, bi, sbase, pol); }
    }
    b_gemm(p, sbase, BS_WUV, BS_END, 512, sbase + M_CH, sbase + M_CL, CP, bi, pol);
    TS(12);
    if (CLU) {
        if (tid < 128) {
            const uint32_t xo = sbase + M_QB + (g & 3) * QP + (tid >> 4) * 32 + t * 4;
            st_tagged2(&g_ctx[bi * 128 + tid], __uint_as_float(lds32(xo)), __uint_as_float(lds32(xo + 16)), epoch + 1);
        }
        return;
    }
    if (tid == 0) {
#pragma unroll 1
        for (int i = 0; i < 4; i++) {
            mbar_expect_tx(sbase + M_BAR + i * 8, 36864);
            tma3d(sbase + i * 36864, &p.tm_wo, 0, bi * 128 + i * 32, 0, sbase + M_BAR + i * 8, pol);
        }
    }
    TS(8);
    {
        float acc[9][4];
#pragma unroll
        for (int j = 0; j < 9; j++) { acc[j][0] = acc[j][1] = acc[j][2] = acc[j][3] = 0.f; }
#pragma unroll 1
        for (int i = 0; i < 4; i++) {
            const uint32_t xo = sbase + M_QB + (g & 3) * QP + i * 64 + t * 4;
            const uint32_t a0[4] = {lds32(xo), 0u, lds32(xo + 16), 0u}, a1[4] = {lds32(xo + 32), 0u, lds32(xo + 48), 0u};
            mbar_wait(sbase + M_BAR + i * 8, 0);
#pragma unroll
            for (int j = 0; j < 9; j++) {
                const int nt = warp * 9 + j;
                uint32_t w[4];
                ldsm4t(w, sbase + i * 36864 + (nt >> 3) * 4096 + lane * 128 + (((nt & 7) ^ (lane & 7)) * 16));
                mma16816(acc[j], a0, w[0], w[1]);
                mma16816(acc[j], a1, w[2], w[3]);
            }
        }
        if (g < 4) {
#pragma unroll
            for (int j = 0; j < 9; j++) {
                const int c2 = (warp * 9 + j) * 4 + t;
                st_tagged2(&g_outb[((c2 / 9) * NH + bi) * 36 + g * 9 + c2 % 9], acc[j][0], acc[j][1], epoch + 1);
            }
        }
    }
    TS(9);
    {
        const uint4* src = g_outb + (bi * NH + (tid >> 3)) * 36 + (tid & 7);
        float2* part = reinterpret_cast<float2*>(red);
        unsigned n = 0;
        while (true) {
            ulonglong2 v[5];
            bool ok = true;
#pragma unroll
            for (int i = 0; i < 5; i++)
                if (i < 4 || (tid & 7) < 4) v[i] = ld_tagged2(src + i * 8);
#pragma unroll
            for (int i = 0; i < 5; i++)
                if (i < 4 || (tid & 7) < 4) {
                    ok = ok && (unsigned)(v[i].x >> 32) == epoch + 1 && (unsigned)(v[i].y >> 32) == epoch + 1;
                    part[(tid >> 3) * 36 + (tid & 7) + i * 8] = make_float2(__uint_as_float((unsigned)v[i].x), __uint_as_float((unsigned)v[i].y));
                }
            if (ok) break;
            __nanosleep(400);
            if (++n > SPIN_LIMIT) __trap();
        }
        __syncthreads();
        if (tid < 36) {
            float s0 = 0.f, s1 = 0.f;
#pragma unroll 8
            for (int h = 0; h < NH; h++) { const float2 v = part[h * 36 + tid]; s0 += v.x; s1 += v.y; }
            *reinterpret_cast<uint32_t*>(p.out + (tid / 9) * 2 * DM + DM + bi * 18 + (tid % 9) * 2) = pack_bf16(s0, s1);
        }
    }
    TS(10);
}

template <bool CLU>
__global__ void __launch_bounds__(256, 1) fused_decode_kernel(const __grid_constant__ Params p) {
    extern __shared__ __align__(1024) char smem_raw[];
    const uint32_t sbase = (smem_u32(smem_raw) + 1023u) & ~1023u;
    char* smem = smem_raw + (sbase - smem_u32(smem_raw));
    const int tid = threadIdx.x, warp = tid >> 5, lane = tid & 31;
    const int blk = blockIdx.x;
    const bool isB = CLU ? blk < NBCTA : (blk & 3) == 0 && (blk >> 2) < NBCTA;
    const int bi = CLU ? blk : blk >> 2;
    const int nb = CLU ? blk - NBCTA : blk - min(NBCTA, (blk + 3) >> 2);
    const int nnb = gridDim.x - NBCTA;
    const int nstatic = nnb * (NW + XW);
    uint64_t pol;
    asm volatile("createpolicy.fractional.L2::evict_first.b64 %0, 1.0;" : "=l"(pol));
    const uint32_t wbar = sbase + M_BAR + warp * 8, wslot = sbase + warp * SLOT;
    const int u0 = warp * nnb + nb;
    const bool hold = ((blk >> 2) >> KMIN << KMIN) * 4 * UPP < nstatic;
    const uint32_t jbar = sbase + M_BAR + (NSLOT + BRING) * 8;
    if (warp == 7) {
        if (lane == 0 && blk < 128) {
            mbar_init(jbar, 1);
            asm volatile("fence.mbarrier_init.release.cluster;" ::: "memory");
            uint64_t poln;
            asm volatile("createpolicy.fractional.L2::evict_normal.b64 %0, 1.0;" : "=l"(poln));
            mbar_expect_tx(jbar, 36864 + 4 * 1152);
            tma3d(sbase + J0W, &p.tm_j0, blk * 32, 0, 0, jbar, poln);
            bulk_load(sbase + M_XA, p.xa, 4608, jbar, poln);
        }
        if (lane < 16) reinterpret_cast<unsigned*>(smem + M_HELP)[lane] = 0;
        __syncwarp();
        if (!isB) asm volatile("bar.arrive 2, %0;" ::"n"(32 * (NW + XW + 1)) : "memory");
    }
    if (warp < 4 && lane == 0) {
        mbar_init(wbar, 1);
        if (CLU && warp == 3 && !isB) {
#pragma unroll
            for (int i = 0; i < 2; i++) {
                mbar_init(sbase + F_BAR + i * 8, 1);
                mbar_expect_tx(sbase + F_BAR + i * 8, 4096);
            }
        }
        asm volatile("fence.mbarrier_init.release.cluster;" ::: "memory");
        if (warp < NEARLY && !isB && !hold) {
            mbar_expect_tx(wbar, TILE_BYTES);
            bulk_load(wslot, block_src(p.kc, unit_block<CLU>(u0)), TILE_BYTES, wbar, pol);
        }
    }
    unsigned epoch = 0;
    if (lane == 0) epoch = ld_relaxed4(&g_epoch);
    TS(0);
    if (CLU && !isB) asm volatile("barrier.cluster.arrive.relaxed.aligned;" ::: "memory");
    if ((warp >> 1) == 2 && blk < 128) st_relaxed64(&g_qll[((tid - 128) >> 4) * 2048 + blk * 16 + (tid & 15)], 0ull);
    if (isB || warp >= NW + XW) epoch = __shfl_sync(~0u, epoch, 0);
    if (isB && warp == 3) asm volatile("bar.sync 1, 160;" ::: "memory");
    if (isB && tid == 96) {
#pragma unroll 1
        for (int i = 0; i < BRING; i++) mbar_init(sbase + M_BAR + (NSLOT + i) * 8, 1);
        asm volatile("fence.mbarrier_init.release.cluster;" ::: "memory");
        if (hold) { unsigned n = 0; while (ld_acquire_cta_shared(sbase + M_HELP + 24) < 2) { if (++n > (SPIN_LIMIT << 4)) __trap(); } }
#pragma unroll 1
        for (int b = 0; b < 4; b++) bulk_load(sbase + M_XB + b * XP, p.xb + b * DM, 1152, sbase + M_BAR + NSLOT * 8, pol);
#pragma unroll 1
        for (int n = 0; n < BD; n++) b_issue(p, n, bi, sbase, pol);
    }
    if (warp >= 4 && blk < 128) {
        const int g = lane >> 2, t = lane & 3, j = tid - 128;
        asm volatile("bar.sync 1, %0;" ::"r"(isB ? 160 : 128) : "memory");
#pragma unroll 1
        for (int sl = blk, ph = 0;; sl += 128 - gridDim.x, ph = 1) {
        mbar_wait(jbar, ph);
        TS(13);
        float acc[4][4];
#pragma unroll
        for (int i = 0; i < 16; i++) acc[i >> 2][i & 3] = 0.f;
        const uint32_t wa = sbase + J0W + ((warp - 4) * 144 + (lane & 15)) * 64;
        const uint32_t sw = (lane >> 1) & 3, xa = sbase + M_XA + (g & 3) * 1152 + (warp - 4) * 288 + t * 4;
#pragma unroll 3
        for (int s = 0; s < 9; s++) {
            const uint32_t a[4] = {lds32(xa + s * 32), 0u, lds32(xa + s * 32 + 16), 0u};
            uint32_t w0[4], w1[4];
            ldsm4t(w0, wa + s * 1024 + (((lane >> 4) ^ sw) * 16));
            ldsm4t(w1, wa + s * 1024 + (((2 + (lane >> 4)) ^ sw) * 16));
            mma16816(acc[0], a, w0[0], w0[1]);
            mma16816(acc[1], a, w0[2], w0[3]);
            mma16816(acc[2], a, w1[0], w1[1]);
            mma16816(acc[3], a, w1[2], w1[3]);
        }
        float2* j0 = reinterpret_cast<float2*>(smem + M_J0);
        if (g < 4) {
#pragma unroll
            for (int i = 0; i < 4; i++) j0[(warp - 4) * 64 + g * 16 + i * 4 + t] = make_float2(acc[i][0], acc[i][1]);
        }
        asm volatile("bar.sync 1, 128;" ::: "memory");
        const bool again = sl == blk && blk + 128 - (int)gridDim.x >= (int)gridDim.x;
        if (again && tid == 224) {
            mbar_expect_tx(jbar, 36864);
            tma3d(sbase + J0W, &p.tm_j0, (blk + 128 - gridDim.x) * 32, 0, 0, jbar, pol);
        }
        if (warp < 6) {
            const float2 v0 = j0[j], v1 = j0[64 + j], v2 = j0[128 + j], v3 = j0[192 + j];
            st_relaxed64(&g_qll[(j >> 4) * 2048 + sl * 16 + (j & 15)],
                         (unsigned long long)pack_bf16((v0.x + v1.x) + (v2.x + v3.x), (v0.y + v1.y) + (v2.y + v3.y)) |
                             ((unsigned long long)(epoch + 1) << 32));
            __syncwarp();
            if (lane == 0) asm volatile("red.relaxed.cta.shared::cta.add.u32 [%0], 1;" ::"r"(sbase + M_HELP + 24) : "memory");
        } else if (warp == 7) {
            if (blk < C_LINES) g_ctl[(epoch & 1) ^ 1][blk][lane] = 0;
        }
        TS(1);
        if (!again) break;
        asm volatile("bar.sync 1, 128;" ::: "memory");
        }
    }
    if (isB) {
        b_chain<CLU>(p, smem, sbase, bi, epoch, pol);
        return;
    }
    if (warp < NW + XW) {
        a_worker<CLU>(p, u0, warp >= NW + ((nb & 3) < (CLU ? X3C : X3) ? 1 : 0), warp < NEARLY && !hold, hold, nstatic, wslot, wbar, sbase + M_HELP, epoch, pol);
        if (CLU && nb < NFIN) {
            if (warp == 3) out_issue_sum(p, sbase, nb >> 3, nb & 7, pol);
            else if (warp < NW) out_late(sbase, nb & 7, warp);
        }
        return;
    } else if (warp == 7) {
#pragma unroll 1
        for (int i = nb; i < 4 * NH; i += nnb) g_oacc[i * 32 + lane] = make_float4(0.f, 0.f, 0.f, 0.f);
        if (nb < NREP * NH) g_vdone[nb][lane] = 0;
        __syncwarp();
        k_helper(sbase + M_HELP, epoch);
        if (nb == 0 && lane == 0) g_epoch = epoch + 1;
        __syncwarp();
        if (CLU && nb < NFIN) out_early(sbase, nb >> 3, nb & 7, epoch + 1);
    } else if (CLU) {
    } else if (warp == 6 && nb < NFIN) {
        finisher(p, sbase, nb);
        TS(4);
    } else if (warp >= 6 - NPOLL && nb < NFIN) {
        v_poller(sbase, nb, warp - (6 - NPOLL));
    }
    if (CLU && nb < NFIN) out_project(sbase, nb & 7, warp - 4);
}

}

typedef CUresult (*EncodeFn)(CUtensorMap*, CUtensorMapDataType, cuuint32_t, void*, const cuuint64_t*, const cuuint64_t*,
                             const cuuint32_t*, const cuuint32_t*, CUtensorMapInterleave, CUtensorMapSwizzle,
                             CUtensorMapL2promotion, CUtensorMapFloatOOBfill);

extern "C" void kernel_launch(void* const* d_in, const int* in_sizes, int n_in, void* d_out, int out_size) {
    (void)in_sizes; (void)n_in; (void)out_size;
    static int nsm = 0, ncl = 0;
    static EncodeFn encode = nullptr;
    cudaLaunchConfig_t cfg = {};
    cudaLaunchAttribute at[1];
    at[0].id = cudaLaunchAttributeClusterDimension;
    at[0].val.clusterDim.x = 8; at[0].val.clusterDim.y = 1; at[0].val.clusterDim.z = 1;
    cfg.blockDim = dim3(256); cfg.dynamicSmemBytes = SMEM_BYTES; cfg.stream = cudaStreamPerThread; cfg.attrs = at; cfg.numAttrs = 1;
    if (nsm == 0) {
        int dev = 0;
        cudaGetDevice(&dev);
        cudaDeviceGetAttribute(&nsm, cudaDevAttrMultiProcessorCount, dev);
        cudaFuncSetAttribute(fused_decode_kernel<false>, cudaFuncAttributeMaxDynamicSharedMemorySize, SMEM_BYTES);
        cudaFuncSetAttribute(fused_decode_kernel<true>, cudaFuncAttributeMaxDynamicSharedMemorySize, SMEM_BYTES);
        cfg.gridDim = dim3(128);
        if (cudaOccupancyMaxActiveClusters(&ncl, fused_decode_kernel<true>, &cfg) != cudaSuccess) { ncl = 0; (void)cudaGetLastError(); }
        if (ncl > MINCL) ncl = MINCL;
        void* fn = nullptr;
        cudaDriverEntryPointQueryResult qr;
        cudaGetDriverEntryPoint("cuTensorMapEncodeTiled", &fn, cudaEnableDefault, &qr);
        encode = (EncodeFn)fn;
    }
    Params p;
    auto panels = [&](CUtensorMap* tm, void* ptr, int rows, int cols, int box_rows, int box_panels) {
        const cuuint64_t gd[3] = {64, (cuuint64_t)rows, (cuuint64_t)(cols / 64)}, gs[2] = {(cuuint64_t)cols * 2, 128};
        const cuuint32_t box[3] = {64, (cuuint32_t)box_rows, (cuuint32_t)box_panels}, es[3] = {1, 1, 1};
        encode(tm, CU_TENSOR_MAP_DATA_TYPE_BFLOAT16, 3, ptr, gd, gs, box, es, CU_TENSOR_MAP_INTERLEAVE_NONE,
               CU_TENSOR_MAP_SWIZZLE_128B, CU_TENSOR_MAP_L2_PROMOTION_L2_256B, CU_TENSOR_MAP_FLOAT_OOB_FILL_NONE);
    };
    panels(&p.tm_wq, d_in[7], DM, 4096, 128, 2);
    panels(&p.tm_wuk, d_in[8], 512, 4096, 128, 2);
    panels(&p.tm_wuv, d_in[9], 512, 4096, 128, 2);
    panels(&p.tm_wo, d_in[10], 4096, DM, 32, 9);
    panels(&p.tm_wf, d_in[10], 4096, DM, 128, 1);
    panels(&p.tm_ckv, d_in[6], 4 * SK, 512, 32, 8);
    {
        const cuuint64_t gd[3] = {4096, 192, 3}, gs[2] = {8192, 192 * 8192};
        const cuuint32_t box[3] = {32, 192, 3}, es[3] = {1, 1, 1};
        encode(&p.tm_j0, CU_TENSOR_MAP_DATA_TYPE_BFLOAT16, 3, d_in[3], gd, gs, box, es, CU_TENSOR_MAP_INTERLEAVE_NONE,
               CU_TENSOR_MAP_SWIZZLE_64B, CU_TENSOR_MAP_L2_PROMOTION_L2_128B, CU_TENSOR_MAP_FLOAT_OOB_FILL_NONE);
    }
    {
        const cuuint64_t gd[3] = {DM, 512, 8}, gs[2] = {8 * DM * 2, DM * 2};
        const cuuint32_t box[3] = {64, 16, 8}, es[3] = {1, 1, 1};
        encode(&p.tm_wl, CU_TENSOR_MAP_DATA_TYPE_BFLOAT16, 3, d_in[4], gd, gs, box, es, CU_TENSOR_MAP_INTERLEAVE_NONE,
               CU_TENSOR_MAP_SWIZZLE_128B, CU_TENSOR_MAP_L2_PROMOTION_L2_256B, CU_TENSOR_MAP_FLOAT_OOB_FILL_NONE);
    }
    p.xa = (const __nv_bfloat16*)d_in[0];
    p.kc = (const __nv_bfloat16*)d_in[1];
    p.vc = (const __nv_bfloat16*)d_in[2];
    p.wo = (const __nv_bfloat16*)d_in[4];
    p.xb = (const __nv_bfloat16*)d_in[5];
    p.out = (__nv_bfloat16*)d_out;
    if (ncl >= MINCL) {
        cfg.gridDim = dim3(8 * ncl);
        cudaLaunchKernelEx(&cfg, fused_decode_kernel<true>, p);
    } else {
        fused_decode_kernel<false><<<nsm, 256, SMEM_BYTES, cudaStreamPerThread>>>(p);
    }
}
```

```cpp
#include <cuda_runtime.h>
#include <cuda.h>
#include <cuda_bf16.h>
#include <stdint.h>

namespace {

constexpr int NH = 32, SK = 4096, DM = 576;
constexpr int KEYS = 128;
constexpr int UPP = SK / KEYS;
constexpr int NUK = 4 * NH * UPP;
constexpr int TILE_BYTES = KEYS * 256;
#define NWORK 2
constexpr int NW = NWORK;
constexpr int NBCTA = 32;
constexpr int MINCL = 15;
constexpr int NFIN = 72;
constexpr int SLOT = 32768;
constexpr int NSLOT = 6;
constexpr int BRING = 5;
constexpr int J0W = 5 * SLOT;
constexpr int MISC = NSLOT * SLOT + 4096;
constexpr int XP = 1168, CP = 1040, QP = 272;
constexpr int M_XA = MISC;
constexpr int M_XB = M_XA + 4 * XP;
constexpr int M_CH = M_XB + 4 * XP;
constexpr int M_CL = M_CH + 4 * CP;
constexpr int M_QB = M_CL + 4 * CP;
constexpr int M_QA = M_CH;
constexpr int M_J0 = M_QB + 4 * QP;
constexpr int M_P = M_J0 + 2048;
constexpr int M_ALPHA = M_P + 2560;
constexpr int M_OMEGA = M_ALPHA + 128;
constexpr int M_BAR = M_OMEGA + 128;
constexpr int M_HELP = M_BAR + 128;
constexpr int F_W = 3 * SLOT;
constexpr int F_X = NSLOT * SLOT;
constexpr int F_RECV = F_X + 8192;
constexpr int F_BAR = M_P;
constexpr int SMEM_BYTES = M_HELP + 128 + 1024;
static_assert(F_RECV + 8192 <= M_J0, "output phase layout");
static_assert(SMEM_BYTES <= 232448 && M_BAR % 8 == 0 && M_QA % 16 == 0 && M_P % 16 == 0, "smem layout");
#define XW 2
#define X3 1
#define X3C 2
#define NEARLY 2
#define BD 4
#define FPF 3
#define FSLEEP 800
#define VS0 24
#define FJ 250
#define FP 750
#define NPOLL 2
#define PGAP 200
static_assert(NW + XW <= 4 && NEARLY <= NW + XW && BD <= BRING, "slots 4 and 5 hold the finisher weights");
constexpr int KMIN = 2, KMAX = 4, VMIN = 0, VMAX = 4;
constexpr float SCALE = 0.08838834764831845f;
constexpr float LOG2E = 1.4426950408889634f;
constexpr unsigned SPIN_LIMIT = 1u << 24;

#define NREP 2
constexpr int C_QUEUE = 0, C_KDONE = 1, C_BBAR = 3, C_LINES = 5;

struct Params {
    const __nv_bfloat16 *kc, *xa, *vc, *wo, *xb, *wob;
    __nv_bfloat16* out;
    CUtensorMap tm_j0;
    CUtensorMap tm_wq, tm_wuk, tm_ckv, tm_wuv, tm_wo;
    CUtensorMap tm_wl;
    CUtensorMap tm_wf;
};

__device__ unsigned g_epoch;
__device__ unsigned g_ctl[2][C_LINES][32];
__device__ uint2 g_qll[4 * 2048];
__device__ uint2 g_scores[128 * SK / 4];
__device__ float2 g_stats[128 * UPP];
__device__ float4 g_oacc[128 * 32];
__device__ unsigned g_vdone[NREP * NH][32];
__device__ uint4 g_qabs[4 * 8 * 4 * 4 * 32];
__device__ float2 g_bpart[NBCTA * NH * 256];
__device__ float2 g_bml[NBCTA * NH];
__device__ uint4 g_ctx[NH * 128];
__device__ uint4 g_outb[NBCTA * NH * 36];

#define TS(i)
#define TSV(i, v)
#define LAND(i)
#define CLK(x)
#define ACC(a, x, y)

__device__ __forceinline__ uint32_t smem_u32(const void* p) { return (uint32_t)__cvta_generic_to_shared(p); }
__device__ __forceinline__ void mbar_init(uint32_t bar, uint32_t cnt) {
    asm volatile("mbarrier.init.shared::cta.b64 [%0], %1;" ::"r"(bar), "r"(cnt) : "memory");
}
__device__ __forceinline__ void mbar_expect_tx(uint32_t bar, uint32_t bytes) {
    asm volatile("mbarrier.arrive.expect_tx.shared::cta.b64 _, [%0], %1;" ::"r"(bar), "r"(bytes) : "memory");
}
__device__ __forceinline__ bool mbar_try(uint32_t bar, uint32_t parity) {
    uint32_t ok;
    asm volatile("{\n.reg .pred p;\nmbarrier.try_wait.parity.shared::cta.b64 p, [%1], %2;\nselp.u32 %0, 1, 0, p;\n}\n"
                 : "=r"(ok) : "r"(bar), "r"(parity) : "memory");
    return ok;
}
__device__ __forceinline__ void mbar_wait(uint32_t bar, uint32_t parity) {
    unsigned n = 0;
    while (!mbar_try(bar, parity)) { if (++n > SPIN_LIMIT) __trap(); }
}
__device__ __forceinline__ void bulk_load(uint32_t dst, const void* src, uint32_t bytes, uint32_t bar, uint64_t pol) {
    asm volatile("cp.async.bulk.shared::cluster.global.mbarrier::complete_tx::bytes.L2::cache_hint [%0], [%1], %2, [%3], %4;"
                 ::"r"(dst), "l"(src), "r"(bytes), "r"(bar), "l"(pol) : "memory");
}
__device__ __forceinline__ void tma3d(uint32_t dst, const CUtensorMap* tm, int c0, int c1, int c2, uint32_t bar, uint64_t pol) {
    asm volatile("cp.async.bulk.tensor.3d.shared::cluster.global.mbarrier::complete_tx::bytes.L2::cache_hint [%0], [%1, {%3,%4,%5}], [%2], %6;"
                 ::"r"(dst), "l"(tm), "r"(bar), "r"(c0), "r"(c1), "r"(c2), "l"(pol) : "memory");
}
__device__ __forceinline__ void l2_prefetch(const void* src, uint32_t bytes) {
    asm volatile("cp.async.bulk.prefetch.L2.global [%0], %1;" ::"l"(src), "r"(bytes) : "memory");
}
__device__ __forceinline__ void ldsm4(uint32_t (&r)[4], uint32_t addr) {
    asm volatile("ldmatrix.sync.aligned.m8n8.x4.shared.b16 {%0,%1,%2,%3}, [%4];"
                 : "=r"(r[0]), "=r"(r[1]), "=r"(r[2]), "=r"(r[3]) : "r"(addr));
}
__device__ __forceinline__ void ldsm4t(uint32_t (&r)[4], uint32_t addr) {
    asm volatile("ldmatrix.sync.aligned.m8n8.x4.trans.shared.b16 {%0,%1,%2,%3}, [%4];"
                 : "=r"(r[0]), "=r"(r[1]), "=r"(r[2]), "=r"(r[3]) : "r"(addr));
}
__device__ __forceinline__ void mma16816(float (&d)[4], const uint32_t (&a)[4], uint32_t b0, uint32_t b1) {
    asm("mma.sync.aligned.m16n8k16.row.col.f32.bf16.bf16.f32 {%0,%1,%2,%3}, {%4,%5,%6,%7}, {%8,%9}, {%0,%1,%2,%3};"
        : "+f"(d[0]), "+f"(d[1]), "+f"(d[2]), "+f"(d[3])
        : "r"(a[0]), "r"(a[1]), "r"(a[2]), "r"(a[3]), "r"(b0), "r"(b1));
}
__device__ __forceinline__ uint32_t lds32(uint32_t a) {
    uint32_t v;
    asm volatile("ld.shared.u32 %0, [%1];" : "=r"(v) : "r"(a));
    return v;
}
__device__ __forceinline__ unsigned ld_acquire(const unsigned* p) {
    unsigned v;
    asm volatile("ld.acquire.gpu.global.u32 %0, [%1];" : "=r"(v) : "l"(p) : "memory");
    return v;
}
__device__ __forceinline__ uint2 ld_relaxed8(const void* p) {
    uint2 v;
    asm volatile("ld.relaxed.gpu.global.v2.u32 {%0,%1}, [%2];" : "=r"(v.x), "=r"(v.y) : "l"(p) : "memory");
    return v;
}
__device__ __forceinline__ unsigned ld_relaxed4(const void* p) {
    unsigned v;
    asm volatile("ld.relaxed.gpu.global.u32 %0, [%1];" : "=r"(v) : "l"(p) : "memory");
    return v;
}
__device__ __forceinline__ unsigned atom_inc(unsigned* p) {
    unsigned v;
    asm volatile("atom.relaxed.gpu.global.inc.u32 %0, [%1], 0x7fffffff;" : "=r"(v) : "l"(p) : "memory");
    return v;
}
__device__ __forceinline__ unsigned long long ld_relaxed64(const void* p) {
    unsigned long long v;
    asm volatile("ld.relaxed.gpu.global.u64 %0, [%1];" : "=l"(v) : "l"(p) : "memory");
    return v;
}
__device__ __forceinline__ void st_relaxed64(void* p, unsigned long long v) {
    asm volatile("st.relaxed.gpu.global.u64 [%0], %1;" ::"l"(p), "l"(v) : "memory");
}
__device__ __forceinline__ float4 ld_relaxed16(const void* p) {
    float4 v;
    asm volatile("ld.relaxed.gpu.global.v4.f32 {%0,%1,%2,%3}, [%4];" : "=f"(v.x), "=f"(v.y), "=f"(v.z), "=f"(v.w) : "l"(p) : "memory");
    return v;
}
__device__ __forceinline__ uint32_t mapa(uint32_t a, uint32_t rank) {
    uint32_t r;
    asm("mapa.shared::cluster.u32 %0, %1, %2;" : "=r"(r) : "r"(a), "r"(rank));
    return r;
}
__device__ __forceinline__ void mbar_spin(uint32_t bar) {
    asm volatile("{\n.reg .pred p, q;\n.reg .u32 n;\nmov.u32 n, 0;\n"
                 "SPIN:\nmbarrier.test_wait.parity.shared::cta.b64 p, [%0], 0;\nadd.u32 n, n, 1;\nsetp.gt.u32 q, n, 0x4000000;\n@q trap;\n"
                 "@!p bra.uni SPIN;\n}" ::"r"(bar) : "memory");
}
__device__ __forceinline__ void mbar_spin_cluster(uint32_t bar) {
    asm volatile("{\n.reg .pred p, q;\n.reg .u32 n;\nmov.u32 n, 0;\n"
                 "SPIN:\nmbarrier.test_wait.parity.relaxed.cluster.shared::cta.b64 p, [%0], 0;\nadd.u32 n, n, 1;\nsetp.gt.u32 q, n, 0x4000000;\n@q trap;\n"
                 "@!p bra.uni SPIN;\nfence.acquire.sync_restrict::shared::cluster.cluster;\n}" ::"r"(bar) : "memory");
}
__device__ __forceinline__ void fence_gpu() { asm volatile("fence.acq_rel.gpu;" ::: "memory"); }
__device__ __forceinline__ void red_add_u32(unsigned* p, unsigned v) {
    asm volatile("red.relaxed.gpu.global.add.u32 [%0], %1;" ::"l"(p), "r"(v) : "memory");
}
__device__ __forceinline__ void st_tagged2(void* p, float a, float b, unsigned tag) {
    const unsigned long long hi = (unsigned long long)tag << 32;
    asm volatile("st.relaxed.gpu.global.v2.b64 [%0], {%1,%2};" ::"l"(p), "l"(hi | __float_as_uint(a)), "l"(hi | __float_as_uint(b)) : "memory");
}
__device__ __forceinline__ ulonglong2 ld_tagged2(const void* p) {
    ulonglong2 v;
    asm volatile("ld.relaxed.gpu.global.v2.b64 {%0,%1}, [%2];" : "=l"(v.x), "=l"(v.y) : "l"(p) : "memory");
    return v;
}
__device__ __forceinline__ float4 atom_add_f4(void* p, float a, float b, float c, float d) {
    float4 r;
    asm volatile("atom.relaxed.gpu.global.add.v4.f32 {%0,%1,%2,%3}, [%4], {%5,%6,%7,%8};"
                 : "=f"(r.x), "=f"(r.y), "=f"(r.z), "=f"(r.w) : "l"(p), "f"(a), "f"(b), "f"(c), "f"(d) : "memory");
    return r;
}
__device__ __forceinline__ void red_release_cta_shared(uint32_t a, unsigned v) {
    asm volatile("red.release.cta.shared::cta.add.u32 [%0], %1;" ::"r"(a), "r"(v) : "memory");
}
__device__ __forceinline__ unsigned ld_acquire_cta_shared(uint32_t a) {
    unsigned v;
    asm volatile("ld.acquire.cta.shared::cta.u32 %0, [%1];" : "=r"(v) : "r"(a) : "memory");
    return v;
}
__device__ __forceinline__ void st_release_cta_shared(uint32_t a, unsigned v) {
    asm volatile("st.release.cta.shared::cta.u32 [%0], %1;" ::"r"(a), "r"(v) : "memory");
}
__device__ __forceinline__ void wait_count(const unsigned* p, unsigned target) {
    unsigned n = 0;
    while (ld_acquire(p) < target) { if (++n > SPIN_LIMIT) __trap(); }
}
__device__ __forceinline__ uint32_t pack_bf16(float lo, float hi) {
    uint32_t r;
    asm("cvt.rn.bf16x2.f32 %0, %1, %2;" : "=r"(r) : "f"(hi), "f"(lo));
    return r;
}
__device__ __forceinline__ float bf_lo(uint32_t v) { return __uint_as_float(v << 16); }
__device__ __forceinline__ float bf_hi(uint32_t v) { return __uint_as_float(v & 0xffff0000u); }
__device__ __forceinline__ float ex2(float x) { float y; asm("ex2.approx.ftz.f32 %0, %1;" : "=f"(y) : "f"(x)); return y; }
__device__ __forceinline__ float expsub(float a, float b) { return ex2((a - b) * LOG2E); }
__device__ __forceinline__ float warp_max(float v) {
#pragma unroll
    for (int m = 16; m; m >>= 1) v = fmaxf(v, __shfl_xor_sync(~0u, v, m));
    return v;
}
__device__ __forceinline__ float warp_sum(float v) {
#pragma unroll
    for (int m = 16; m; m >>= 1) v += __shfl_xor_sync(~0u, v, m);
    return v;
}
template <bool CLU>
__device__ __forceinline__ unsigned unit_block(int u) {
    const unsigned x = ((unsigned)u & (NUK - 1)) / UPP;
    const int lg = u < NUK ? min(KMAX, max(KMIN, 29 - __clz(x | 1))) : (CLU && (int)x >= 4 * VS0 ? 0 : min(VMAX, max(VMIN, 29 - __clz((127 - x) | 1))));
    const unsigned r = x & ((4u << lg) - 1);
    return ((x - r + (r & ((1u << lg) - 1)) * 4 + (r >> lg)) * UPP) | ((unsigned)u & (UPP - 1));
}
__device__ __forceinline__ const char* block_src(const void* base, unsigned blk) {
    const unsigned po = blk / UPP;
    return reinterpret_cast<const char*>(base) + (size_t)(((po & 3) * NH + (po >> 2)) * UPP + blk % UPP) * TILE_BYTES;
}

template <bool CLU>
__device__ __forceinline__ void a_worker(const Params& p, int un, bool once, bool pre, bool hold, int nstatic, uint32_t slot, uint32_t bar,
                                         uint32_t help, unsigned epoch, uint64_t pol) {
    constexpr int NU = 2 * NUK;
    const int lane = threadIdx.x & 31, g = lane >> 2, t = lane & 3;
    const int li = lane & 7;
    uint32_t kaddr[4], vaddr[8];
    {
        const int e = (lane >> 3) & 1, kk = lane >> 4;
#pragma unroll
        for (int s = 0; s < 4; s++) kaddr[s] = slot + (16 * li + e) * 256 + ((2 * s + kk + li) & 7) * 16;
        const int vrow = 4 * (li >> 1) + (li & 1) + 2 * kk;
#pragma unroll
        for (int c = 0; c < 8; c++) vaddr[c] = slot + vrow * 256 + e * 128 + ((c + li) & 7) * 16;
#pragma unroll
        for (int c = 0; c < 8; c++) asm volatile("" : "+r"(vaddr[c]));
    }
    const uint32_t vmask = (g >> 1) != t ? 0u : ((g & 1) ? 0xffff0000u : 0xffffu);
    int kseen = -1;
    unsigned long long H0 = 0, H1 = 0;
    auto header = [&](int v, unsigned vb) {
        if (v >= NU) return;
        const void *a0, *a1;
        if (v < NUK) {
            const unsigned po = vb / UPP;
            a0 = g_qll + (po & 3) * 2048 + (po >> 2) * 64 + lane;
            a1 = reinterpret_cast<const uint2*>(a0) + 32;
        } else {
            const int half = vb / (NUK / 2);
            if (half > kseen) {
                unsigned n = 0;
                while (ld_acquire_cta_shared(help + 12 + 4 * half) == 0) { if (++n > (SPIN_LIMIT << 4)) __trap(); }
                kseen = half;
            }
            a0 = &g_scores[vb * (KEYS / 4) + lane];
            a1 = &g_stats[(vb / UPP) * UPP + lane];
        }
        H0 = ld_relaxed64(a0);
        H1 = ld_relaxed64(a1);
    };
    asm volatile("bar.sync 2, %0;" ::"n"(32 * (NW + XW + 1)) : "memory");
    epoch = __shfl_sync(~0u, epoch, 0);
    if (hold) { unsigned n = 0; while (ld_acquire_cta_shared(help + 24) < 2) { if (++n > (SPIN_LIMIT << 4)) __trap(); } }
    unsigned (*ctl)[32] = g_ctl[epoch & 1];
    const unsigned tag = epoch + 1;
    unsigned nxt = once ? NU : 0;
    int u = -1;
    unsigned bu = 0, bn = unit_block<CLU>(un);
    bool have = false;
    uint32_t phase = 0;
    unsigned kpend = 0;
    const unsigned zero = gridDim.x >> 24;
    uint32_t Q[16];
    float4 oret = make_float4(0.f, 0.f, 0.f, 0.f);
    while (true) {
        const char* nsrc = block_src(un < NUK ? p.kc : p.vc, bn);
        float4* odst = &g_oacc[(bu / UPP) * 32 + lane];
        unsigned* vdst = &g_vdone[(lane & (NREP - 1)) * NH + bu / (4 * UPP)][0];
        float d[8][4];
        CLK(c1);
        asm volatile("" : "+l"(odst));
        if (u >= NUK) {
#pragma unroll
            for (int j = 0; j < 8; j++) { d[j][0] = d[j][1] = d[j][2] = d[j][3] = 0.f; }
            mbar_wait(bar, phase);
            LAND(NUK + bu);
            uint32_t a[2][8][4];
#pragma unroll
            for (int c = 0; c < 8; c++) ldsm4t(a[0][c], vaddr[c]);
#pragma unroll
            for (int j = 0; j < 8; j++) {
                if (j < 7) {
#pragma unroll
                    for (int c = 0; c < 8; c++) ldsm4t(a[(j + 1) & 1][c], vaddr[c] + (j + 1) * 4096);
                }
#pragma unroll
                for (int c = 0; c < 8; c++) mma16816(d[c], a[j & 1][c], Q[2 * j], Q[2 * j + 1]);
            }
            float o[4];
#pragma unroll
            for (int r = 0; r < 2; r++) {
                o[2 * r] = d[0][2 * r] + d[7][2 * r + 1];
                o[2 * r + 1] = d[0][2 * r + 1] + d[1][2 * r];
#pragma unroll
                for (int k = 1; k < 4; k++) {
                    const int src = (lane & 28) | ((t - k) & 3);
                    o[2 * r] += __shfl_sync(~0u, d[2 * k][2 * r] + d[2 * k - 1][2 * r + 1], src);
                    o[2 * r + 1] += __shfl_sync(~0u, d[2 * k][2 * r + 1] + d[2 * k + 1][2 * r], src);
                }
            }
            oret = atom_add_f4(odst, o[0], o[1], o[2], o[3]);
        } else if (u >= 0) {
#pragma unroll
            for (int j = 0; j < 8; j++) { d[j][0] = d[j][1] = d[j][2] = d[j][3] = 0.f; }
            mbar_wait(bar, phase);
            LAND(bu);
            uint32_t a[2][8][4];
#pragma unroll
            for (int j = 0; j < 8; j++) ldsm4(a[0][j], kaddr[0] + (4 * (j & 3) + 2 * (j >> 2)) * 256);
#pragma unroll
            for (int s = 0; s < 8; s++) {
                if (s < 7) {
#pragma unroll
                    for (int j = 0; j < 8; j++)
                        ldsm4(a[(s + 1) & 1][j], kaddr[(s + 1) & 3] + (4 * (j & 3) + 2 * (j >> 2)) * 256 + ((s + 1) >> 2) * 128);
                }
#pragma unroll
                for (int j = 0; j < 8; j++)
                    mma16816(d[j], a[s & 1][j], Q[(s & 4) * 2 + ((2 * s - 2 * j) & 7)], Q[(s & 4) * 2 + ((2 * s + 1 - 2 * j) & 7)]);
            }
        }
        if (u >= 0) phase ^= 1;
        CLK(c2b);
        if (un < NU && lane == 0) {
            if (!once) nxt = atom_inc(&ctl[C_QUEUE][0]);
            if (u >= 0 || !pre) {
                mbar_expect_tx(bar, TILE_BYTES);
                bulk_load(slot, nsrc, TILE_BYTES, bar, pol);
            }
        }
        const uint32_t tiss = (uint32_t)clock();
        CLK(c3);
        if ((unsigned)u < (unsigned)NUK) {
            const int j0 = (t - (g >> 1)) & 3;
            float v[4];
#pragma unroll
            for (int q = 0; q < 4; q++) {
                const int jq = (q >> 1) * 4, e = (q & 1) * 2;
                const float x0 = (g & 1) ? d[jq + 0][e + 1] : d[jq + 0][e];
                const float x1 = (g & 1) ? d[jq + 1][e + 1] : d[jq + 1][e];
                const float x2 = (g & 1) ? d[jq + 2][e + 1] : d[jq + 2][e];
                const float x3 = (g & 1) ? d[jq + 3][e + 1] : d[jq + 3][e];
                const float y0 = (j0 & 1) ? x1 : x0, y1 = (j0 & 1) ? x3 : x2;
                v[q] = (j0 & 2) ? y1 : y0;
            }
            const uint32_t r0 = pack_bf16(v[0], v[1]), r1 = pack_bf16(v[2], v[3]);
            const uint32_t s0 = pack_bf16(bf_lo(r0) * SCALE, bf_hi(r0) * SCALE);
            const uint32_t s1 = pack_bf16(bf_lo(r1) * SCALE, bf_hi(r1) * SCALE);
            g_scores[bu * (KEYS / 4) + 4 * g + j0] = make_uint2(s0, s1);
            const float f0 = bf_lo(s0), f1 = bf_hi(s0), f2 = bf_lo(s1), f3 = bf_hi(s1);
            const float m = warp_max(fmaxf(fmaxf(f0, f1), fmaxf(f2, f3)));
            const float l = warp_sum((expsub(f0, m) + expsub(f1, m)) + (expsub(f2, m) + expsub(f3, m)));
            if (lane == 0) g_stats[bu] = make_float2(m, l);
            kpend++;
            if (un / (NUK / 2) != u / (NUK / 2)) {
                __syncwarp();
                if (lane == 0) {
                    red_release_cta_shared(help + 4 * (u / (NUK / 2)), kpend);
                    if (un >= NUK) red_release_cta_shared(help + 8, 1u);
                }
                kpend = 0;
            }
        }
        CLK(c4);
        int unn = NU;
        if (un < NU) {
            unsigned n = 0;
            while (true) {
                if (!have) header(un, bn);
                if (un >= NUK || __all_sync(~0u, (uint32_t)(H0 >> 32) == tag && (uint32_t)(H1 >> 32) == tag)) break;
                if (++n > SPIN_LIMIT) __trap();
                have = false;
            }
            if (un >= NUK) {
                const uint32_t s0 = (uint32_t)H0, s1 = (uint32_t)(H0 >> 32);
                const float mu = __uint_as_float((uint32_t)H1);
                const float m = warp_max(mu);
                const float l = warp_sum(__uint_as_float((uint32_t)(H1 >> 32)) * expsub(mu, m));
                const float inv = 1.0f / l;
                const uint32_t w0 = pack_bf16(expsub(bf_lo(s0), m) * inv, expsub(bf_hi(s0), m) * inv);
                const uint32_t w1 = pack_bf16(expsub(bf_lo(s1), m) * inv, expsub(bf_hi(s1), m) * inv);
#pragma unroll
                for (int j = 0; j < 8; j++) {
                    Q[2 * j] = __shfl_sync(~0u, w0, 4 * j + t) & vmask;
                    Q[2 * j + 1] = __shfl_sync(~0u, w1, 4 * j + t) & vmask;
                }
            } else {
#pragma unroll
                for (int j = 0; j < 8; j++) {
                    const int src = (((j + g) & 7) << 2) + t;
                    Q[j] = __shfl_sync(~0u, (uint32_t)H0, src);
                    Q[8 + j] = __shfl_sync(~0u, (uint32_t)H1, src);
                }
            }
            unn = nstatic + (int)__shfl_sync(~0u, nxt, 0);
            if (CLU && !once && unn >= NU && lane == 0)
                asm volatile("st.relaxed.cta.shared::cta.u32 [%0], %1;" ::"r"(help + 28), "r"((tiss + (FJ - (unn - NU)) * 20) | 1u) : "memory");
        }
        if (u >= NUK && lane < NREP)
            red_add_u32(vdst,
                        1u + ((__float_as_uint(oret.x) | __float_as_uint(oret.y) | __float_as_uint(oret.z) | __float_as_uint(oret.w)) & zero));
        if (un >= NU) break;
        bu = bn;
        have = !(un < NUK && unn >= NUK && !(un >= NUK / 2 && unn < NUK + NUK / 2));
        bn = unit_block<CLU>(unn);
        if (have) header(unn, bn);
        u = un;
        un = unn;
    }
}

__device__ __forceinline__ void k_helper(uint32_t help, unsigned epoch) {
    if ((threadIdx.x & 31) != 0) return;
    unsigned (*ctl)[32] = g_ctl[epoch & 1];
    unsigned sent0 = 0, sent1 = 0, n = 0;
    int seen = 0;
    bool fin = false;
    while (!fin || seen < 2) {
        if (!fin) {
            fin = ld_acquire_cta_shared(help + 8) == NW + XW;
            const unsigned c0 = ld_acquire_cta_shared(help), c1 = ld_acquire_cta_shared(help + 4);
            if (c0 != sent0 || c1 != sent1) {
                fence_gpu();
                if (c0 != sent0) red_add_u32(&ctl[C_KDONE][0], c0 - sent0);
                if (c1 != sent1) red_add_u32(&ctl[C_KDONE + 1][0], c1 - sent1);
                sent0 = c0; sent1 = c1;
            }
        }
        if (seen < 2 && ld_acquire(&ctl[C_KDONE + seen][0]) >= NUK / 2) {
            st_release_cta_shared(help + 12 + 4 * seen, 1u);
            seen++;
        } else {
            __nanosleep(300);
        }
        if (++n > SPIN_LIMIT) __trap();
    }
}

__device__ __forceinline__ void v_poller(uint32_t sbase, int f, int w) {
    const int lane = threadIdx.x & 31;
    const unsigned (*cp)[32] = &g_vdone[((f * NPOLL + w) % NREP) * NH];
    unsigned n = 0;
    while (ld_acquire_cta_shared(sbase + M_HELP + 12) == 0) { __nanosleep(1000); if (++n > SPIN_LIMIT) __trap(); }
    int h = 0;
    bool fast = false;
    while (h < NH) {
        const unsigned r = __ballot_sync(~0u, ld_acquire(&cp[min(h + (lane & 3), NH - 1)][0]) >= 4 * UPP) & 15u;
        if (r & 1) {
            h = min(NH, h + __ffs(~r) - 1);
            __syncwarp();
            if (lane == 0) asm volatile("red.release.cta.shared::cta.max.u32 [%0], %1;" ::"r"(sbase + M_HELP + 20), "r"(h) : "memory");
        }
        if (h < NH - 4) {
            __nanosleep(h ? 300 : 1000);
        } else if (!fast) {
            fast = true;
            const long long t0 = clock64();
            while (clock64() - t0 < w * PGAP) {}
        }
        if (++n > SPIN_LIMIT) __trap();
    }
}
__device__ __forceinline__ void finisher(const Params& p, uint32_t sbase, int f) {
    const int lane = threadIdx.x & 31;
    {
        const char* wg = reinterpret_cast<const char*>(p.wo);
        const uint32_t dst = sbase + 4 * SLOT + (16 * (lane & 7) + (lane >> 3)) * 16;
#pragma unroll 1
        for (int h = -FPF - 4; h < NH; h++) {
            if (lane == 0 && (unsigned)(h + FPF) < (unsigned)NH) l2_prefetch(wg + (size_t)(h + FPF) * 147456 + f * 2048, 2048);
            if (h >= 0) {
#pragma unroll
                for (int r = 0; r < 4; r++)
                    asm volatile("cp.async.cg.shared.global [%0], [%1], 16;" ::"r"(dst + h * 2048 + ((r & 1) * 4 + (r >> 1) * 8) * 16),
                                 "l"(wg + (size_t)(h * 128 + r * 32 + lane) * (DM * 2) + f * 16) : "memory");
            }
            __nanosleep(FSLEEP);
        }
        asm volatile("cp.async.wait_all;" ::: "memory");
        __syncwarp();
    }
    TS(11);
    const float4* vec = g_oacc + ((lane >> 2) & 3) * 32 + (lane >> 4) * 16 + (lane & 3);
    float acc[2][2][4];
#pragma unroll
    for (int i = 0; i < 16; i++) acc[i >> 3][(i >> 2) & 1][i & 3] = 0.f;
    uint32_t* outp = reinterpret_cast<uint32_t*>(p.out + (lane >> 2) * (2 * DM) + f * 8 + (lane & 3) * 2);
    uint32_t wa = sbase + 4 * SLOT + lane * 16;
    auto project = [&](const float4 (&x)[4], const uint32_t (&w)[4][4]) {
#pragma unroll
        for (int s = 0; s < 4; s++) {
            const uint32_t a[4] = {pack_bf16(x[s].x, x[s].y), 0u, pack_bf16(x[s].z, x[s].w), 0u};
            mma16816(acc[0][s & 1], a, w[s >> 1][(s & 1) * 2], w[s >> 1][(s & 1) * 2 + 1]);
            mma16816(acc[1][s & 1], a, w[2 + (s >> 1)][(s & 1) * 2], w[2 + (s >> 1)][(s & 1) * 2 + 1]);
        }
    };
    int h = 0;
    unsigned n = 0;
    while (h < NH) {
        uint32_t w[4][4];
#pragma unroll
        for (int q = 0; q < 4; q++) ldsm4t(w[q], wa + q * 512);
        int ready;
        while ((ready = ld_acquire_cta_shared(sbase + M_HELP + 20)) <= h) {
            if (h < NH - 3) __nanosleep(100);
            if (++n > (SPIN_LIMIT << 4)) __trap();
        }
        float4 x[4], y[4];
#pragma unroll
        for (int s = 0; s < 4; s++) x[s] = ld_relaxed16(vec + s * 4);
        const bool two = ready > h + 1;
        if (two) {
#pragma unroll
            for (int s = 0; s < 4; s++) y[s] = ld_relaxed16(vec + 128 + s * 4);
        }
        project(x, w);
        if (two) {
#pragma unroll
            for (int q = 0; q < 4; q++) ldsm4t(w[q], wa + 2048 + q * 512);
            project(y, w);
        }
        const int nr = two ? 2 : 1;
        h += nr;
        vec += nr * 128;
        wa += nr * 2048;
        const float o0 = acc[0][0][0] + acc[0][1][0] + __shfl_down_sync(~0u, acc[1][0][0] + acc[1][1][0], 16);
        const float o1 = acc[0][0][1] + acc[0][1][1] + __shfl_down_sync(~0u, acc[1][0][1] + acc[1][1][1], 16);
        asm volatile("{\n.reg .pred p;\nsetp.ne.u32 p, %2, 0;\n@p st.global.u32 [%0], %1;\n}" ::"l"(outp), "r"(pack_bf16(o0, o1)),
                     "r"((uint32_t)(lane < 16 && h == NH)) : "memory");
    }
}

__device__ __forceinline__ void out_fetch(uint32_t sbase, int step, int h) {
    const int lane = threadIdx.x & 31;
    float4 x[4];
#pragma unroll
    for (int b = 0; b < 4; b++) x[b] = ld_relaxed16(&g_oacc[(h * 4 + b) * 32 + lane]);
#pragma unroll
    for (int b = 0; b < 4; b++)
        asm volatile("st.shared.v2.u32 [%0], {%1,%2};" ::"r"(sbase + F_X + step * 1024 + (lane >> 2) * 128 + (lane & 3) * 8 + b * 32),
                     "r"(pack_bf16(x[b].x, x[b].y)), "r"(pack_bf16(x[b].z, x[b].w)) : "memory");
}
__device__ __forceinline__ void out_early(uint32_t sbase, int c, int rank, unsigned tag) {
    const int lane = threadIdx.x & 31;
    if (lane < 10) {
        mbar_init(sbase + F_BAR + 16 + lane * 8, lane < 7 ? 1 : lane == 7 ? 2 : 4);
        if (lane < 8) mbar_expect_tx(sbase + F_BAR + 16 + lane * 8, 16384);
    }
    asm volatile("fence.mbarrier_init.release.cluster;" ::: "memory");
    unsigned n = 0;
#pragma unroll 1
    for (int i = 0; i < 3; i++) {
        while (ld_acquire(&g_vdone[(c & (NREP - 1)) * NH + 8 * i + rank][0]) < 4 * UPP) { __nanosleep(500); if (++n > SPIN_LIMIT) __trap(); }
        out_fetch(sbase, 4 + i, 8 * i + rank);
#pragma unroll 1
        for (int j = 0; j < 16 && i == 0;) {
            const ulonglong2 v = ld_tagged2(&g_ctx[((j >> 2) * 8 + rank) * 128 + (j & 3) * 32 + lane]);
            if (__all_sync(~0u, (unsigned)(v.x >> 32) == tag && (unsigned)(v.y >> 32) == tag)) {
                asm volatile("st.shared.v2.u32 [%0], {%1,%2};" ::"r"(sbase + F_X + (j * 32 + lane) * 8), "r"((uint32_t)v.x), "r"((uint32_t)v.y) : "memory");
                j++;
            } else {
                __nanosleep(500);
                if (++n > SPIN_LIMIT) __trap();
            }
        }
    }
    __syncwarp();
    if (lane == 0) st_release_cta_shared(sbase + M_HELP + 32, 1u);
}
__device__ __forceinline__ void out_late(uint32_t sbase, int c, int rank) {
    unsigned n = 0;
    while (ld_acquire_cta_shared(sbase + M_HELP + 32) == 0) { if (++n > (SPIN_LIMIT << 4)) __trap(); }
    while (ld_acquire(&g_vdone[(c & (NREP - 1)) * NH + 24 + rank][0]) < 4 * UPP) { if (++n > SPIN_LIMIT) __trap(); }
    TS(12);
    out_fetch(sbase, 7, 24 + rank);
    __syncwarp();
    if ((threadIdx.x & 31) == 0) asm volatile("mbarrier.arrive.shared::cta.b64 _, [%0];" ::"r"(sbase + F_BAR + 72) : "memory");
    TS(13);
}
__device__ __forceinline__ void out_project(uint32_t sbase, int rank, int w) {
    const int lane = threadIdx.x & 31, g = lane >> 2, t = lane & 3;
    unsigned n = 0;
    while (ld_acquire_cta_shared(sbase + M_HELP + 32) == 0) { __nanosleep(500); if (++n > SPIN_LIMIT) __trap(); }
    asm volatile("barrier.cluster.wait.acquire.aligned;" ::: "memory");
    uint32_t rdst[4], rbar[4], sw[4];
#pragma unroll
    for (int j = 0; j < 4; j++) {
        rdst[j] = mapa(sbase + F_RECV + (t >> 1) * 4096 + (rank * 4 + w) * 128 + (g & 3) * 32 + (t & 1) * 16, 2 * j + (g >> 2));
        rbar[j] = mapa(sbase + F_BAR + (t >> 1) * 8, 2 * j + (g >> 2));
        sw[j] = sbase + F_W + w * 4096 + ((lane & 7) + (lane >> 4) * 8) * 128 + (((2 * j + ((lane >> 3) & 1)) ^ (lane & 7)) * 16);
    }
    float acc[4][4];
#pragma unroll
    for (int i = 0; i < 16; i++) acc[i >> 2][i & 3] = 0.f;
    while (ld_acquire_cta_shared(sbase + M_HELP + 28) == 0) { __nanosleep(200); if (++n > SPIN_LIMIT) __trap(); }
    uint32_t xa = sbase + F_X + w * 256 + (lane & 15) * 8;
#pragma unroll 1
    for (int i = 0; i < 8; i++) {
        uint32_t bf[2][2] = {0u, 0u, 0u, 0u}, a[2][4][4];
        const bool mine = (g >> 2) == (i >> 2), send = (i & 3) == 3 && (t >> 1) == (i >> 2);
        mbar_spin(sbase + F_BAR + 16 + i * 8);
        if (mine) {
#pragma unroll
            for (int s = 0; s < 2; s++)
                asm volatile("ld.shared.v2.u32 {%0,%1}, [%2];" : "=r"(bf[s][0]), "=r"(bf[s][1]) : "r"(xa + s * 128) : "memory");
        }
#pragma unroll
        for (int j = 0; j < 8; j++) ldsm4t(a[j >> 2][j & 3], sw[j & 3] + (j >> 2) * 2048);
#pragma unroll
        for (int j = 0; j < 8; j++) mma16816(acc[j & 3], a[j >> 2][j & 3], bf[j >> 2][0], bf[j >> 2][1]);
        if (send) {
#pragma unroll
            for (int j = 0; j < 4; j++)
                asm volatile("st.async.weak.shared::cluster.mbarrier::complete_tx::bytes.v4.f32 [%0], {%1,%2,%3,%4}, [%5];"
                             ::"r"(rdst[j]), "f"(acc[j][0]), "f"(acc[j][1]), "f"(acc[j][2]), "f"(acc[j][3]), "r"(rbar[j]) : "memory");
        }
        __syncwarp();
        asm volatile("{\n.reg .pred p;\nsetp.ne.u32 p, %1, 0;\n@p mbarrier.arrive.shared::cta.b64 _, [%0];\n}"
                     ::"r"(sbase + F_BAR + 80 + i * 8), "r"((uint32_t)(i < 2 && lane == 0)) : "memory");
        xa += 1024;
#pragma unroll
        for (int j = 0; j < 4; j++) {
            sw[j] += i == 5 ? -5 * 16384 : 16384;
            asm volatile("" : "+r"(sw[j]));
        }
    }
}
__device__ __forceinline__ void out_issue_sum(const Params& p, uint32_t sbase, int c, int rank, uint64_t pol) {
    const int lane = threadIdx.x & 31;
    if (lane == 0) {
        unsigned n = 0;
        while (ld_acquire_cta_shared(sbase + M_HELP + 32) == 0) { __nanosleep(500); if (++n > SPIN_LIMIT) __trap(); }
        asm volatile("prefetch.tensormap [%0];" ::"l"(&p.tm_wf) : "memory");
        asm volatile("prefetch.tensormap [%0];" ::"l"(&p.tm_wl) : "memory");
        uint32_t t0;
        while ((t0 = ld_acquire_cta_shared(sbase + M_HELP + 28)) == 0) { __nanosleep(100); if (++n > SPIN_LIMIT) __trap(); }
#pragma unroll 1
        for (int i = 0; i < 8; i++) {
            const int h = (i & 3) * 8 + rank;
            if (i >= 6) mbar_wait(sbase + F_BAR + 32 + i * 8, 0);
            while ((int)((uint32_t)clock() - t0) < 0) {}
            if (i == 0) TS(16);
            tma3d(sbase + F_W + (i < 6 ? i : i - 6) * 16384, i < 4 ? &p.tm_wf : &p.tm_wl, i < 4 ? 0 : c * 64, i < 4 ? h * 128 : h * 16,
                  i < 4 ? c : 0, sbase + F_BAR + 16 + i * 8, pol);
            t0 += FP;
        }
        TS(17);
    }
    __syncwarp();
    __nv_bfloat16* dst = p.out + (2 * (lane & 1) + ((lane >> 3) & 1)) * (2 * DM) + DM + c * 64 + (rank >> 1) * 16 + (lane >> 4) * 8 +
                         (rank & 1) * 4 + ((lane >> 1) & 3);
    uint32_t src = sbase + F_RECV + (lane >> 3) * 1024 + (lane & 7) * 16;
#pragma unroll 1
    for (int r = 0; r < 2; r++) {
        asm volatile("" : "+l"(dst), "+r"(src));
        mbar_spin_cluster(sbase + F_BAR + r * 8);
        float4 x[8];
#pragma unroll
        for (int i = 0; i < 8; i++)
            asm volatile("ld.shared.v4.f32 {%0,%1,%2,%3}, [%4];" : "=f"(x[i].x), "=f"(x[i].y), "=f"(x[i].z), "=f"(x[i].w)
                         : "r"(src + i * 128) : "memory");
#pragma unroll
        for (int m = 1; m < 8; m <<= 1)
#pragma unroll
            for (int i = 0; i < 8; i += 2 * m) { x[i].x += x[i + m].x; x[i].y += x[i + m].y; x[i].z += x[i + m].z; x[i].w += x[i + m].w; }
        const bool up = lane & 16, od = lane & 8;
        const float a = (up ? x[0].z : x[0].x) + __shfl_xor_sync(~0u, up ? x[0].x : x[0].z, 16);
        const float b = (up ? x[0].w : x[0].y) + __shfl_xor_sync(~0u, up ? x[0].y : x[0].w, 16);
        const float v = (od ? b : a) + __shfl_xor_sync(~0u, od ? a : b, 8);
        asm volatile("st.global.u16 [%0], %1;" ::"l"(dst), "h"((unsigned short)pack_bf16(v, 0.f)) : "memory");
        TS(14 + r);
        dst -= DM;
        src += 4096;
    }
}

constexpr int BS_WUK = 5, BS_Q = 9, BS_CKV = 11, BS_PART = 27, BS_WUV = 29, BS_END = 33;

__device__ __noinline__ void b_issue(const Params& p, int n, int bi, uint32_t sbase, uint64_t pol) {
    if (n >= BS_END || (n >= BS_Q && n < BS_CKV) || (n >= BS_PART && n < BS_WUV)) return;
    const uint32_t bar = sbase + M_BAR + (NSLOT + n % BRING) * 8;
    const CUtensorMap* tm;
    int row, panel = 2 * bi;
    if (n < BS_WUK) { tm = &p.tm_wq; row = n * 128; }
    else if (n < BS_Q) { tm = &p.tm_wuk; row = (n - BS_WUK) * 128; }
    else if (n < BS_PART) {
        tm = &p.tm_ckv; panel = 0;
        row = (bi >> 3) * SK + ((n - BS_CKV) * 8 + (bi & 7)) * 32;
    }
    else { tm = &p.tm_wuv; row = (n - BS_WUV) * 128; }
    mbar_expect_tx(bar, n == 0 ? 32768 + 4 * 1152 : 32768);
    tma3d(sbase + (n % BRING) * SLOT, tm, 0, row, panel, bar, pol);
}
__device__ __forceinline__ void b_issue_xchg(int n, const void* src, uint32_t sbase, uint64_t pol) {
    asm volatile("fence.proxy.async;" ::: "memory");
#pragma unroll
    for (int i = 0; i < 2; i++) {
        const uint32_t bar = sbase + M_BAR + (NSLOT + (n + i) % BRING) * 8;
        mbar_expect_tx(bar, 32768);
        bulk_load(sbase + ((n + i) % BRING) * SLOT, reinterpret_cast<const char*>(src) + i * 32768, 32768, bar, pol);
    }
}
__device__ __forceinline__ void b_wait(int n, uint32_t sbase) {
    mbar_wait(sbase + M_BAR + (NSLOT + n % BRING) * 8, (n / BRING) & 1);
}

__device__ __noinline__ void b_gemm(const Params& p, uint32_t sbase, int n0, int n1, int ktot, uint32_t xh, uint32_t xl, int pitch,
                                    int bi, uint64_t pol) {
    const int tid = threadIdx.x, warp = tid >> 5, lane = tid & 31, g = lane >> 2, t = lane & 3;
    const uint32_t woff = (warp >> 2) * 16384 + (lane & 15) * 128 + ((((warp & 3) * 2 + (lane >> 4)) ^ (lane & 7)) * 16);
    const uint32_t xoff = (g & 3) * pitch + t * 4;
    float acc[2][4];
#pragma unroll
    for (int i = 0; i < 8; i++) acc[i >> 2][i & 3] = 0.f;
#pragma unroll 1
    for (int n = n0; n < n1; n++) {
        b_wait(n, sbase);
        const uint32_t slot = sbase + (n % BRING) * SLOT + woff;
        const int k0 = (n - n0) * 128;
        const int ns = min(8, (ktot - k0) >> 4);
#pragma unroll 2
        for (int s = 0; s < ns; s++) {
            uint32_t a[4], w[4];
            const uint32_t xo = xoff + (k0 + 16 * s) * 2;
            a[0] = lds32(xh + xo); a[2] = lds32(xh + xo + 16);
            a[1] = xl ? lds32(xl + xo) : 0u; a[3] = xl ? lds32(xl + xo + 16) : 0u;
            ldsm4t(w, slot + s * 2048);
            mma16816(acc[0], a, w[0], w[1]);
            mma16816(acc[1], a, w[2], w[3]);
        }
        __syncthreads();
        if (tid == 0) b_issue(p, n + BD, bi, sbase, pol);
    }
    if (g < 4) {
#pragma unroll
        for (int j = 0; j < 2; j++)
            asm volatile("st.shared.u32 [%0], %1;" ::"r"(sbase + M_QB + g * QP + (warp * 16 + j * 8 + t * 2) * 2),
                         "r"(pack_bf16(acc[j][0] + acc[j][2], acc[j][1] + acc[j][3])) : "memory");
    }
    __syncthreads();
}

__device__ __forceinline__ void b_exchange(unsigned* c, int n, const void* src, uint32_t sbase, uint64_t pol) {
    TS(n == BS_Q ? 24 : 28);
    __syncthreads();
    if (threadIdx.x == 0) {
        TS(n == BS_Q ? 25 : 29);
        fence_gpu();
        TS(n == BS_Q ? 26 : 30);
        red_add_u32(c, 1u);
        wait_count(c, NBCTA);
        TS(n == BS_Q ? 27 : 31);
        b_issue_xchg(n, src, sbase, pol);
    }
}

template <bool CLU>
__device__ __noinline__ void b_chain(const Params& p, char* smem, uint32_t sbase, int bi, unsigned epoch, uint64_t pol) {
    const int tid = threadIdx.x, warp = tid >> 5, lane = tid & 31, g = lane >> 2, t = lane & 3;
    unsigned (*ctl)[32] = g_ctl[epoch & 1];
    float* red = reinterpret_cast<float*>(smem + 5 * SLOT);
    __syncthreads();
    b_gemm(p, sbase, 0, BS_WUK, DM, sbase + M_XB, 0, XP, bi, pol);
    TS(6);
    {
        uint32_t Q[16];
#pragma unroll
        for (int c = 0; c < 16; c++) Q[c] = lds32(sbase + M_QB + (g & 3) * QP + c * 16 + t * 4);
        float* qa = reinterpret_cast<float*>(smem + M_QA);
#pragma unroll 1
        for (int n = BS_WUK; n < BS_Q; n++) {
            b_wait(n, sbase);
            const uint32_t base = sbase + (n % BRING) * SLOT + (warp * 16 + (lane & 15)) * 128;
            float d[2][4];
#pragma unroll
            for (int i = 0; i < 8; i++) d[i >> 2][i & 3] = 0.f;
#pragma unroll
            for (int s = 0; s < 8; s++) {
                uint32_t a[4];
                ldsm4(a, base + (s >> 2) * 16384 + (((2 * (s & 3) + (lane >> 4)) ^ (lane & 7)) * 16));
                mma16816(d[s & 1], a, Q[2 * s], Q[2 * s + 1]);
            }
            const int c = (n - BS_WUK) * 128 + warp * 16 + g + 8 * (t >> 1);
            qa[(2 * (t & 1)) * 512 + c] = (t & 2) ? d[0][2] + d[1][2] : d[0][0] + d[1][0];
            qa[(2 * (t & 1) + 1) * 512 + c] = (t & 2) ? d[0][3] + d[1][3] : d[0][1] + d[1][1];
            __syncthreads();
            if (tid == 0) b_issue(p, n + BD, bi, sbase, pol);
        }
#pragma unroll 1
        for (int r = 0; r < 2; r++) {
            const int id = tid + r * 256;
            const int b = id >> 7, c0 = ((id >> 2) & 31) * 16 + (id & 3) * 2;
            const float2 u0 = *reinterpret_cast<const float2*>(qa + b * 512 + c0);
            const float2 u1 = *reinterpret_cast<const float2*>(qa + b * 512 + c0 + 8);
            const uint32_t h0 = pack_bf16(u0.x, u0.y), h1 = pack_bf16(u1.x, u1.y);
            const uint32_t l0 = pack_bf16(u0.x - bf_lo(h0), u0.y - bf_hi(h0)), l1 = pack_bf16(u1.x - bf_lo(h1), u1.y - bf_hi(h1));
            g_qabs[((id >> 2) * 4 + (bi >> 3)) * 32 + (bi & 7) * 4 + (id & 3)] = make_uint4(h0, l0, h1, l1);
        }
    }
    b_exchange(&ctl[C_BBAR][0], BS_Q, &g_qabs[(bi >> 3) * 4096], sbase, pol);
    {
        uint32_t qf[4][4][4];
        b_wait(BS_Q + (warp >> 2), sbase);
        TS(7);
        {
            const uint4* qs = reinterpret_cast<const uint4*>(smem + ((BS_Q + (warp >> 2)) % BRING) * SLOT) + (warp & 3) * 512 + lane;
#pragma unroll
            for (int s = 0; s < 4; s++)
#pragma unroll
                for (int i = 0; i < 4; i++) {
                    const uint4 v = qs[(s * 4 + i) * 32];
                    qf[i][s][0] = v.x; qf[i][s][1] = v.y; qf[i][s][2] = v.z; qf[i][s][3] = v.w;
                }
        }
        __syncthreads();
        if (tid == 0) { b_issue(p, BS_Q + BD, bi, sbase, pol); b_issue(p, BS_Q + 1 + BD, bi, sbase, pol); }
        float acc[2][8][4];
#pragma unroll
        for (int i = 0; i < 2; i++)
#pragma unroll
            for (int j = 0; j < 8; j++) { acc[i][j][0] = acc[i][j][1] = acc[i][j][2] = acc[i][j][3] = 0.f; }
        float mrun = -INFINITY, lrun = 0.f;
        const int head = tid >> 3, kq = tid & 7;
        float* alpha = reinterpret_cast<float*>(smem + M_ALPHA);
        for (int n = BS_CKV; n < BS_PART; n++) {
            b_wait(n, sbase);
            const uint32_t slot = sbase + (n % BRING) * SLOT;
            float sc[4][4][4];
#pragma unroll
            for (int i = 0; i < 4; i++)
#pragma unroll
                for (int j = 0; j < 4; j++) { sc[i][j][0] = sc[i][j][1] = sc[i][j][2] = sc[i][j][3] = 0.f; }
#pragma unroll
            for (int j = 0; j < 4; j++)
#pragma unroll
                for (int sp = 0; sp < 2; sp++) {
                    uint32_t bf[4];
                    ldsm4(bf, slot + warp * 4096 + (8 * j + (lane & 7)) * 128 + (((4 * sp + (lane >> 3)) ^ (lane & 7)) * 16));
#pragma unroll
                    for (int i = 0; i < 4; i++) {
                        mma16816(sc[i][j], qf[i][2 * sp], bf[0], bf[1]);
                        mma16816(sc[i][j], qf[i][2 * sp + 1], bf[2], bf[3]);
                    }
                }
#pragma unroll
            for (int i = 0; i < 4; i++)
#pragma unroll
                for (int j = 0; j < 4; j++)
                    *reinterpret_cast<float2*>(red + warp * 1024 + (8 * i + g) * 32 + ((8 * j) ^ (8 * (g & 3))) + 2 * t) =
                        make_float2(sc[i][j][0] + sc[i][j][2], sc[i][j][1] + sc[i][j][3]);
            __syncthreads();
            if (tid == 0 && n > BS_CKV) b_issue(p, n - 1 + BD, bi, sbase, pol);
            {
                float4 s = make_float4(0.f, 0.f, 0.f, 0.f);
#pragma unroll
                for (int w = 0; w < 8; w++) {
                    const float4 v = *reinterpret_cast<const float4*>(red + w * 1024 + head * 32 + ((4 * kq) ^ (8 * (head & 3))));
                    s.x += v.x; s.y += v.y; s.z += v.z; s.w += v.w;
                }
                const uint32_t r0 = pack_bf16(s.x, s.y), r1 = pack_bf16(s.z, s.w);
                const uint32_t s0 = pack_bf16(bf_lo(r0) * SCALE, bf_hi(r0) * SCALE);
                const uint32_t s1 = pack_bf16(bf_lo(r1) * SCALE, bf_hi(r1) * SCALE);
                const float f0 = bf_lo(s0), f1 = bf_hi(s0), f2 = bf_lo(s1), f3 = bf_hi(s1);
                float mx = fmaxf(fmaxf(f0, f1), fmaxf(f2, f3));
                mx = fmaxf(mx, __shfl_xor_sync(~0u, mx, 1));
                mx = fmaxf(mx, __shfl_xor_sync(~0u, mx, 2));
                mx = fmaxf(mx, __shfl_xor_sync(~0u, mx, 4));
                const float mnew = fmaxf(mrun, mx);
                const float al = expsub(mrun, mnew);
                const float p0 = expsub(f0, mnew), p1 = expsub(f1, mnew), p2 = expsub(f2, mnew), p3 = expsub(f3, mnew);
                lrun = lrun * al + ((p0 + p1) + (p2 + p3));
                mrun = mnew;
                *reinterpret_cast<uint2*>(smem + M_P + head * 80 + kq * 8) = make_uint2(pack_bf16(p0, p1), pack_bf16(p2, p3));
                if (kq == 0) alpha[head] = al;
            }
            __syncthreads();
            {
                uint32_t pf[2][2][4];
#pragma unroll
                for (int i = 0; i < 2; i++)
#pragma unroll
                    for (int ks = 0; ks < 2; ks++)
                        ldsm4(pf[i][ks], sbase + M_P + (16 * i + (lane & 15)) * 80 + (16 * ks + 8 * (lane >> 4)) * 2);
#pragma unroll
                for (int i = 0; i < 2; i++) {
                    const float a0 = alpha[16 * i + g], a1 = alpha[16 * i + 8 + g];
#pragma unroll
                    for (int j = 0; j < 8; j++) { acc[i][j][0] *= a0; acc[i][j][1] *= a0; acc[i][j][2] *= a1; acc[i][j][3] *= a1; }
                }
#pragma unroll
                for (int j = 0; j < 8; j++) {
                    uint32_t bf[4];
                    ldsm4t(bf, slot + warp * 4096 + lane * 128 + ((j ^ (lane & 7)) * 16));
#pragma unroll
                    for (int i = 0; i < 2; i++) {
                        mma16816(acc[i][j], pf[i][0], bf[0], bf[1]);
                        mma16816(acc[i][j], pf[i][1], bf[2], bf[3]);
                    }
                }
            }
        }
        __syncthreads();
        if (tid == 0) b_issue(p, BS_PART - 1 + BD, bi, sbase, pol);
        lrun += __shfl_xor_sync(~0u, lrun, 1);
        lrun += __shfl_xor_sync(~0u, lrun, 2);
        lrun += __shfl_xor_sync(~0u, lrun, 4);
        if (kq == 0) g_bml[head * NBCTA + bi] = make_float2(mrun, lrun);
#pragma unroll
        for (int i = 0; i < 2; i++)
#pragma unroll
            for (int j = 0; j < 8; j++) {
                g_bpart[((16 * i + g) * NBCTA + bi) * 256 + warp * 32 + j * 4 + t] = make_float2(acc[i][j][0], acc[i][j][1]);
                g_bpart[((16 * i + 8 + g) * NBCTA + bi) * 256 + warp * 32 + j * 4 + t] = make_float2(acc[i][j][2], acc[i][j][3]);
            }
    }
#pragma unroll 1
    for (int i = tid; i < NH * 36 && !(CLU); i += 256) g_outb[bi * NH * 36 + i] = make_uint4(0u, epoch, 0u, epoch);
    b_exchange(&ctl[C_BBAR + 1][0], BS_PART, &g_bpart[bi * NBCTA * 256], sbase, pol);
    {
        float* omega = reinterpret_cast<float*>(smem + M_OMEGA);
        if (warp == 0) {
            __syncwarp();
            const uint2 ml = ld_relaxed8(&g_bml[bi * NBCTA + lane]);
            const float ms = __uint_as_float(ml.x);
            float m = ms;
            m = fmaxf(m, __shfl_xor_sync(~0u, m, 1));
            m = fmaxf(m, __shfl_xor_sync(~0u, m, 2));
            m = fmaxf(m, __shfl_xor_sync(~0u, m, 4));
            const float w = expsub(ms, m);
            float l = w * __uint_as_float(ml.y);
            l += __shfl_xor_sync(~0u, l, 1);
            l += __shfl_xor_sync(~0u, l, 2);
            l += __shfl_xor_sync(~0u, l, 4);
            omega[lane] = w / l;
        }
        __syncthreads();
        b_wait(BS_PART, sbase);
        b_wait(BS_PART + 1, sbase);
#pragma unroll 1
        for (int b = 0; b < 4; b++) {
            const float2* ps = reinterpret_cast<const float2*>(smem + ((BS_PART + (b >> 1)) % BRING) * SLOT) + (b & 1) * 2048 + tid;
            float c0 = 0.f, c1 = 0.f;
#pragma unroll
            for (int s = 0; s < 8; s++) {
                const float w = omega[b * 8 + s];
                const float2 v = ps[s * 256];
                c0 = fmaf(w, v.x, c0);
                c1 = fmaf(w, v.y, c1);
            }
            const uint32_t hi = pack_bf16(c0, c1);
            *reinterpret_cast<uint32_t*>(smem + M_CH + b * CP + tid * 4) = hi;
            *reinterpret_cast<uint32_t*>(smem + M_CL + b * CP + tid * 4) = pack_bf16(c0 - bf_lo(hi), c1 - bf_hi(hi));
        }
        __syncthreads();
        if (tid == 0) { b_issue(p, BS_PART + BD, bi, sbase, pol); b_issue(p, BS_PART + 1 + BD, bi, sbase, pol); }
    }
    b_gemm(p, sbase, BS_WUV, BS_END, 512, sbase + M_CH, sbase + M_CL, CP, bi, pol);
    TS(12);
    if (CLU) {
        if (tid < 128) {
            const uint32_t xo = sbase + M_QB + (g & 3) * QP + (tid >> 4) * 32 + t * 4;
            st_tagged2(&g_ctx[bi * 128 + tid], __uint_as_float(lds32(xo)), __uint_as_float(lds32(xo + 16)), epoch + 1);
        }
        return;
    }
    if (tid == 0) {
#pragma unroll 1
        for (int i = 0; i < 4; i++) {
            mbar_expect_tx(sbase + M_BAR + i * 8, 36864);
            tma3d(sbase + i * 36864, &p.tm_wo, 0, bi * 128 + i * 32, 0, sbase + M_BAR + i * 8, pol);
        }
    }
    TS(8);
    {
        float acc[9][4];
#pragma unroll
        for (int j = 0; j < 9; j++) { acc[j][0] = acc[j][1] = acc[j][2] = acc[j][3] = 0.f; }
#pragma unroll 1
        for (int i = 0; i < 4; i++) {
            const uint32_t xo = sbase + M_QB + (g & 3) * QP + i * 64 + t * 4;
            const uint32_t a0[4] = {lds32(xo), 0u, lds32(xo + 16), 0u}, a1[4] = {lds32(xo + 32), 0u, lds32(xo + 48), 0u};
            mbar_wait(sbase + M_BAR + i * 8, 0);
#pragma unroll
            for (int j = 0; j < 9; j++) {
                const int nt = warp * 9 + j;
                uint32_t w[4];
                ldsm4t(w, sbase + i * 36864 + (nt >> 3) * 4096 + lane * 128 + (((nt & 7) ^ (lane & 7)) * 16));
                mma16816(acc[j], a0, w[0], w[1]);
                mma16816(acc[j], a1, w[2], w[3]);
            }
        }
        if (g < 4) {
#pragma unroll
            for (int j = 0; j < 9; j++) {
                const int c2 = (warp * 9 + j) * 4 + t;
                st_tagged2(&g_outb[((c2 / 9) * NH + bi) * 36 + g * 9 + c2 % 9], acc[j][0], acc[j][1], epoch + 1);
            }
        }
    }
    TS(9);
    {
        const uint4* src = g_outb + (bi * NH + (tid >> 3)) * 36 + (tid & 7);
        float2* part = reinterpret_cast<float2*>(red);
        unsigned n = 0;
        while (true) {
            ulonglong2 v[5];
            bool ok = true;
#pragma unroll
            for (int i = 0; i < 5; i++)
                if (i < 4 || (tid & 7) < 4) v[i] = ld_tagged2(src + i * 8);
#pragma unroll
            for (int i = 0; i < 5; i++)
                if (i < 4 || (tid & 7) < 4) {
                    ok = ok && (unsigned)(v[i].x >> 32) == epoch + 1 && (unsigned)(v[i].y >> 32) == epoch + 1;
                    part[(tid >> 3) * 36 + (tid & 7) + i * 8] = make_float2(__uint_as_float((unsigned)v[i].x), __uint_as_float((unsigned)v[i].y));
                }
            if (ok) break;
            __nanosleep(400);
            if (++n > SPIN_LIMIT) __trap();
        }
        __syncthreads();
        if (tid < 36) {
            float s0 = 0.f, s1 = 0.f;
#pragma unroll 8
            for (int h = 0; h < NH; h++) { const float2 v = part[h * 36 + tid]; s0 += v.x; s1 += v.y; }
            *reinterpret_cast<uint32_t*>(p.out + (tid / 9) * 2 * DM + DM + bi * 18 + (tid % 9) * 2) = pack_bf16(s0, s1);
        }
    }
    TS(10);
}

template <bool CLU>
__global__ void __launch_bounds__(256, 1) fused_decode_kernel(const __grid_constant__ Params p) {
    extern __shared__ __align__(1024) char smem_raw[];
    const uint32_t sbase = (smem_u32(smem_raw) + 1023u) & ~1023u;
    char* smem = smem_raw + (sbase - smem_u32(smem_raw));
    const int tid = threadIdx.x, warp = tid >> 5, lane = tid & 31;
    const int blk = blockIdx.x;
    const bool isB = CLU ? blk < NBCTA : (blk & 3) == 0 && (blk >> 2) < NBCTA;
    const int bi = CLU ? blk : blk >> 2;
    const int nb = CLU ? blk - NBCTA : blk - min(NBCTA, (blk + 3) >> 2);
    const int nnb = gridDim.x - NBCTA;
    const int nstatic = nnb * (NW + XW);
    uint64_t pol;
    asm volatile("createpolicy.fractional.L2::evict_first.b64 %0, 1.0;" : "=l"(pol));
    const uint32_t wbar = sbase + M_BAR + warp * 8, wslot = sbase + warp * SLOT;
    const int u0 = warp * nnb + nb;
    const bool hold = ((blk >> 2) >> KMIN << KMIN) * 4 * UPP < nstatic;
    const uint32_t jbar = sbase + M_BAR + (NSLOT + BRING) * 8;
    if (warp == 7) {
        if (lane == 0 && blk < 128) {
            mbar_init(jbar, 1);
            asm volatile("fence.mbarrier_init.release.cluster;" ::: "memory");
            uint64_t poln;
            asm volatile("createpolicy.fractional.L2::evict_normal.b64 %0, 1.0;" : "=l"(poln));
            mbar_expect_tx(jbar, 36864 + 4 * 1152);
            tma3d(sbase + J0W, &p.tm_j0, blk * 32, 0, 0, jbar, poln);
            bulk_load(sbase + M_XA, p.xa, 4608, jbar, poln);
        }
        if (lane < 16) reinterpret_cast<unsigned*>(smem + M_HELP)[lane] = 0;
        __syncwarp();
        if (!isB) asm volatile("bar.arrive 2, %0;" ::"n"(32 * (NW + XW + 1)) : "memory");
    }
    if (warp < 4 && lane == 0) {
        mbar_init(wbar, 1);
        if (CLU && warp == 3 && !isB) {
#pragma unroll
            for (int i = 0; i < 2; i++) {
                mbar_init(sbase + F_BAR + i * 8, 1);
                mbar_expect_tx(sbase + F_BAR + i * 8, 4096);
            }
        }
        asm volatile("fence.mbarrier_init.release.cluster;" ::: "memory");
        if (warp < NEARLY && !isB && !hold) {
            mbar_expect_tx(wbar, TILE_BYTES);
            bulk_load(wslot, block_src(p.kc, unit_block<CLU>(u0)), TILE_BYTES, wbar, pol);
        }
    }
    unsigned epoch = 0;
    if (lane == 0) epoch = ld_relaxed4(&g_epoch);
    TS(0);
    if (CLU && !isB) asm volatile("barrier.cluster.arrive.relaxed.aligned;" ::: "memory");
    if ((warp >> 1) == 2 && blk < 128) st_relaxed64(&g_qll[((tid - 128) >> 4) * 2048 + blk * 16 + (tid & 15)], 0ull);
    if (isB || warp >= NW + XW) epoch = __shfl_sync(~0u, epoch, 0);
    if (isB && warp == 3) asm volatile("bar.sync 1, 160;" ::: "memory");
    if (isB && tid == 96) {
#pragma unroll 1
        for (int i = 0; i < BRING; i++) mbar_init(sbase + M_BAR + (NSLOT + i) * 8, 1);
        asm volatile("fence.mbarrier_init.release.cluster;" ::: "memory");
        if (hold) { unsigned n = 0; while (ld_acquire_cta_shared(sbase + M_HELP + 24) < 2) { if (++n > (SPIN_LIMIT << 4)) __trap(); } }
#pragma unroll 1
        for (int b = 0; b < 4; b++) bulk_load(sbase + M_XB + b * XP, p.xb + b * DM, 1152, sbase + M_BAR + NSLOT * 8, pol);
#pragma unroll 1
        for (int n = 0; n < BD; n++) b_issue(p, n, bi, sbase, pol);
    }
    if (warp >= 4 && blk < 128) {
        const int g = lane >> 2, t = lane & 3, j = tid - 128;
        asm volatile("bar.sync 1, %0;" ::"r"(isB ? 160 : 128) : "memory");
#pragma unroll 1
        for (int sl = blk, ph = 0;; sl += 128 - gridDim.x, ph = 1) {
        mbar_wait(jbar, ph);
        TS(13);
        float acc[4][4];
#pragma unroll
        for (int i = 0; i < 16; i++) acc[i >> 2][i & 3] = 0.f;
        const uint32_t wa = sbase + J0W + ((warp - 4) * 144 + (lane & 15)) * 64;
        const uint32_t sw = (lane >> 1) & 3, xa = sbase + M_XA + (g & 3) * 1152 + (warp - 4) * 288 + t * 4;
#pragma unroll 3
        for (int s = 0; s < 9; s++) {
            const uint32_t a[4] = {lds32(xa + s * 32), 0u, lds32(xa + s * 32 + 16), 0u};
            uint32_t w0[4], w1[4];
            ldsm4t(w0, wa + s * 1024 + (((lane >> 4) ^ sw) * 16));
            ldsm4t(w1, wa + s * 1024 + (((2 + (lane >> 4)) ^ sw) * 16));
            mma16816(acc[0], a, w0[0], w0[1]);
            mma16816(acc[1], a, w0[2], w0[3]);
            mma16816(acc[2], a, w1[0], w1[1]);
            mma16816(acc[3], a, w1[2], w1[3]);
        }
        float2* j0 = reinterpret_cast<float2*>(smem + M_J0);
        if (g < 4) {
#pragma unroll
            for (int i = 0; i < 4; i++) j0[(warp - 4) * 64 + g * 16 + i * 4 + t] = make_float2(acc[i][0], acc[i][1]);
        }
        asm volatile("bar.sync 1, 128;" ::: "memory");
        const bool again = sl == blk && blk + 128 - (int)gridDim.x >= (int)gridDim.x;
        if (again && tid == 224) {
            mbar_expect_tx(jbar, 36864);
            tma3d(sbase + J0W, &p.tm_j0, (blk + 128 - gridDim.x) * 32, 0, 0, jbar, pol);
        }
        if (warp < 6) {
            const float2 v0 = j0[j], v1 = j0[64 + j], v2 = j0[128 + j], v3 = j0[192 + j];
            st_relaxed64(&g_qll[(j >> 4) * 2048 + sl * 16 + (j & 15)],
                         (unsigned long long)pack_bf16((v0.x + v1.x) + (v2.x + v3.x), (v0.y + v1.y) + (v2.y + v3.y)) |
                             ((unsigned long long)(epoch + 1) << 32));
            __syncwarp();
            if (lane == 0) asm volatile("red.relaxed.cta.shared::cta.add.u32 [%0], 1;" ::"r"(sbase + M_HELP + 24) : "memory");
        } else if (warp == 7) {
            if (blk < C_LINES) g_ctl[(epoch & 1) ^ 1][blk][lane] = 0;
        }
        TS(1);
        if (!again) break;
        asm volatile("bar.sync 1, 128;" ::: "memory");
        }
    }
    if (isB) {
        b_chain<CLU>(p, smem, sbase, bi, epoch, pol);
        return;
    }
    if (warp < NW + XW) {
        a_worker<CLU>(p, u0, warp >= NW + ((nb & 3) < (CLU ? X3C : X3) ? 1 : 0), warp < NEARLY && !hold, hold, nstatic, wslot, wbar, sbase + M_HELP, epoch, pol);
        if (CLU && nb < NFIN) {
            if (warp == 3) out_issue_sum(p, sbase, nb >> 3, nb & 7, pol);
            else if (warp == 0) out_late(sbase, nb >> 3, nb & 7);
        }
        return;
    } else if (warp == 7) {
#pragma unroll 1
        for (int i = nb; i < 4 * NH; i += nnb) g_oacc[i * 32 + lane] = make_float4(0.f, 0.f, 0.f, 0.f);
        if (nb < NREP * NH) g_vdone[nb][lane] = 0;
        __syncwarp();
        k_helper(sbase + M_HELP, epoch);
        if (nb == 0 && lane == 0) g_epoch = epoch + 1;
        __syncwarp();
        if (CLU && nb < NFIN) out_early(sbase, nb >> 3, nb & 7, epoch + 1);
    } else if (CLU) {
    } else if (warp == 6 && nb < NFIN) {
        finisher(p, sbase, nb);
        TS(4);
    } else if (warp >= 6 - NPOLL && nb < NFIN) {
        v_poller(sbase, nb, warp - (6 - NPOLL));
    }
    if (CLU && nb < NFIN) out_project(sbase, nb & 7, warp - 4);
}

}

typedef CUresult (*EncodeFn)(CUtensorMap*, CUtensorMapDataType, cuuint32_t, void*, const cuuint64_t*, const cuuint64_t*,
                             const cuuint32_t*, const cuuint32_t*, CUtensorMapInterleave, CUtensorMapSwizzle,
                             CUtensorMapL2promotion, CUtensorMapFloatOOBfill);

extern "C" void kernel_launch(void* const* d_in, const int* in_sizes, int n_in, void* d_out, int out_size) {
    (void)in_sizes; (void)n_in; (void)out_size;
    static int nsm = 0, ncl = 0;
    static EncodeFn encode = nullptr;
    cudaLaunchConfig_t cfg = {};
    cudaLaunchAttribute at[1];
    at[0].id = cudaLaunchAttributeClusterDimension;
    at[0].val.clusterDim.x = 8; at[0].val.clusterDim.y = 1; at[0].val.clusterDim.z = 1;
    cfg.blockDim = dim3(256); cfg.dynamicSmemBytes = SMEM_BYTES; cfg.stream = cudaStreamPerThread; cfg.attrs = at; cfg.numAttrs = 1;
    if (nsm == 0) {
        int dev = 0;
        cudaGetDevice(&dev);
        cudaDeviceGetAttribute(&nsm, cudaDevAttrMultiProcessorCount, dev);
        cudaFuncSetAttribute(fused_decode_kernel<false>, cudaFuncAttributeMaxDynamicSharedMemorySize, SMEM_BYTES);
        cudaFuncSetAttribute(fused_decode_kernel<true>, cudaFuncAttributeMaxDynamicSharedMemorySize, SMEM_BYTES);
        cfg.gridDim = dim3(128);
        if (cudaOccupancyMaxActiveClusters(&ncl, fused_decode_kernel<true>, &cfg) != cudaSuccess) { ncl = 0; (void)cudaGetLastError(); }
        if (ncl > MINCL) ncl = MINCL;
        void* fn = nullptr;
        cudaDriverEntryPointQueryResult qr;
        cudaGetDriverEntryPoint("cuTensorMapEncodeTiled", &fn, cudaEnableDefault, &qr);
        encode = (EncodeFn)fn;
    }
    Params p;
    auto panels = [&](CUtensorMap* tm, void* ptr, int rows, int cols, int box_rows, int box_panels) {
        const cuuint64_t gd[3] = {64, (cuuint64_t)rows, (cuuint64_t)(cols / 64)}, gs[2] = {(cuuint64_t)cols * 2, 128};
        const cuuint32_t box[3] = {64, (cuuint32_t)box_rows, (cuuint32_t)box_panels}, es[3] = {1, 1, 1};
        encode(tm, CU_TENSOR_MAP_DATA_TYPE_BFLOAT16, 3, ptr, gd, gs, box, es, CU_TENSOR_MAP_INTERLEAVE_NONE,
               CU_TENSOR_MAP_SWIZZLE_128B, CU_TENSOR_MAP_L2_PROMOTION_L2_256B, CU_TENSOR_MAP_FLOAT_OOB_FILL_NONE);
    };
    panels(&p.tm_wq, d_in[7], DM, 4096, 128, 2);
    panels(&p.tm_wuk, d_in[8], 512, 4096, 128, 2);
    panels(&p.tm_wuv, d_in[9], 512, 4096, 128, 2);
    panels(&p.tm_wo, d_in[10], 4096, DM, 32, 9);
    panels(&p.tm_wf, d_in[10], 4096, DM, 128, 1);
    panels(&p.tm_ckv, d_in[6], 4 * SK, 512, 32, 8);
    {
        const cuuint64_t gd[3] = {4096, 192, 3}, gs[2] = {8192, 192 * 8192};
        const cuuint32_t box[3] = {32, 192, 3}, es[3] = {1, 1, 1};
        encode(&p.tm_j0, CU_TENSOR_MAP_DATA_TYPE_BFLOAT16, 3, d_in[3], gd, gs, box, es, CU_TENSOR_MAP_INTERLEAVE_NONE,
               CU_TENSOR_MAP_SWIZZLE_64B, CU_TENSOR_MAP_L2_PROMOTION_L2_128B, CU_TENSOR_MAP_FLOAT_OOB_FILL_NONE);
    }
    {
        const cuuint64_t gd[3] = {DM, 512, 8}, gs[2] = {8 * DM * 2, DM * 2};
        const cuuint32_t box[3] = {64, 16, 8}, es[3] = {1, 1, 1};
        encode(&p.tm_wl, CU_TENSOR_MAP_DATA_TYPE_BFLOAT16, 3, d_in[4], gd, gs, box, es, CU_TENSOR_MAP_INTERLEAVE_NONE,
               CU_TENSOR_MAP_SWIZZLE_128B, CU_TENSOR_MAP_L2_PROMOTION_L2_256B, CU_TENSOR_MAP_FLOAT_OOB_FILL_NONE);
    }
    p.xa = (const __nv_bfloat16*)d_in[0];
    p.kc = (const __nv_bfloat16*)d_in[1];
    p.vc = (const __nv_bfloat16*)d_in[2];
    p.wo = (const __nv_bfloat16*)d_in[4];
    p.xb = (const __nv_bfloat16*)d_in[5];
    p.wob = (const __nv_bfloat16*)d_in[10];
    p.out = (__nv_bfloat16*)d_out;
    if (ncl >= MINCL) {
        cfg.gridDim = dim3(8 * ncl);
        cudaLaunchKernelEx(&cfg, fused_decode_kernel<true>, p);
    } else {
        fused_decode_kernel<false><<<nsm, 256, SMEM_BYTES, cudaStreamPerThread>>>(p);
    }
}
```

```cpp
#include <cuda_runtime.h>
#include <cuda.h>
#include <cuda_bf16.h>
#include <stdint.h>

namespace {

constexpr int NH = 32, SK = 4096, DM = 576;
constexpr int KEYS = 128;
constexpr int UPP = SK / KEYS;
constexpr int NUK = 4 * NH * UPP;
constexpr int TILE_BYTES = KEYS * 256;
#define NWORK 2
constexpr int NW = NWORK;
constexpr int NBCTA = 32;
constexpr int MINCL = 15;
constexpr int NFIN = 72;
constexpr int SLOT = 32768;
constexpr int NSLOT = 6;
constexpr int BRING = 5;
constexpr int J0W = 5 * SLOT;
constexpr int MISC = NSLOT * SLOT + 4096;
constexpr int XP = 1168, CP = 1040, QP = 272;
constexpr int M_XA = MISC;
constexpr int M_XB = M_XA + 4 * XP;
constexpr int M_CH = M_XB + 4 * XP;
constexpr int M_CL = M_CH + 4 * CP;
constexpr int M_QB = M_CL + 4 * CP;
constexpr int M_QA = M_CH;
constexpr int M_J0 = M_QB + 4 * QP;
constexpr int M_P = M_J0 + 2048;
constexpr int M_ALPHA = M_P + 2560;
constexpr int M_OMEGA = M_ALPHA + 128;
constexpr int M_BAR = M_OMEGA + 128;
constexpr int M_HELP = M_BAR + 128;
constexpr int F_W = 3 * SLOT;
constexpr int F_X = NSLOT * SLOT, FXP = 1088;
constexpr int F_RECV = F_X + 8 * FXP;
constexpr int F_BAR = M_P;
constexpr int SMEM_BYTES = M_HELP + 128 + 1024;
static_assert(F_RECV + 2048 <= M_J0, "output phase layout");
static_assert(SMEM_BYTES <= 232448 && M_BAR % 8 == 0 && M_QA % 16 == 0 && M_P % 16 == 0, "smem layout");
#define XW 2
#define X3 1
#define X3C 2
#define NEARLY 2
#define BD 4
#define FPF 3
#define FSLEEP 800
#define VS0 24
#define FJ 270
#define FP 384
#define NPOLL 2
#define PGAP 200
static_assert(NW + XW <= 4 && NEARLY <= NW + XW && BD <= BRING, "slots 4 and 5 hold the finisher weights");
constexpr int KMIN = 2, KMAX = 4, VMIN = 0, VMAX = 4;
constexpr float SCALE = 0.08838834764831845f;
constexpr float LOG2E = 1.4426950408889634f;
constexpr unsigned SPIN_LIMIT = 1u << 24;

#define NREP 2
constexpr int C_QUEUE = 0, C_KDONE = 1, C_BBAR = 3, C_LINES = 5;

struct Params {
    const __nv_bfloat16 *kc, *xa, *vc, *wo, *xb, *wob;
    __nv_bfloat16* out;
    CUtensorMap tm_j0;
    CUtensorMap tm_wq, tm_wuk, tm_ckv, tm_wuv, tm_wo;
    CUtensorMap tm_wl;
    CUtensorMap tm_wf;
};

__device__ unsigned g_epoch;
__device__ unsigned g_ctl[2][C_LINES][32];
__device__ uint2 g_qll[4 * 2048];
__device__ uint2 g_scores[128 * SK / 4];
__device__ float2 g_stats[128 * UPP];
__device__ float4 g_oacc[128 * 32];
__device__ unsigned g_vdone[NREP * NH][32];
__device__ uint4 g_qabs[4 * 8 * 4 * 4 * 32];
__device__ float2 g_bpart[NBCTA * NH * 256];
__device__ float2 g_bml[NBCTA * NH];
__device__ uint4 g_ctx[NH * 128];
__device__ uint4 g_outb[NBCTA * NH * 36];

#define TS(i)
#define TSV(i, v)
#define LAND(i)
#define CLK(x)
#define ACC(a, x, y)

__device__ __forceinline__ uint32_t smem_u32(const void* p) { return (uint32_t)__cvta_generic_to_shared(p); }
__device__ __forceinline__ void mbar_init(uint32_t bar, uint32_t cnt) {
    asm volatile("mbarrier.init.shared::cta.b64 [%0], %1;" ::"r"(bar), "r"(cnt) : "memory");
}
__device__ __forceinline__ void mbar_expect_tx(uint32_t bar, uint32_t bytes) {
    asm volatile("mbarrier.arrive.expect_tx.shared::cta.b64 _, [%0], %1;" ::"r"(bar), "r"(bytes) : "memory");
}
__device__ __forceinline__ bool mbar_try(uint32_t bar, uint32_t parity) {
    uint32_t ok;
    asm volatile("{\n.reg .pred p;\nmbarrier.try_wait.parity.shared::cta.b64 p, [%1], %2;\nselp.u32 %0, 1, 0, p;\n}\n"
                 : "=r"(ok) : "r"(bar), "r"(parity) : "memory");
    return ok;
}
__device__ __forceinline__ void mbar_wait(uint32_t bar, uint32_t parity) {
    unsigned n = 0;
    while (!mbar_try(bar, parity)) { if (++n > SPIN_LIMIT) __trap(); }
}
__device__ __forceinline__ void bulk_load(uint32_t dst, const void* src, uint32_t bytes, uint32_t bar, uint64_t pol) {
    asm volatile("cp.async.bulk.shared::cluster.global.mbarrier::complete_tx::bytes.L2::cache_hint [%0], [%1], %2, [%3], %4;"
                 ::"r"(dst), "l"(src), "r"(bytes), "r"(bar), "l"(pol) : "memory");
}
__device__ __forceinline__ void tma3d(uint32_t dst, const CUtensorMap* tm, int c0, int c1, int c2, uint32_t bar, uint64_t pol) {
    asm volatile("cp.async.bulk.tensor.3d.shared::cluster.global.mbarrier::complete_tx::bytes.L2::cache_hint [%0], [%1, {%3,%4,%5}], [%2], %6;"
                 ::"r"(dst), "l"(tm), "r"(bar), "r"(c0), "r"(c1), "r"(c2), "l"(pol) : "memory");
}
__device__ __forceinline__ void l2_prefetch(const void* src, uint32_t bytes) {
    asm volatile("cp.async.bulk.prefetch.L2.global [%0], %1;" ::"l"(src), "r"(bytes) : "memory");
}
__device__ __forceinline__ void ldsm4(uint32_t (&r)[4], uint32_t addr) {
    asm volatile("ldmatrix.sync.aligned.m8n8.x4.shared.b16 {%0,%1,%2,%3}, [%4];"
                 : "=r"(r[0]), "=r"(r[1]), "=r"(r[2]), "=r"(r[3]) : "r"(addr));
}
__device__ __forceinline__ void ldsm4t(uint32_t (&r)[4], uint32_t addr) {
    asm volatile("ldmatrix.sync.aligned.m8n8.x4.trans.shared.b16 {%0,%1,%2,%3}, [%4];"
                 : "=r"(r[0]), "=r"(r[1]), "=r"(r[2]), "=r"(r[3]) : "r"(addr));
}
__device__ __forceinline__ void mma16816(float (&d)[4], const uint32_t (&a)[4], uint32_t b0, uint32_t b1) {
    asm("mma.sync.aligned.m16n8k16.row.col.f32.bf16.bf16.f32 {%0,%1,%2,%3}, {%4,%5,%6,%7}, {%8,%9}, {%0,%1,%2,%3};"
        : "+f"(d[0]), "+f"(d[1]), "+f"(d[2]), "+f"(d[3])
        : "r"(a[0]), "r"(a[1]), "r"(a[2]), "r"(a[3]), "r"(b0), "r"(b1));
}
__device__ __forceinline__ void wgmma_tile(float (&d)[4], uint32_t da, uint32_t db, int accumulate) {
    asm volatile("{\n.reg .pred p;\n.reg .b32 x, y;\n.reg .b64 a, b;\nsetp.ne.u32 p, %6, 0;\nwgmma.fence.sync.aligned;\n"
                 "add.u32 x, %4, 0;\nadd.u32 y, %5, 0;\nmov.b64 a, {x, 0x40000040};\nmov.b64 b, {y, 1};\n"
                 "wgmma.mma_async.sync.aligned.m64n8k16.f32.bf16.bf16 {%0,%1,%2,%3}, a, b, p, 1, 1, 1, 0;\n"
                 "add.u32 x, %4, 128;\nadd.u32 y, %5, 8;\nmov.b64 a, {x, 0x40000040};\nmov.b64 b, {y, 1};\n"
                 "wgmma.mma_async.sync.aligned.m64n8k16.f32.bf16.bf16 {%0,%1,%2,%3}, a, b, 1, 1, 1, 1, 0;\n"
                 "add.u32 x, %4, 256;\nadd.u32 y, %5, 16;\nmov.b64 a, {x, 0x40000040};\nmov.b64 b, {y, 1};\n"
                 "wgmma.mma_async.sync.aligned.m64n8k16.f32.bf16.bf16 {%0,%1,%2,%3}, a, b, 1, 1, 1, 1, 0;\n"
                 "add.u32 x, %4, 384;\nadd.u32 y, %5, 24;\nmov.b64 a, {x, 0x40000040};\nmov.b64 b, {y, 1};\n"
                 "wgmma.mma_async.sync.aligned.m64n8k16.f32.bf16.bf16 {%0,%1,%2,%3}, a, b, 1, 1, 1, 1, 0;\n"
                 "add.u32 x, %4, 512;\nadd.u32 y, %5, 32;\nmov.b64 a, {x, 0x40000040};\nmov.b64 b, {y, 1};\n"
                 "wgmma.mma_async.sync.aligned.m64n8k16.f32.bf16.bf16 {%0,%1,%2,%3}, a, b, 1, 1, 1, 1, 0;\n"
                 "add.u32 x, %4, 640;\nadd.u32 y, %5, 40;\nmov.b64 a, {x, 0x40000040};\nmov.b64 b, {y, 1};\n"
                 "wgmma.mma_async.sync.aligned.m64n8k16.f32.bf16.bf16 {%0,%1,%2,%3}, a, b, 1, 1, 1, 1, 0;\n"
                 "add.u32 x, %4, 768;\nadd.u32 y, %5, 48;\nmov.b64 a, {x, 0x40000040};\nmov.b64 b, {y, 1};\n"
                 "wgmma.mma_async.sync.aligned.m64n8k16.f32.bf16.bf16 {%0,%1,%2,%3}, a, b, 1, 1, 1, 1, 0;\n"
                 "add.u32 x, %4, 896;\nadd.u32 y, %5, 56;\nmov.b64 a, {x, 0x40000040};\nmov.b64 b, {y, 1};\n"
                 "wgmma.mma_async.sync.aligned.m64n8k16.f32.bf16.bf16 {%0,%1,%2,%3}, a, b, 1, 1, 1, 1, 0;\n"
                 "wgmma.commit_group.sync.aligned;\n}"
                 : "+f"(d[0]), "+f"(d[1]), "+f"(d[2]), "+f"(d[3]) : "r"(da), "r"(db), "r"(accumulate) : "memory");
}
__device__ __forceinline__ uint32_t lds32(uint32_t a) {
    uint32_t v;
    asm volatile("ld.shared.u32 %0, [%1];" : "=r"(v) : "r"(a));
    return v;
}
__device__ __forceinline__ unsigned ld_acquire(const unsigned* p) {
    unsigned v;
    asm volatile("ld.acquire.gpu.global.u32 %0, [%1];" : "=r"(v) : "l"(p) : "memory");
    return v;
}
__device__ __forceinline__ uint2 ld_relaxed8(const void* p) {
    uint2 v;
    asm volatile("ld.relaxed.gpu.global.v2.u32 {%0,%1}, [%2];" : "=r"(v.x), "=r"(v.y) : "l"(p) : "memory");
    return v;
}
__device__ __forceinline__ unsigned ld_relaxed4(const void* p) {
    unsigned v;
    asm volatile("ld.relaxed.gpu.global.u32 %0, [%1];" : "=r"(v) : "l"(p) : "memory");
    return v;
}
__device__ __forceinline__ unsigned atom_inc(unsigned* p) {
    unsigned v;
    asm volatile("atom.relaxed.gpu.global.inc.u32 %0, [%1], 0x7fffffff;" : "=r"(v) : "l"(p) : "memory");
    return v;
}
__device__ __forceinline__ unsigned long long ld_relaxed64(const void* p) {
    unsigned long long v;
    asm volatile("ld.relaxed.gpu.global.u64 %0, [%1];" : "=l"(v) : "l"(p) : "memory");
    return v;
}
__device__ __forceinline__ void st_relaxed64(void* p, unsigned long long v) {
    asm volatile("st.relaxed.gpu.global.u64 [%0], %1;" ::"l"(p), "l"(v) : "memory");
}
__device__ __forceinline__ float4 ld_relaxed16(const void* p) {
    float4 v;
    asm volatile("ld.relaxed.gpu.global.v4.f32 {%0,%1,%2,%3}, [%4];" : "=f"(v.x), "=f"(v.y), "=f"(v.z), "=f"(v.w) : "l"(p) : "memory");
    return v;
}
__device__ __forceinline__ uint32_t mapa(uint32_t a, uint32_t rank) {
    uint32_t r;
    asm("mapa.shared::cluster.u32 %0, %1, %2;" : "=r"(r) : "r"(a), "r"(rank));
    return r;
}
__device__ __forceinline__ void mbar_spin(uint32_t bar) {
    asm volatile("{\n.reg .pred p, q;\n.reg .u32 n;\nmov.u32 n, 0;\n"
                 "SPIN:\nmbarrier.test_wait.parity.shared::cta.b64 p, [%0], 0;\nadd.u32 n, n, 1;\nsetp.gt.u32 q, n, 0x4000000;\n@q trap;\n"
                 "@!p bra.uni SPIN;\n}" ::"r"(bar) : "memory");
}
__device__ __forceinline__ void mbar_spin_cluster(uint32_t bar) {
    asm volatile("{\n.reg .pred p, q;\n.reg .u32 n;\nmov.u32 n, 0;\n"
                 "SPIN:\nmbarrier.test_wait.parity.relaxed.cluster.shared::cta.b64 p, [%0], 0;\nadd.u32 n, n, 1;\nsetp.gt.u32 q, n, 0x4000000;\n@q trap;\n"
                 "@!p bra.uni SPIN;\nfence.acquire.sync_restrict::shared::cluster.cluster;\n}" ::"r"(bar) : "memory");
}
__device__ __forceinline__ uint32_t now_ns() {
    unsigned long long t;
    asm volatile("mov.u64 %0, %globaltimer;" : "=l"(t));
    return (uint32_t)t;
}
__device__ __forceinline__ void fence_gpu() { asm volatile("fence.acq_rel.gpu;" ::: "memory"); }
__device__ __forceinline__ void red_add_u32(unsigned* p, unsigned v) {
    asm volatile("red.relaxed.gpu.global.add.u32 [%0], %1;" ::"l"(p), "r"(v) : "memory");
}
__device__ __forceinline__ void st_tagged2(void* p, float a, float b, unsigned tag) {
    const unsigned long long hi = (unsigned long long)tag << 32;
    asm volatile("st.relaxed.gpu.global.v2.b64 [%0], {%1,%2};" ::"l"(p), "l"(hi | __float_as_uint(a)), "l"(hi | __float_as_uint(b)) : "memory");
}
__device__ __forceinline__ ulonglong2 ld_tagged2(const void* p) {
    ulonglong2 v;
    asm volatile("ld.relaxed.gpu.global.v2.b64 {%0,%1}, [%2];" : "=l"(v.x), "=l"(v.y) : "l"(p) : "memory");
    return v;
}
__device__ __forceinline__ float4 atom_add_f4(void* p, float a, float b, float c, float d) {
    float4 r;
    asm volatile("atom.relaxed.gpu.global.add.v4.f32 {%0,%1,%2,%3}, [%4], {%5,%6,%7,%8};"
                 : "=f"(r.x), "=f"(r.y), "=f"(r.z), "=f"(r.w) : "l"(p), "f"(a), "f"(b), "f"(c), "f"(d) : "memory");
    return r;
}
__device__ __forceinline__ void red_release_cta_shared(uint32_t a, unsigned v) {
    asm volatile("red.release.cta.shared::cta.add.u32 [%0], %1;" ::"r"(a), "r"(v) : "memory");
}
__device__ __forceinline__ unsigned ld_acquire_cta_shared(uint32_t a) {
    unsigned v;
    asm volatile("ld.acquire.cta.shared::cta.u32 %0, [%1];" : "=r"(v) : "r"(a) : "memory");
    return v;
}
__device__ __forceinline__ void st_release_cta_shared(uint32_t a, unsigned v) {
    asm volatile("st.release.cta.shared::cta.u32 [%0], %1;" ::"r"(a), "r"(v) : "memory");
}
__device__ __forceinline__ void wait_count(const unsigned* p, unsigned target) {
    unsigned n = 0;
    while (ld_acquire(p) < target) { if (++n > SPIN_LIMIT) __trap(); }
}
__device__ __forceinline__ uint32_t pack_bf16(float lo, float hi) {
    uint32_t r;
    asm("cvt.rn.bf16x2.f32 %0, %1, %2;" : "=r"(r) : "f"(hi), "f"(lo));
    return r;
}
__device__ __forceinline__ float bf_lo(uint32_t v) { return __uint_as_float(v << 16); }
__device__ __forceinline__ float bf_hi(uint32_t v) { return __uint_as_float(v & 0xffff0000u); }
__device__ __forceinline__ float ex2(float x) { float y; asm("ex2.approx.ftz.f32 %0, %1;" : "=f"(y) : "f"(x)); return y; }
__device__ __forceinline__ float expsub(float a, float b) { return ex2((a - b) * LOG2E); }
__device__ __forceinline__ float warp_max(float v) {
#pragma unroll
    for (int m = 16; m; m >>= 1) v = fmaxf(v, __shfl_xor_sync(~0u, v, m));
    return v;
}
__device__ __forceinline__ float warp_sum(float v) {
#pragma unroll
    for (int m = 16; m; m >>= 1) v += __shfl_xor_sync(~0u, v, m);
    return v;
}
template <bool CLU>
__device__ __forceinline__ unsigned unit_block(int u) {
    const unsigned x = ((unsigned)u & (NUK - 1)) / UPP;
    const int lg = u < NUK ? min(KMAX, max(KMIN, 29 - __clz(x | 1))) : (CLU && (int)x >= 4 * VS0 ? 0 : min(VMAX, max(VMIN, 29 - __clz((127 - x) | 1))));
    const unsigned r = x & ((4u << lg) - 1);
    return ((x - r + (r & ((1u << lg) - 1)) * 4 + (r >> lg)) * UPP) | ((unsigned)u & (UPP - 1));
}
__device__ __forceinline__ const char* block_src(const void* base, unsigned blk) {
    const unsigned po = blk / UPP;
    return reinterpret_cast<const char*>(base) + (size_t)(((po & 3) * NH + (po >> 2)) * UPP + blk % UPP) * TILE_BYTES;
}

template <bool CLU>
__device__ __forceinline__ void a_worker(const Params& p, int un, bool once, bool pre, bool hold, int nstatic, uint32_t slot, uint32_t bar,
                                         uint32_t help, unsigned epoch, uint64_t pol) {
    constexpr int NU = 2 * NUK;
    const int lane = threadIdx.x & 31, g = lane >> 2, t = lane & 3;
    const int li = lane & 7;
    uint32_t kaddr[4], vaddr[8];
    {
        const int e = (lane >> 3) & 1, kk = lane >> 4;
#pragma unroll
        for (int s = 0; s < 4; s++) kaddr[s] = slot + (16 * li + e) * 256 + ((2 * s + kk + li) & 7) * 16;
        const int vrow = 4 * (li >> 1) + (li & 1) + 2 * kk;
#pragma unroll
        for (int c = 0; c < 8; c++) vaddr[c] = slot + vrow * 256 + e * 128 + ((c + li) & 7) * 16;
#pragma unroll
        for (int c = 0; c < 8; c++) asm volatile("" : "+r"(vaddr[c]));
    }
    const uint32_t vmask = (g >> 1) != t ? 0u : ((g & 1) ? 0xffff0000u : 0xffffu);
    int kseen = -1;
    unsigned long long H0 = 0, H1 = 0;
    auto header = [&](int v, unsigned vb) {
        if (v >= NU) return;
        const void *a0, *a1;
        if (v < NUK) {
            const unsigned po = vb / UPP;
            a0 = g_qll + (po & 3) * 2048 + (po >> 2) * 64 + lane;
            a1 = reinterpret_cast<const uint2*>(a0) + 32;
        } else {
            const int half = vb / (NUK / 2);
            if (half > kseen) {
                unsigned n = 0;
                while (ld_acquire_cta_shared(help + 12 + 4 * half) == 0) { if (++n > (SPIN_LIMIT << 4)) __trap(); }
                kseen = half;
            }
            a0 = &g_scores[vb * (KEYS / 4) + lane];
            a1 = &g_stats[(vb / UPP) * UPP + lane];
        }
        H0 = ld_relaxed64(a0);
        H1 = ld_relaxed64(a1);
    };
    asm volatile("bar.sync 2, %0;" ::"n"(32 * (NW + XW + 1)) : "memory");
    epoch = __shfl_sync(~0u, epoch, 0);
    if (hold) { unsigned n = 0; while (ld_acquire_cta_shared(help + 24) < 2) { if (++n > (SPIN_LIMIT << 4)) __trap(); } }
    unsigned (*ctl)[32] = g_ctl[epoch & 1];
    const unsigned tag = epoch + 1;
    unsigned nxt = once ? NU : 0;
    int u = -1;
    unsigned bu = 0, bn = unit_block<CLU>(un);
    bool have = false;
    uint32_t phase = 0;
    unsigned kpend = 0;
    const unsigned zero = gridDim.x >> 24;
    uint32_t Q[16];
    float4 oret = make_float4(0.f, 0.f, 0.f, 0.f);
    while (true) {
        const char* nsrc = block_src(un < NUK ? p.kc : p.vc, bn);
        float4* odst = &g_oacc[(bu / UPP) * 32 + lane];
        unsigned* vdst = &g_vdone[(lane & (NREP - 1)) * NH + bu / (4 * UPP)][0];
        float d[8][4];
        CLK(c1);
        asm volatile("" : "+l"(odst));
        if (u >= NUK) {
#pragma unroll
            for (int j = 0; j < 8; j++) { d[j][0] = d[j][1] = d[j][2] = d[j][3] = 0.f; }
            mbar_wait(bar, phase);
            LAND(NUK + bu);
            uint32_t a[2][8][4];
#pragma unroll
            for (int c = 0; c < 8; c++) ldsm4t(a[0][c], vaddr[c]);
#pragma unroll
            for (int j = 0; j < 8; j++) {
                if (j < 7) {
#pragma unroll
                    for (int c = 0; c < 8; c++) ldsm4t(a[(j + 1) & 1][c], vaddr[c] + (j + 1) * 4096);
                }
#pragma unroll
                for (int c = 0; c < 8; c++) mma16816(d[c], a[j & 1][c], Q[2 * j], Q[2 * j + 1]);
            }
            float o[4];
#pragma unroll
            for (int r = 0; r < 2; r++) {
                o[2 * r] = d[0][2 * r] + d[7][2 * r + 1];
                o[2 * r + 1] = d[0][2 * r + 1] + d[1][2 * r];
#pragma unroll
                for (int k = 1; k < 4; k++) {
                    const int src = (lane & 28) | ((t - k) & 3);
                    o[2 * r] += __shfl_sync(~0u, d[2 * k][2 * r] + d[2 * k - 1][2 * r + 1], src);
                    o[2 * r + 1] += __shfl_sync(~0u, d[2 * k][2 * r + 1] + d[2 * k + 1][2 * r], src);
                }
            }
            oret = atom_add_f4(odst, o[0], o[1], o[2], o[3]);
        } else if (u >= 0) {
#pragma unroll
            for (int j = 0; j < 8; j++) { d[j][0] = d[j][1] = d[j][2] = d[j][3] = 0.f; }
            mbar_wait(bar, phase);
            LAND(bu);
            uint32_t a[2][8][4];
#pragma unroll
            for (int j = 0; j < 8; j++) ldsm4(a[0][j], kaddr[0] + (4 * (j & 3) + 2 * (j >> 2)) * 256);
#pragma unroll
            for (int s = 0; s < 8; s++) {
                if (s < 7) {
#pragma unroll
                    for (int j = 0; j < 8; j++)
                        ldsm4(a[(s + 1) & 1][j], kaddr[(s + 1) & 3] + (4 * (j & 3) + 2 * (j >> 2)) * 256 + ((s + 1) >> 2) * 128);
                }
#pragma unroll
                for (int j = 0; j < 8; j++)
                    mma16816(d[j], a[s & 1][j], Q[(s & 4) * 2 + ((2 * s - 2 * j) & 7)], Q[(s & 4) * 2 + ((2 * s + 1 - 2 * j) & 7)]);
            }
        }
        if (u >= 0) phase ^= 1;
        CLK(c2b);
        if (un < NU && lane == 0) {
            if (!once) nxt = atom_inc(&ctl[C_QUEUE][0]);
            if (u >= 0 || !pre) {
                mbar_expect_tx(bar, TILE_BYTES);
                bulk_load(slot, nsrc, TILE_BYTES, bar, pol);
            }
        }
        const uint32_t tiss = now_ns();
        CLK(c3);
        if ((unsigned)u < (unsigned)NUK) {
            const int j0 = (t - (g >> 1)) & 3;
            float v[4];
#pragma unroll
            for (int q = 0; q < 4; q++) {
                const int jq = (q >> 1) * 4, e = (q & 1) * 2;
                const float x0 = (g & 1) ? d[jq + 0][e + 1] : d[jq + 0][e];
                const float x1 = (g & 1) ? d[jq + 1][e + 1] : d[jq + 1][e];
                const float x2 = (g & 1) ? d[jq + 2][e + 1] : d[jq + 2][e];
                const float x3 = (g & 1) ? d[jq + 3][e + 1] : d[jq + 3][e];
                const float y0 = (j0 & 1) ? x1 : x0, y1 = (j0 & 1) ? x3 : x2;
                v[q] = (j0 & 2) ? y1 : y0;
            }
            const uint32_t r0 = pack_bf16(v[0], v[1]), r1 = pack_bf16(v[2], v[3]);
            const uint32_t s0 = pack_bf16(bf_lo(r0) * SCALE, bf_hi(r0) * SCALE);
            const uint32_t s1 = pack_bf16(bf_lo(r1) * SCALE, bf_hi(r1) * SCALE);
            g_scores[bu * (KEYS / 4) + 4 * g + j0] = make_uint2(s0, s1);
            const float f0 = bf_lo(s0), f1 = bf_hi(s0), f2 = bf_lo(s1), f3 = bf_hi(s1);
            const float m = warp_max(fmaxf(fmaxf(f0, f1), fmaxf(f2, f3)));
            const float l = warp_sum((expsub(f0, m) + expsub(f1, m)) + (expsub(f2, m) + expsub(f3, m)));
            if (lane == 0) g_stats[bu] = make_float2(m, l);
            kpend++;
            if (un / (NUK / 2) != u / (NUK / 2)) {
                __syncwarp();
                if (lane == 0) {
                    red_release_cta_shared(help + 4 * (u / (NUK / 2)), kpend);
                    if (un >= NUK) red_release_cta_shared(help + 8, 1u);
                }
                kpend = 0;
            }
        }
        CLK(c4);
        int unn = NU;
        if (un < NU) {
            unsigned n = 0;
            while (true) {
                if (!have) header(un, bn);
                if (un >= NUK || __all_sync(~0u, (uint32_t)(H0 >> 32) == tag && (uint32_t)(H1 >> 32) == tag)) break;
                if (++n > SPIN_LIMIT) __trap();
                have = false;
            }
            if (un >= NUK) {
                const uint32_t s0 = (uint32_t)H0, s1 = (uint32_t)(H0 >> 32);
                const float mu = __uint_as_float((uint32_t)H1);
                const float m = warp_max(mu);
                const float l = warp_sum(__uint_as_float((uint32_t)(H1 >> 32)) * expsub(mu, m));
                const float inv = 1.0f / l;
                const uint32_t w0 = pack_bf16(expsub(bf_lo(s0), m) * inv, expsub(bf_hi(s0), m) * inv);
                const uint32_t w1 = pack_bf16(expsub(bf_lo(s1), m) * inv, expsub(bf_hi(s1), m) * inv);
#pragma unroll
                for (int j = 0; j < 8; j++) {
                    Q[2 * j] = __shfl_sync(~0u, w0, 4 * j + t) & vmask;
                    Q[2 * j + 1] = __shfl_sync(~0u, w1, 4 * j + t) & vmask;
                }
            } else {
#pragma unroll
                for (int j = 0; j < 8; j++) {
                    const int src = (((j + g) & 7) << 2) + t;
                    Q[j] = __shfl_sync(~0u, (uint32_t)H0, src);
                    Q[8 + j] = __shfl_sync(~0u, (uint32_t)H1, src);
                }
            }
            unn = nstatic + (int)__shfl_sync(~0u, nxt, 0);
            if (CLU && !once && unn >= NU && lane == 0)
                asm volatile("st.relaxed.cta.shared::cta.u32 [%0], %1;" ::"r"(help + 28), "r"((tiss + (FJ - (unn - NU)) * 10) | 1u) : "memory");
        }
        if (u >= NUK && lane < NREP)
            red_add_u32(vdst,
                        1u + ((__float_as_uint(oret.x) | __float_as_uint(oret.y) | __float_as_uint(oret.z) | __float_as_uint(oret.w)) & zero));
        if (un >= NU) break;
        bu = bn;
        have = !(un < NUK && unn >= NUK && !(un >= NUK / 2 && unn < NUK + NUK / 2));
        bn = unit_block<CLU>(unn);
        if (have) header(unn, bn);
        u = un;
        un = unn;
    }
}

__device__ __forceinline__ void k_helper(uint32_t help, unsigned epoch) {
    if ((threadIdx.x & 31) != 0) return;
    unsigned (*ctl)[32] = g_ctl[epoch & 1];
    unsigned sent0 = 0, sent1 = 0, n = 0;
    int seen = 0;
    bool fin = false;
    while (!fin || seen < 2) {
        if (!fin) {
            fin = ld_acquire_cta_shared(help + 8) == NW + XW;
            const unsigned c0 = ld_acquire_cta_shared(help), c1 = ld_acquire_cta_shared(help + 4);
            if (c0 != sent0 || c1 != sent1) {
                fence_gpu();
                if (c0 != sent0) red_add_u32(&ctl[C_KDONE][0], c0 - sent0);
                if (c1 != sent1) red_add_u32(&ctl[C_KDONE + 1][0], c1 - sent1);
                sent0 = c0; sent1 = c1;
            }
        }
        if (seen < 2 && ld_acquire(&ctl[C_KDONE + seen][0]) >= NUK / 2) {
            st_release_cta_shared(help + 12 + 4 * seen, 1u);
            seen++;
        } else {
            __nanosleep(300);
        }
        if (++n > SPIN_LIMIT) __trap();
    }
}

__device__ __forceinline__ void v_poller(uint32_t sbase, int f, int w) {
    const int lane = threadIdx.x & 31;
    const unsigned (*cp)[32] = &g_vdone[((f * NPOLL + w) % NREP) * NH];
    unsigned n = 0;
    while (ld_acquire_cta_shared(sbase + M_HELP + 12) == 0) { __nanosleep(1000); if (++n > SPIN_LIMIT) __trap(); }
    int h = 0;
    bool fast = false;
    while (h < NH) {
        const unsigned r = __ballot_sync(~0u, ld_acquire(&cp[min(h + (lane & 3), NH - 1)][0]) >= 4 * UPP) & 15u;
        if (r & 1) {
            h = min(NH, h + __ffs(~r) - 1);
            __syncwarp();
            if (lane == 0) asm volatile("red.release.cta.shared::cta.max.u32 [%0], %1;" ::"r"(sbase + M_HELP + 20), "r"(h) : "memory");
        }
        if (h < NH - 4) {
            __nanosleep(h ? 300 : 1000);
        } else if (!fast) {
            fast = true;
            const long long t0 = clock64();
            while (clock64() - t0 < w * PGAP) {}
        }
        if (++n > SPIN_LIMIT) __trap();
    }
}
__device__ __forceinline__ void finisher(const Params& p, uint32_t sbase, int f) {
    const int lane = threadIdx.x & 31;
    {
        const char* wg = reinterpret_cast<const char*>(p.wo);
        const uint32_t dst = sbase + 4 * SLOT + (16 * (lane & 7) + (lane >> 3)) * 16;
#pragma unroll 1
        for (int h = -FPF - 4; h < NH; h++) {
            if (lane == 0 && (unsigned)(h + FPF) < (unsigned)NH) l2_prefetch(wg + (size_t)(h + FPF) * 147456 + f * 2048, 2048);
            if (h >= 0) {
#pragma unroll
                for (int r = 0; r < 4; r++)
                    asm volatile("cp.async.cg.shared.global [%0], [%1], 16;" ::"r"(dst + h * 2048 + ((r & 1) * 4 + (r >> 1) * 8) * 16),
                                 "l"(wg + (size_t)(h * 128 + r * 32 + lane) * (DM * 2) + f * 16) : "memory");
            }
            __nanosleep(FSLEEP);
        }
        asm volatile("cp.async.wait_all;" ::: "memory");
        __syncwarp();
    }
    TS(11);
    const float4* vec = g_oacc + ((lane >> 2) & 3) * 32 + (lane >> 4) * 16 + (lane & 3);
    float acc[2][2][4];
#pragma unroll
    for (int i = 0; i < 16; i++) acc[i >> 3][(i >> 2) & 1][i & 3] = 0.f;
    uint32_t* outp = reinterpret_cast<uint32_t*>(p.out + (lane >> 2) * (2 * DM) + f * 8 + (lane & 3) * 2);
    uint32_t wa = sbase + 4 * SLOT + lane * 16;
    auto project = [&](const float4 (&x)[4], const uint32_t (&w)[4][4]) {
#pragma unroll
        for (int s = 0; s < 4; s++) {
            const uint32_t a[4] = {pack_bf16(x[s].x, x[s].y), 0u, pack_bf16(x[s].z, x[s].w), 0u};
            mma16816(acc[0][s & 1], a, w[s >> 1][(s & 1) * 2], w[s >> 1][(s & 1) * 2 + 1]);
            mma16816(acc[1][s & 1], a, w[2 + (s >> 1)][(s & 1) * 2], w[2 + (s >> 1)][(s & 1) * 2 + 1]);
        }
    };
    int h = 0;
    unsigned n = 0;
    while (h < NH) {
        uint32_t w[4][4];
#pragma unroll
        for (int q = 0; q < 4; q++) ldsm4t(w[q], wa + q * 512);
        int ready;
        while ((ready = ld_acquire_cta_shared(sbase + M_HELP + 20)) <= h) {
            if (h < NH - 3) __nanosleep(100);
            if (++n > (SPIN_LIMIT << 4)) __trap();
        }
        float4 x[4], y[4];
#pragma unroll
        for (int s = 0; s < 4; s++) x[s] = ld_relaxed16(vec + s * 4);
        const bool two = ready > h + 1;
        if (two) {
#pragma unroll
            for (int s = 0; s < 4; s++) y[s] = ld_relaxed16(vec + 128 + s * 4);
        }
        project(x, w);
        if (two) {
#pragma unroll
            for (int q = 0; q < 4; q++) ldsm4t(w[q], wa + 2048 + q * 512);
            project(y, w);
        }
        const int nr = two ? 2 : 1;
        h += nr;
        vec += nr * 128;
        wa += nr * 2048;
        const float o0 = acc[0][0][0] + acc[0][1][0] + __shfl_down_sync(~0u, acc[1][0][0] + acc[1][1][0], 16);
        const float o1 = acc[0][0][1] + acc[0][1][1] + __shfl_down_sync(~0u, acc[1][0][1] + acc[1][1][1], 16);
        asm volatile("{\n.reg .pred p;\nsetp.ne.u32 p, %2, 0;\n@p st.global.u32 [%0], %1;\n}" ::"l"(outp), "r"(pack_bf16(o0, o1)),
                     "r"((uint32_t)(lane < 16 && h == NH)) : "memory");
    }
}

__device__ __forceinline__ void out_fetch(uint32_t sbase, int step, int h) {
    const int lane = threadIdx.x & 31, g = lane >> 2;
    float4 x[4];
#pragma unroll
    for (int b = 0; b < 4; b++) x[b] = ld_relaxed16(&g_oacc[(h * 4 + ((b + g) & 3)) * 32 + lane]);
#pragma unroll
    for (int b = 0; b < 4; b++) {
        const uint32_t a = sbase + F_X + step * FXP + g * 128 + ((b + g) & 3) * 16 + (lane & 3) * 4;
        asm volatile("st.shared.u32 [%0], %1;\nst.shared.u32 [%0 + 64], %2;" ::"r"(a), "r"(pack_bf16(x[b].x, x[b].y)), "r"(pack_bf16(x[b].z, x[b].w)) : "memory");
    }
    asm volatile("fence.proxy.async.shared::cta;" ::: "memory");
}
__device__ __forceinline__ void out_early(uint32_t sbase, int c, int rank, unsigned tag) {
    const int lane = threadIdx.x & 31;
    if (lane < 10) {
        mbar_init(sbase + F_BAR + 16 + lane * 8, lane < 7 ? 1 : lane == 7 ? 2 : 4);
        if (lane < 8) mbar_expect_tx(sbase + F_BAR + 16 + lane * 8, 16384);
    }
    asm volatile("fence.mbarrier_init.release.cluster;" ::: "memory");
    unsigned n = 0;
#pragma unroll 1
    for (int i = 0; i < 3; i++) {
        while (ld_acquire(&g_vdone[(c & (NREP - 1)) * NH + 8 * i + rank][0]) < 4 * UPP) { __nanosleep(500); if (++n > SPIN_LIMIT) __trap(); }
        out_fetch(sbase, 4 + i, 8 * i + rank);
#pragma unroll 1
        for (int j = 0; j < 16 && i == 0;) {
            const ulonglong2 v = ld_tagged2(&g_ctx[((j >> 2) * 8 + rank) * 128 + (j & 3) * 32 + lane]);
            if (__all_sync(~0u, (unsigned)(v.x >> 32) == tag && (unsigned)(v.y >> 32) == tag)) {
                asm volatile("st.shared.v2.u32 [%0], {%1,%2};" ::"r"(sbase + F_X + (j >> 2) * FXP + ((j & 3) * 32 + lane) * 8), "r"((uint32_t)v.x), "r"((uint32_t)v.y) : "memory");
                j++;
            } else {
                __nanosleep(500);
                if (++n > SPIN_LIMIT) __trap();
            }
        }
    }
    __syncwarp();
    if (lane == 0) st_release_cta_shared(sbase + M_HELP + 32, 1u);
}
__device__ __forceinline__ void out_late(uint32_t sbase, int c, int rank) {
    unsigned n = 0;
    while (ld_acquire_cta_shared(sbase + M_HELP + 32) == 0) { if (++n > (SPIN_LIMIT << 4)) __trap(); }
    while (ld_acquire(&g_vdone[(c & (NREP - 1)) * NH + 24 + rank][0]) < 4 * UPP) { if (++n > SPIN_LIMIT) __trap(); }
    TS(12);
    out_fetch(sbase, 7, 24 + rank);
    __syncwarp();
    if ((threadIdx.x & 31) == 0) asm volatile("mbarrier.arrive.shared::cta.b64 _, [%0];" ::"r"(sbase + F_BAR + 72) : "memory");
    TS(13);
}
__device__ __forceinline__ void out_project(uint32_t sbase, int rank, int w) {
    const int lane = threadIdx.x & 31, g = lane >> 2, t = lane & 3;
    unsigned n = 0;
    while (ld_acquire_cta_shared(sbase + M_HELP + 32) == 0) { __nanosleep(500); if (++n > SPIN_LIMIT) __trap(); }
    asm volatile("barrier.cluster.wait.acquire.aligned;" ::: "memory");
    uint32_t rdst = mapa(sbase + F_RECV + rank * 128 + (g & 3) * 32 + t * 16, 2 * w + (g >> 2)), rbar = mapa(sbase + F_BAR, 2 * w + (g >> 2));
    while (ld_acquire_cta_shared(sbase + M_HELP + 28) == 0) { __nanosleep(200); if (++n > SPIN_LIMIT) __trap(); }
    const uint32_t da = (1u << 16) | (((sbase + F_W) & 0x3ffff) >> 4), db = (4u << 16) | (((sbase + F_X) & 0x3ffff) >> 4);
    float d[4] = {0.f, 0.f, 0.f, 0.f};
#pragma unroll
    for (int i = 0; i < 8; i++) {
        mbar_spin(sbase + F_BAR + 16 + i * 8);
        wgmma_tile(d, da + (i % 6) * 1024, db + i * (FXP / 16), i & 3);
        if (i < 2 || (i & 3) == 3) asm volatile("wgmma.wait_group.sync.aligned 0;" : "+f"(d[0]), "+f"(d[1]), "+f"(d[2]), "+f"(d[3])::"memory");
        if (i < 2) {
            asm volatile("{\n.reg .pred p;\nsetp.eq.u32 p, %1, 0;\n@p mbarrier.arrive.shared::cta.b64 _, [%0];\n}"
                         ::"r"(sbase + F_BAR + 80 + i * 8), "r"(lane) : "memory");
        } else if ((i & 3) == 3) {
            if (t < 2)
                asm volatile("st.async.weak.shared::cluster.mbarrier::complete_tx::bytes.v4.f32 [%0], {%1,%2,%3,%4}, [%5];"
                             ::"r"(rdst), "f"(d[0]), "f"(d[1]), "f"(d[2]), "f"(d[3]), "r"(rbar) : "memory");
            __syncwarp();
            rdst += 1024;
            rbar += 8;
            asm volatile("" : "+r"(rdst), "+r"(rbar));
        }
    }
}
__device__ __forceinline__ void out_issue_sum(const Params& p, uint32_t sbase, int c, int rank, uint64_t pol) {
    const int lane = threadIdx.x & 31;
    if (lane == 0) {
        unsigned n = 0;
        while (ld_acquire_cta_shared(sbase + M_HELP + 32) == 0) { __nanosleep(500); if (++n > SPIN_LIMIT) __trap(); }
        asm volatile("prefetch.tensormap [%0];" ::"l"(&p.tm_wf) : "memory");
        asm volatile("prefetch.tensormap [%0];" ::"l"(&p.tm_wl) : "memory");
        uint32_t t0;
        while ((t0 = ld_acquire_cta_shared(sbase + M_HELP + 28)) == 0) { __nanosleep(100); if (++n > SPIN_LIMIT) __trap(); }
#pragma unroll 1
        for (int i = 0; i < 8; i++) {
            const int h = (i & 3) * 8 + rank;
            if (i >= 6) mbar_wait(sbase + F_BAR + 32 + i * 8, 0);
            while ((int)(now_ns() - t0) < 0) {}
            if (i == 0) TS(16);
            tma3d(sbase + F_W + (i < 6 ? i : i - 6) * 16384, i < 4 ? &p.tm_wf : &p.tm_wl, i < 4 ? 0 : c * 64, i < 4 ? h * 128 : h * 16,
                  i < 4 ? c : 0, sbase + F_BAR + 16 + i * 8, pol);
            t0 += FP;
        }
        TS(17);
    }
    __syncwarp();
    __nv_bfloat16* dst = p.out + (((lane >> 1) & 2) + (lane & 1)) * (2 * DM) + DM + c * 64 + (rank >> 1) * 16 + (lane & 2) * 4 +
                         (rank & 1) * 4 + (lane >> 3);
    uint32_t src = sbase + F_RECV + lane * 4;
#pragma unroll 1
    for (int r = 0; r < 2; r++) {
        asm volatile("" : "+l"(dst), "+r"(src));
        mbar_spin_cluster(sbase + F_BAR + r * 8);
        float x[8];
#pragma unroll
        for (int i = 0; i < 8; i++) asm volatile("ld.shared.f32 %0, [%1];" : "=f"(x[i]) : "r"(src + i * 128) : "memory");
        const float v = ((x[0] + x[1]) + (x[2] + x[3])) + ((x[4] + x[5]) + (x[6] + x[7]));
        asm volatile("st.global.u16 [%0], %1;" ::"l"(dst), "h"((unsigned short)pack_bf16(v, 0.f)) : "memory");
        TS(14 + r);
        dst -= DM;
        src += 1024;
    }
}

constexpr int BS_WUK = 5, BS_Q = 9, BS_CKV = 11, BS_PART = 27, BS_WUV = 29, BS_END = 33;

__device__ __noinline__ void b_issue(const Params& p, int n, int bi, uint32_t sbase, uint64_t pol) {
    if (n >= BS_END || (n >= BS_Q && n < BS_CKV) || (n >= BS_PART && n < BS_WUV)) return;
    const uint32_t bar = sbase + M_BAR + (NSLOT + n % BRING) * 8;
    const CUtensorMap* tm;
    int row, panel = 2 * bi;
    if (n < BS_WUK) { tm = &p.tm_wq; row = n * 128; }
    else if (n < BS_Q) { tm = &p.tm_wuk; row = (n - BS_WUK) * 128; }
    else if (n < BS_PART) {
        tm = &p.tm_ckv; panel = 0;
        row = (bi >> 3) * SK + ((n - BS_CKV) * 8 + (bi & 7)) * 32;
    }
    else { tm = &p.tm_wuv; row = (n - BS_WUV) * 128; }
    mbar_expect_tx(bar, n == 0 ? 32768 + 4 * 1152 : 32768);
    tma3d(sbase + (n % BRING) * SLOT, tm, 0, row, panel, bar, pol);
}
__device__ __forceinline__ void b_issue_xchg(int n, const void* src, uint32_t sbase, uint64_t pol) {
    asm volatile("fence.proxy.async;" ::: "memory");
#pragma unroll
    for (int i = 0; i < 2; i++) {
        const uint32_t bar = sbase + M_BAR + (NSLOT + (n + i) % BRING) * 8;
        mbar_expect_tx(bar, 32768);
        bulk_load(sbase + ((n + i) % BRING) * SLOT, reinterpret_cast<const char*>(src) + i * 32768, 32768, bar, pol);
    }
}
__device__ __forceinline__ void b_wait(int n, uint32_t sbase) {
    mbar_wait(sbase + M_BAR + (NSLOT + n % BRING) * 8, (n / BRING) & 1);
}

__device__ __noinline__ void b_gemm(const Params& p, uint32_t sbase, int n0, int n1, int ktot, uint32_t xh, uint32_t xl, int pitch,
                                    int bi, uint64_t pol) {
    const int tid = threadIdx.x, warp = tid >> 5, lane = tid & 31, g = lane >> 2, t = lane & 3;
    const uint32_t woff = (warp >> 2) * 16384 + (lane & 15) * 128 + ((((warp & 3) * 2 + (lane >> 4)) ^ (lane & 7)) * 16);
    const uint32_t xoff = (g & 3) * pitch + t * 4;
    float acc[2][4];
#pragma unroll
    for (int i = 0; i < 8; i++) acc[i >> 2][i & 3] = 0.f;
#pragma unroll 1
    for (int n = n0; n < n1; n++) {
        b_wait(n, sbase);
        const uint32_t slot = sbase + (n % BRING) * SLOT + woff;
        const int k0 = (n - n0) * 128;
        const int ns = min(8, (ktot - k0) >> 4);
#pragma unroll 2
        for (int s = 0; s < ns; s++) {
            uint32_t a[4], w[4];
            const uint32_t xo = xoff + (k0 + 16 * s) * 2;
            a[0] = lds32(xh + xo); a[2] = lds32(xh + xo + 16);
            a[1] = xl ? lds32(xl + xo) : 0u; a[3] = xl ? lds32(xl + xo + 16) : 0u;
            ldsm4t(w, slot + s * 2048);
            mma16816(acc[0], a, w[0], w[1]);
            mma16816(acc[1], a, w[2], w[3]);
        }
        __syncthreads();
        if (tid == 0) b_issue(p, n + BD, bi, sbase, pol);
    }
    if (g < 4) {
#pragma unroll
        for (int j = 0; j < 2; j++)
            asm volatile("st.shared.u32 [%0], %1;" ::"r"(sbase + M_QB + g * QP + (warp * 16 + j * 8 + t * 2) * 2),
                         "r"(pack_bf16(acc[j][0] + acc[j][2], acc[j][1] + acc[j][3])) : "memory");
    }
    __syncthreads();
}

__device__ __forceinline__ void b_exchange(unsigned* c, int n, const void* src, uint32_t sbase, uint64_t pol) {
    TS(n == BS_Q ? 24 : 28);
    __syncthreads();
    if (threadIdx.x == 0) {
        TS(n == BS_Q ? 25 : 29);
        fence_gpu();
        TS(n == BS_Q ? 26 : 30);
        red_add_u32(c, 1u);
        wait_count(c, NBCTA);
        TS(n == BS_Q ? 27 : 31);
        b_issue_xchg(n, src, sbase, pol);
    }
}

template <bool CLU>
__device__ __noinline__ void b_chain(const Params& p, char* smem, uint32_t sbase, int bi, unsigned epoch, uint64_t pol) {
    const int tid = threadIdx.x, warp = tid >> 5, lane = tid & 31, g = lane >> 2, t = lane & 3;
    unsigned (*ctl)[32] = g_ctl[epoch & 1];
    float* red = reinterpret_cast<float*>(smem + 5 * SLOT);
    __syncthreads();
    b_gemm(p, sbase, 0, BS_WUK, DM, sbase + M_XB, 0, XP, bi, pol);
    TS(6);
    {
        uint32_t Q[16];
#pragma unroll
        for (int c = 0; c < 16; c++) Q[c] = lds32(sbase + M_QB + (g & 3) * QP + c * 16 + t * 4);
        float* qa = reinterpret_cast<float*>(smem + M_QA);
#pragma unroll 1
        for (int n = BS_WUK; n < BS_Q; n++) {
            b_wait(n, sbase);
            const uint32_t base = sbase + (n % BRING) * SLOT + (warp * 16 + (lane & 15)) * 128;
            float d[2][4];
#pragma unroll
            for (int i = 0; i < 8; i++) d[i >> 2][i & 3] = 0.f;
#pragma unroll
            for (int s = 0; s < 8; s++) {
                uint32_t a[4];
                ldsm4(a, base + (s >> 2) * 16384 + (((2 * (s & 3) + (lane >> 4)) ^ (lane & 7)) * 16));
                mma16816(d[s & 1], a, Q[2 * s], Q[2 * s + 1]);
            }
            const int c = (n - BS_WUK) * 128 + warp * 16 + g + 8 * (t >> 1);
            qa[(2 * (t & 1)) * 512 + c] = (t & 2) ? d[0][2] + d[1][2] : d[0][0] + d[1][0];
            qa[(2 * (t & 1) + 1) * 512 + c] = (t & 2) ? d[0][3] + d[1][3] : d[0][1] + d[1][1];
            __syncthreads();
            if (tid == 0) b_issue(p, n + BD, bi, sbase, pol);
        }
#pragma unroll 1
        for (int r = 0; r < 2; r++) {
            const int id = tid + r * 256;
            const int b = id >> 7, c0 = ((id >> 2) & 31) * 16 + (id & 3) * 2;
            const float2 u0 = *reinterpret_cast<const float2*>(qa + b * 512 + c0);
            const float2 u1 = *reinterpret_cast<const float2*>(qa + b * 512 + c0 + 8);
            const uint32_t h0 = pack_bf16(u0.x, u0.y), h1 = pack_bf16(u1.x, u1.y);
            const uint32_t l0 = pack_bf16(u0.x - bf_lo(h0), u0.y - bf_hi(h0)), l1 = pack_bf16(u1.x - bf_lo(h1), u1.y - bf_hi(h1));
            g_qabs[((id >> 2) * 4 + (bi >> 3)) * 32 + (bi & 7) * 4 + (id & 3)] = make_uint4(h0, l0, h1, l1);
        }
    }
    b_exchange(&ctl[C_BBAR][0], BS_Q, &g_qabs[(bi >> 3) * 4096], sbase, pol);
    {
        uint32_t qf[4][4][4];
        b_wait(BS_Q + (warp >> 2), sbase);
        TS(7);
        {
            const uint4* qs = reinterpret_cast<const uint4*>(smem + ((BS_Q + (warp >> 2)) % BRING) * SLOT) + (warp & 3) * 512 + lane;
#pragma unroll
            for (int s = 0; s < 4; s++)
#pragma unroll
                for (int i = 0; i < 4; i++) {
                    const uint4 v = qs[(s * 4 + i) * 32];
                    qf[i][s][0] = v.x; qf[i][s][1] = v.y; qf[i][s][2] = v.z; qf[i][s][3] = v.w;
                }
        }
        __syncthreads();
        if (tid == 0) { b_issue(p, BS_Q + BD, bi, sbase, pol); b_issue(p, BS_Q + 1 + BD, bi, sbase, pol); }
        float acc[2][8][4];
#pragma unroll
        for (int i = 0; i < 2; i++)
#pragma unroll
            for (int j = 0; j < 8; j++) { acc[i][j][0] = acc[i][j][1] = acc[i][j][2] = acc[i][j][3] = 0.f; }
        float mrun = -INFINITY, lrun = 0.f;
        const int head = tid >> 3, kq = tid & 7;
        float* alpha = reinterpret_cast<float*>(smem + M_ALPHA);
        for (int n = BS_CKV; n < BS_PART; n++) {
            b_wait(n, sbase);
            const uint32_t slot = sbase + (n % BRING) * SLOT;
            float sc[4][4][4];
#pragma unroll
            for (int i = 0; i < 4; i++)
#pragma unroll
                for (int j = 0; j < 4; j++) { sc[i][j][0] = sc[i][j][1] = sc[i][j][2] = sc[i][j][3] = 0.f; }
#pragma unroll
            for (int j = 0; j < 4; j++)
#pragma unroll
                for (int sp = 0; sp < 2; sp++) {
                    uint32_t bf[4];
                    ldsm4(bf, slot + warp * 4096 + (8 * j + (lane & 7)) * 128 + (((4 * sp + (lane >> 3)) ^ (lane & 7)) * 16));
#pragma unroll
                    for (int i = 0; i < 4; i++) {
                        mma16816(sc[i][j], qf[i][2 * sp], bf[0], bf[1]);
                        mma16816(sc[i][j], qf[i][2 * sp + 1], bf[2], bf[3]);
                    }
                }
#pragma unroll
            for (int i = 0; i < 4; i++)
#pragma unroll
                for (int j = 0; j < 4; j++)
                    *reinterpret_cast<float2*>(red + warp * 1024 + (8 * i + g) * 32 + ((8 * j) ^ (8 * (g & 3))) + 2 * t) =
                        make_float2(sc[i][j][0] + sc[i][j][2], sc[i][j][1] + sc[i][j][3]);
            __syncthreads();
            if (tid == 0 && n > BS_CKV) b_issue(p, n - 1 + BD, bi, sbase, pol);
            {
                float4 s = make_float4(0.f, 0.f, 0.f, 0.f);
#pragma unroll
                for (int w = 0; w < 8; w++) {
                    const float4 v = *reinterpret_cast<const float4*>(red + w * 1024 + head * 32 + ((4 * kq) ^ (8 * (head & 3))));
                    s.x += v.x; s.y += v.y; s.z += v.z; s.w += v.w;
                }
                const uint32_t r0 = pack_bf16(s.x, s.y), r1 = pack_bf16(s.z, s.w);
                const uint32_t s0 = pack_bf16(bf_lo(r0) * SCALE, bf_hi(r0) * SCALE);
                const uint32_t s1 = pack_bf16(bf_lo(r1) * SCALE, bf_hi(r1) * SCALE);
                const float f0 = bf_lo(s0), f1 = bf_hi(s0), f2 = bf_lo(s1), f3 = bf_hi(s1);
                float mx = fmaxf(fmaxf(f0, f1), fmaxf(f2, f3));
                mx = fmaxf(mx, __shfl_xor_sync(~0u, mx, 1));
                mx = fmaxf(mx, __shfl_xor_sync(~0u, mx, 2));
                mx = fmaxf(mx, __shfl_xor_sync(~0u, mx, 4));
                const float mnew = fmaxf(mrun, mx);
                const float al = expsub(mrun, mnew);
                const float p0 = expsub(f0, mnew), p1 = expsub(f1, mnew), p2 = expsub(f2, mnew), p3 = expsub(f3, mnew);
                lrun = lrun * al + ((p0 + p1) + (p2 + p3));
                mrun = mnew;
                *reinterpret_cast<uint2*>(smem + M_P + head * 80 + kq * 8) = make_uint2(pack_bf16(p0, p1), pack_bf16(p2, p3));
                if (kq == 0) alpha[head] = al;
            }
            __syncthreads();
            {
                uint32_t pf[2][2][4];
#pragma unroll
                for (int i = 0; i < 2; i++)
#pragma unroll
                    for (int ks = 0; ks < 2; ks++)
                        ldsm4(pf[i][ks], sbase + M_P + (16 * i + (lane & 15)) * 80 + (16 * ks + 8 * (lane >> 4)) * 2);
#pragma unroll
                for (int i = 0; i < 2; i++) {
                    const float a0 = alpha[16 * i + g], a1 = alpha[16 * i + 8 + g];
#pragma unroll
                    for (int j = 0; j < 8; j++) { acc[i][j][0] *= a0; acc[i][j][1] *= a0; acc[i][j][2] *= a1; acc[i][j][3] *= a1; }
                }
#pragma unroll
                for (int j = 0; j < 8; j++) {
                    uint32_t bf[4];
                    ldsm4t(bf, slot + warp * 4096 + lane * 128 + ((j ^ (lane & 7)) * 16));
#pragma unroll
                    for (int i = 0; i < 2; i++) {
                        mma16816(acc[i][j], pf[i][0], bf[0], bf[1]);
                        mma16816(acc[i][j], pf[i][1], bf[2], bf[3]);
                    }
                }
            }
        }
        __syncthreads();
        if (tid == 0) b_issue(p, BS_PART - 1 + BD, bi, sbase, pol);
        lrun += __shfl_xor_sync(~0u, lrun, 1);
        lrun += __shfl_xor_sync(~0u, lrun, 2);
        lrun += __shfl_xor_sync(~0u, lrun, 4);
        if (kq == 0) g_bml[head * NBCTA + bi] = make_float2(mrun, lrun);
#pragma unroll
        for (int i = 0; i < 2; i++)
#pragma unroll
            for (int j = 0; j < 8; j++) {
                g_bpart[((16 * i + g) * NBCTA + bi) * 256 + warp * 32 + j * 4 + t] = make_float2(acc[i][j][0], acc[i][j][1]);
                g_bpart[((16 * i + 8 + g) * NBCTA + bi) * 256 + warp * 32 + j * 4 + t] = make_float2(acc[i][j][2], acc[i][j][3]);
            }
    }
#pragma unroll 1
    for (int i = tid; i < NH * 36 && !(CLU); i += 256) g_outb[bi * NH * 36 + i] = make_uint4(0u, epoch, 0u, epoch);
    b_exchange(&ctl[C_BBAR + 1][0], BS_PART, &g_bpart[bi * NBCTA * 256], sbase, pol);
    {
        float* omega = reinterpret_cast<float*>(smem + M_OMEGA);
        if (warp == 0) {
            __syncwarp();
            const uint2 ml = ld_relaxed8(&g_bml[bi * NBCTA + lane]);
            const float ms = __uint_as_float(ml.x);
            float m = ms;
            m = fmaxf(m, __shfl_xor_sync(~0u, m, 1));
            m = fmaxf(m, __shfl_xor_sync(~0u, m, 2));
            m = fmaxf(m, __shfl_xor_sync(~0u, m, 4));
            const float w = expsub(ms, m);
            float l = w * __uint_as_float(ml.y);
            l += __shfl_xor_sync(~0u, l, 1);
            l += __shfl_xor_sync(~0u, l, 2);
            l += __shfl_xor_sync(~0u, l, 4);
            omega[lane] = w / l;
        }
        __syncthreads();
        b_wait(BS_PART, sbase);
        b_wait(BS_PART + 1, sbase);
#pragma unroll 1
        for (int b = 0; b < 4; b++) {
            const float2* ps = reinterpret_cast<const float2*>(smem + ((BS_PART + (b >> 1)) % BRING) * SLOT) + (b & 1) * 2048 + tid;
            float c0 = 0.f, c1 = 0.f;
#pragma unroll
            for (int s = 0; s < 8; s++) {
                const float w = omega[b * 8 + s];
                const float2 v = ps[s * 256];
                c0 = fmaf(w, v.x, c0);
                c1 = fmaf(w, v.y, c1);
            }
            const uint32_t hi = pack_bf16(c0, c1);
            *reinterpret_cast<uint32_t*>(smem + M_CH + b * CP + tid * 4) = hi;
            *reinterpret_cast<uint32_t*>(smem + M_CL + b * CP + tid * 4) = pack_bf16(c0 - bf_lo(hi), c1 - bf_hi(hi));
        }
        __syncthreads();
        if (tid == 0) { b_issue(p, BS_PART + BD, bi, sbase, pol); b_issue(p, BS_PART + 1 + BD, bi, sbase, pol); }
    }
    b_gemm(p, sbase, BS_WUV, BS_END, 512, sbase + M_CH, sbase + M_CL, CP, bi, pol);
    TS(12);
    if (CLU) {
        if (tid < 128) {
            const uint32_t xo = sbase + M_QB + ((tid >> 1) & 3) * QP + (tid >> 3) * 16 + (tid & 1) * 8;
            st_tagged2(&g_ctx[bi * 128 + tid], __uint_as_float(lds32(xo)), __uint_as_float(lds32(xo + 4)), epoch + 1);
        }
        return;
    }
    if (tid == 0) {
#pragma unroll 1
        for (int i = 0; i < 4; i++) {
            mbar_expect_tx(sbase + M_BAR + i * 8, 36864);
            tma3d(sbase + i * 36864, &p.tm_wo, 0, bi * 128 + i * 32, 0, sbase + M_BAR + i * 8, pol);
        }
    }
    TS(8);
    {
        float acc[9][4];
#pragma unroll
        for (int j = 0; j < 9; j++) { acc[j][0] = acc[j][1] = acc[j][2] = acc[j][3] = 0.f; }
#pragma unroll 1
        for (int i = 0; i < 4; i++) {
            const uint32_t xo = sbase + M_QB + (g & 3) * QP + i * 64 + t * 4;
            const uint32_t a0[4] = {lds32(xo), 0u, lds32(xo + 16), 0u}, a1[4] = {lds32(xo + 32), 0u, lds32(xo + 48), 0u};
            mbar_wait(sbase + M_BAR + i * 8, 0);
#pragma unroll
            for (int j = 0; j < 9; j++) {
                const int nt = warp * 9 + j;
                uint32_t w[4];
                ldsm4t(w, sbase + i * 36864 + (nt >> 3) * 4096 + lane * 128 + (((nt & 7) ^ (lane & 7)) * 16));
                mma16816(acc[j], a0, w[0], w[1]);
                mma16816(acc[j], a1, w[2], w[3]);
            }
        }
        if (g < 4) {
#pragma unroll
            for (int j = 0; j < 9; j++) {
                const int c2 = (warp * 9 + j) * 4 + t;
                st_tagged2(&g_outb[((c2 / 9) * NH + bi) * 36 + g * 9 + c2 % 9], acc[j][0], acc[j][1], epoch + 1);
            }
        }
    }
    TS(9);
    {
        const uint4* src = g_outb + (bi * NH + (tid >> 3)) * 36 + (tid & 7);
        float2* part = reinterpret_cast<float2*>(red);
        unsigned n = 0;
        while (true) {
            ulonglong2 v[5];
            bool ok = true;
#pragma unroll
            for (int i = 0; i < 5; i++)
                if (i < 4 || (tid & 7) < 4) v[i] = ld_tagged2(src + i * 8);
#pragma unroll
            for (int i = 0; i < 5; i++)
                if (i < 4 || (tid & 7) < 4) {
                    ok = ok && (unsigned)(v[i].x >> 32) == epoch + 1 && (unsigned)(v[i].y >> 32) == epoch + 1;
                    part[(tid >> 3) * 36 + (tid & 7) + i * 8] = make_float2(__uint_as_float((unsigned)v[i].x), __uint_as_float((unsigned)v[i].y));
                }
            if (ok) break;
            __nanosleep(400);
            if (++n > SPIN_LIMIT) __trap();
        }
        __syncthreads();
        if (tid < 36) {
            float s0 = 0.f, s1 = 0.f;
#pragma unroll 8
            for (int h = 0; h < NH; h++) { const float2 v = part[h * 36 + tid]; s0 += v.x; s1 += v.y; }
            *reinterpret_cast<uint32_t*>(p.out + (tid / 9) * 2 * DM + DM + bi * 18 + (tid % 9) * 2) = pack_bf16(s0, s1);
        }
    }
    TS(10);
}

template <bool CLU>
__global__ void __launch_bounds__(256, 1) fused_decode_kernel(const __grid_constant__ Params p) {
    extern __shared__ __align__(1024) char smem_raw[];
    const uint32_t sbase = (smem_u32(smem_raw) + 1023u) & ~1023u;
    char* smem = smem_raw + (sbase - smem_u32(smem_raw));
    const int tid = threadIdx.x, warp = tid >> 5, lane = tid & 31;
    const int blk = blockIdx.x;
    const bool isB = CLU ? blk < NBCTA : (blk & 3) == 0 && (blk >> 2) < NBCTA;
    const int bi = CLU ? blk : blk >> 2;
    const int nb = CLU ? blk - NBCTA : blk - min(NBCTA, (blk + 3) >> 2);
    const int nnb = gridDim.x - NBCTA;
    const int nstatic = nnb * (NW + XW);
    uint64_t pol;
    asm volatile("createpolicy.fractional.L2::evict_first.b64 %0, 1.0;" : "=l"(pol));
    const uint32_t wbar = sbase + M_BAR + warp * 8, wslot = sbase + warp * SLOT;
    const int u0 = warp * nnb + nb;
    const bool hold = ((blk >> 2) >> KMIN << KMIN) * 4 * UPP < nstatic;
    const uint32_t jbar = sbase + M_BAR + (NSLOT + BRING) * 8;
    if (warp == 7) {
        if (lane == 0 && blk < 128) {
            mbar_init(jbar, 1);
            asm volatile("fence.mbarrier_init.release.cluster;" ::: "memory");
            uint64_t poln;
            asm volatile("createpolicy.fractional.L2::evict_normal.b64 %0, 1.0;" : "=l"(poln));
            mbar_expect_tx(jbar, 36864 + 4 * 1152);
            tma3d(sbase + J0W, &p.tm_j0, blk * 32, 0, 0, jbar, poln);
            bulk_load(sbase + M_XA, p.xa, 4608, jbar, poln);
        }
        if (lane < 16) reinterpret_cast<unsigned*>(smem + M_HELP)[lane] = 0;
        __syncwarp();
        if (!isB) asm volatile("bar.arrive 2, %0;" ::"n"(32 * (NW + XW + 1)) : "memory");
    }
    if (warp < 4 && lane == 0) {
        mbar_init(wbar, 1);
        if (CLU && warp == 3 && !isB) {
#pragma unroll
            for (int i = 0; i < 2; i++) {
                mbar_init(sbase + F_BAR + i * 8, 1);
                mbar_expect_tx(sbase + F_BAR + i * 8, 1024);
            }
        }
        asm volatile("fence.mbarrier_init.release.cluster;" ::: "memory");
        if (warp < NEARLY && !isB && !hold) {
            mbar_expect_tx(wbar, TILE_BYTES);
            bulk_load(wslot, block_src(p.kc, unit_block<CLU>(u0)), TILE_BYTES, wbar, pol);
        }
    }
    unsigned epoch = 0;
    if (lane == 0) epoch = ld_relaxed4(&g_epoch);
    TS(0);
    if (CLU && !isB) asm volatile("barrier.cluster.arrive.relaxed.aligned;" ::: "memory");
    if ((warp >> 1) == 2 && blk < 128) st_relaxed64(&g_qll[((tid - 128) >> 4) * 2048 + blk * 16 + (tid & 15)], 0ull);
    if (isB || warp >= NW + XW) epoch = __shfl_sync(~0u, epoch, 0);
    if (isB && warp == 3) asm volatile("bar.sync 1, 160;" ::: "memory");
    if (isB && tid == 96) {
#pragma unroll 1
        for (int i = 0; i < BRING; i++) mbar_init(sbase + M_BAR + (NSLOT + i) * 8, 1);
        asm volatile("fence.mbarrier_init.release.cluster;" ::: "memory");
        if (hold) { unsigned n = 0; while (ld_acquire_cta_shared(sbase + M_HELP + 24) < 2) { if (++n > (SPIN_LIMIT << 4)) __trap(); } }
#pragma unroll 1
        for (int b = 0; b < 4; b++) bulk_load(sbase + M_XB + b * XP, p.xb + b * DM, 1152, sbase + M_BAR + NSLOT * 8, pol);
#pragma unroll 1
        for (int n = 0; n < BD; n++) b_issue(p, n, bi, sbase, pol);
    }
    if (warp >= 4 && blk < 128) {
        const int g = lane >> 2, t = lane & 3, j = tid - 128;
        asm volatile("bar.sync 1, %0;" ::"r"(isB ? 160 : 128) : "memory");
#pragma unroll 1
        for (int sl = blk, ph = 0;; sl += 128 - gridDim.x, ph = 1) {
        mbar_wait(jbar, ph);
        TS(13);
        float acc[4][4];
#pragma unroll
        for (int i = 0; i < 16; i++) acc[i >> 2][i & 3] = 0.f;
        const uint32_t wa = sbase + J0W + ((warp - 4) * 144 + (lane & 15)) * 64;
        const uint32_t sw = (lane >> 1) & 3, xa = sbase + M_XA + (g & 3) * 1152 + (warp - 4) * 288 + t * 4;
#pragma unroll 3
        for (int s = 0; s < 9; s++) {
            const uint32_t a[4] = {lds32(xa + s * 32), 0u, lds32(xa + s * 32 + 16), 0u};
            uint32_t w0[4], w1[4];
            ldsm4t(w0, wa + s * 1024 + (((lane >> 4) ^ sw) * 16));
            ldsm4t(w1, wa + s * 1024 + (((2 + (lane >> 4)) ^ sw) * 16));
            mma16816(acc[0], a, w0[0], w0[1]);
            mma16816(acc[1], a, w0[2], w0[3]);
            mma16816(acc[2], a, w1[0], w1[1]);
            mma16816(acc[3], a, w1[2], w1[3]);
        }
        float2* j0 = reinterpret_cast<float2*>(smem + M_J0);
        if (g < 4) {
#pragma unroll
            for (int i = 0; i < 4; i++) j0[(warp - 4) * 64 + g * 16 + i * 4 + t] = make_float2(acc[i][0], acc[i][1]);
        }
        asm volatile("bar.sync 1, 128;" ::: "memory");
        const bool again = sl == blk && blk + 128 - (int)gridDim.x >= (int)gridDim.x;
        if (again && tid == 224) {
            mbar_expect_tx(jbar, 36864);
            tma3d(sbase + J0W, &p.tm_j0, (blk + 128 - gridDim.x) * 32, 0, 0, jbar, pol);
        }
        if (warp < 6) {
            const float2 v0 = j0[j], v1 = j0[64 + j], v2 = j0[128 + j], v3 = j0[192 + j];
            st_relaxed64(&g_qll[(j >> 4) * 2048 + sl * 16 + (j & 15)],
                         (unsigned long long)pack_bf16((v0.x + v1.x) + (v2.x + v3.x), (v0.y + v1.y) + (v2.y + v3.y)) |
                             ((unsigned long long)(epoch + 1) << 32));
            __syncwarp();
            if (lane == 0) asm volatile("red.relaxed.cta.shared::cta.add.u32 [%0], 1;" ::"r"(sbase + M_HELP + 24) : "memory");
        } else if (warp == 7) {
            if (blk < C_LINES) g_ctl[(epoch & 1) ^ 1][blk][lane] = 0;
        }
        TS(1);
        if (!again) break;
        asm volatile("bar.sync 1, 128;" ::: "memory");
        }
    }
    if (isB) {
        b_chain<CLU>(p, smem, sbase, bi, epoch, pol);
        return;
    }
    if (warp < NW + XW) {
        a_worker<CLU>(p, u0, warp >= NW + ((nb & 3) < (CLU ? X3C : X3) ? 1 : 0), warp < NEARLY && !hold, hold, nstatic, wslot, wbar, sbase + M_HELP, epoch, pol);
        if (CLU && nb < NFIN) {
            if (warp == 3) out_issue_sum(p, sbase, nb >> 3, nb & 7, pol);
            else if (warp == 0) out_late(sbase, nb >> 3, nb & 7);
        }
        return;
    } else if (warp == 7) {
#pragma unroll 1
        for (int i = nb; i < 4 * NH; i += nnb) g_oacc[i * 32 + lane] = make_float4(0.f, 0.f, 0.f, 0.f);
        if (nb < NREP * NH) g_vdone[nb][lane] = 0;
        __syncwarp();
        k_helper(sbase + M_HELP, epoch);
        if (nb == 0 && lane == 0) g_epoch = epoch + 1;
        __syncwarp();
        if (CLU && nb < NFIN) out_early(sbase, nb >> 3, nb & 7, epoch + 1);
    } else if (CLU) {
    } else if (warp == 6 && nb < NFIN) {
        finisher(p, sbase, nb);
        TS(4);
    } else if (warp >= 6 - NPOLL && nb < NFIN) {
        v_poller(sbase, nb, warp - (6 - NPOLL));
    }
    if (CLU && nb < NFIN) out_project(sbase, nb & 7, warp - 4);
}

}

typedef CUresult (*EncodeFn)(CUtensorMap*, CUtensorMapDataType, cuuint32_t, void*, const cuuint64_t*, const cuuint64_t*,
                             const cuuint32_t*, const cuuint32_t*, CUtensorMapInterleave, CUtensorMapSwizzle,
                             CUtensorMapL2promotion, CUtensorMapFloatOOBfill);

extern "C" void kernel_launch(void* const* d_in, const int* in_sizes, int n_in, void* d_out, int out_size) {
    (void)in_sizes; (void)n_in; (void)out_size;
    static int nsm = 0, ncl = 0;
    static EncodeFn encode = nullptr;
    cudaLaunchConfig_t cfg = {};
    cudaLaunchAttribute at[1];
    at[0].id = cudaLaunchAttributeClusterDimension;
    at[0].val.clusterDim.x = 8; at[0].val.clusterDim.y = 1; at[0].val.clusterDim.z = 1;
    cfg.blockDim = dim3(256); cfg.dynamicSmemBytes = SMEM_BYTES; cfg.stream = cudaStreamPerThread; cfg.attrs = at; cfg.numAttrs = 1;
    if (nsm == 0) {
        int dev = 0;
        cudaGetDevice(&dev);
        cudaDeviceGetAttribute(&nsm, cudaDevAttrMultiProcessorCount, dev);
        cudaFuncSetAttribute(fused_decode_kernel<false>, cudaFuncAttributeMaxDynamicSharedMemorySize, SMEM_BYTES);
        cudaFuncSetAttribute(fused_decode_kernel<true>, cudaFuncAttributeMaxDynamicSharedMemorySize, SMEM_BYTES);
        cfg.gridDim = dim3(128);
        if (cudaOccupancyMaxActiveClusters(&ncl, fused_decode_kernel<true>, &cfg) != cudaSuccess) { ncl = 0; (void)cudaGetLastError(); }
        if (ncl > MINCL) ncl = MINCL;
        void* fn = nullptr;
        cudaDriverEntryPointQueryResult qr;
        cudaGetDriverEntryPoint("cuTensorMapEncodeTiled", &fn, cudaEnableDefault, &qr);
        encode = (EncodeFn)fn;
    }
    Params p;
    auto panels = [&](CUtensorMap* tm, void* ptr, int rows, int cols, int box_rows, int box_panels) {
        const cuuint64_t gd[3] = {64, (cuuint64_t)rows, (cuuint64_t)(cols / 64)}, gs[2] = {(cuuint64_t)cols * 2, 128};
        const cuuint32_t box[3] = {64, (cuuint32_t)box_rows, (cuuint32_t)box_panels}, es[3] = {1, 1, 1};
        encode(tm, CU_TENSOR_MAP_DATA_TYPE_BFLOAT16, 3, ptr, gd, gs, box, es, CU_TENSOR_MAP_INTERLEAVE_NONE,
               CU_TENSOR_MAP_SWIZZLE_128B, CU_TENSOR_MAP_L2_PROMOTION_L2_256B, CU_TENSOR_MAP_FLOAT_OOB_FILL_NONE);
    };
    panels(&p.tm_wq, d_in[7], DM, 4096, 128, 2);
    panels(&p.tm_wuk, d_in[8], 512, 4096, 128, 2);
    panels(&p.tm_wuv, d_in[9], 512, 4096, 128, 2);
    panels(&p.tm_wo, d_in[10], 4096, DM, 32, 9);
    panels(&p.tm_wf, d_in[10], 4096, DM, 128, 1);
    panels(&p.tm_ckv, d_in[6], 4 * SK, 512, 32, 8);
    {
        const cuuint64_t gd[3] = {4096, 192, 3}, gs[2] = {8192, 192 * 8192};
        const cuuint32_t box[3] = {32, 192, 3}, es[3] = {1, 1, 1};
        encode(&p.tm_j0, CU_TENSOR_MAP_DATA_TYPE_BFLOAT16, 3, d_in[3], gd, gs, box, es, CU_TENSOR_MAP_INTERLEAVE_NONE,
               CU_TENSOR_MAP_SWIZZLE_64B, CU_TENSOR_MAP_L2_PROMOTION_L2_128B, CU_TENSOR_MAP_FLOAT_OOB_FILL_NONE);
    }
    {
        const cuuint64_t gd[3] = {DM, 512, 8}, gs[2] = {8 * DM * 2, DM * 2};
        const cuuint32_t box[3] = {64, 16, 8}, es[3] = {1, 1, 1};
        encode(&p.tm_wl, CU_TENSOR_MAP_DATA_TYPE_BFLOAT16, 3, d_in[4], gd, gs, box, es, CU_TENSOR_MAP_INTERLEAVE_NONE,
               CU_TENSOR_MAP_SWIZZLE_128B, CU_TENSOR_MAP_L2_PROMOTION_L2_256B, CU_TENSOR_MAP_FLOAT_OOB_FILL_NONE);
    }
    p.xa = (const __nv_bfloat16*)d_in[0];
    p.kc = (const __nv_bfloat16*)d_in[1];
    p.vc = (const __nv_bfloat16*)d_in[2];
    p.wo = (const __nv_bfloat16*)d_in[4];
    p.xb = (const __nv_bfloat16*)d_in[5];
    p.wob = (const __nv_bfloat16*)d_in[10];
    p.out = (__nv_bfloat16*)d_out;
    if (ncl >= MINCL) {
        cfg.gridDim = dim3(8 * ncl);
        cudaLaunchKernelEx(&cfg, fused_decode_kernel<true>, p);
    } else {
        fused_decode_kernel<false><<<nsm, 256, SMEM_BYTES, cudaStreamPerThread>>>(p);
    }
}
```

```cpp
#include <cuda_runtime.h>
#include <cuda.h>
#include <cuda_bf16.h>
#include <stdint.h>

namespace {

constexpr int NH = 32, SK = 4096, DM = 576;
constexpr int KEYS = 128;
constexpr int UPP = SK / KEYS;
constexpr int NUK = 4 * NH * UPP;
constexpr int TILE_BYTES = KEYS * 256;
#define NWORK 2
constexpr int NW = NWORK;
constexpr int NBCTA = 32;
constexpr int MINCL = 15;
constexpr int NFIN = 72;
constexpr int SLOT = 32768;
constexpr int NSLOT = 6;
constexpr int BRING = 5;
constexpr int J0W = 5 * SLOT;
constexpr int MISC = NSLOT * SLOT + 4096;
constexpr int XP = 1168, CP = 1040, QP = 272;
constexpr int M_XA = MISC;
constexpr int M_XB = M_XA + 4 * XP;
constexpr int M_CH = M_XB + 4 * XP;
constexpr int M_CL = M_CH + 4 * CP;
constexpr int M_QB = M_CL + 4 * CP;
constexpr int M_QA = M_CH;
constexpr int M_J0 = M_QB + 4 * QP;
constexpr int M_P = M_J0 + 2048;
constexpr int M_ALPHA = M_P + 2560;
constexpr int M_OMEGA = M_ALPHA + 128;
constexpr int M_BAR = M_OMEGA + 128;
constexpr int M_HELP = M_BAR + 128;
constexpr int F_W = 3 * SLOT;
constexpr int F_X = NSLOT * SLOT, FXP = 1088;
constexpr int F_RECV = F_X + 8 * FXP;
constexpr int F_BAR = M_P;
constexpr int SMEM_BYTES = M_HELP + 128 + 1024;
static_assert(F_RECV + 2048 <= M_J0, "output phase layout");
static_assert(SMEM_BYTES <= 232448 && M_BAR % 8 == 0 && M_QA % 16 == 0 && M_P % 16 == 0, "smem layout");
#define XW 2
#define X3 1
#define X3C 2
#define NEARLY 2
#define BD 4
#define FPF 3
#define FSLEEP 800
#define VMINC 2
#define FJ 270
#define FP 384
#define NPOLL 2
#define PGAP 200
static_assert(NW + XW <= 4 && NEARLY <= NW + XW && BD <= BRING, "slots 4 and 5 hold the finisher weights");
constexpr int KMIN = 2, KMAX = 4, VMAX = 4;
constexpr float SCALE = 0.08838834764831845f;
constexpr float LOG2E = 1.4426950408889634f;
constexpr unsigned SPIN_LIMIT = 1u << 24;

#define NREP 2
constexpr int C_QUEUE = 0, C_KDONE = 1, C_BBAR = 3, C_LINES = 5;

struct Params {
    const __nv_bfloat16 *kc, *xa, *vc, *wo, *xb, *wob;
    __nv_bfloat16* out;
    CUtensorMap tm_j0;
    CUtensorMap tm_wq, tm_wuk, tm_ckv, tm_wuv, tm_wo;
    CUtensorMap tm_wl;
    CUtensorMap tm_wf;
};

__device__ unsigned g_epoch;
__device__ unsigned g_ctl[2][C_LINES][32];
__device__ uint2 g_qll[4 * 2048];
__device__ uint2 g_scores[128 * SK / 4];
__device__ float2 g_stats[128 * UPP];
__device__ float4 g_oacc[128 * 32];
__device__ unsigned g_vdone[NREP * NH][32];
__device__ uint4 g_qabs[4 * 8 * 4 * 4 * 32];
__device__ float2 g_bpart[NBCTA * NH * 256];
__device__ float2 g_bml[NBCTA * NH];
__device__ uint4 g_ctx[NH * 128];
__device__ uint4 g_outb[NBCTA * NH * 36];

#define TS(i)
#define TSV(i, v)
#define LAND(i)
#define CLK(x)
#define ACC(a, x, y)

__device__ __forceinline__ uint32_t smem_u32(const void* p) { return (uint32_t)__cvta_generic_to_shared(p); }
__device__ __forceinline__ void mbar_init(uint32_t bar, uint32_t cnt) {
    asm volatile("mbarrier.init.shared::cta.b64 [%0], %1;" ::"r"(bar), "r"(cnt) : "memory");
}
__device__ __forceinline__ void mbar_expect_tx(uint32_t bar, uint32_t bytes) {
    asm volatile("mbarrier.arrive.expect_tx.shared::cta.b64 _, [%0], %1;" ::"r"(bar), "r"(bytes) : "memory");
}
__device__ __forceinline__ bool mbar_try(uint32_t bar, uint32_t parity) {
    uint32_t ok;
    asm volatile("{\n.reg .pred p;\nmbarrier.try_wait.parity.shared::cta.b64 p, [%1], %2;\nselp.u32 %0, 1, 0, p;\n}\n"
                 : "=r"(ok) : "r"(bar), "r"(parity) : "memory");
    return ok;
}
__device__ __forceinline__ void mbar_wait(uint32_t bar, uint32_t parity) {
    unsigned n = 0;
    while (!mbar_try(bar, parity)) { if (++n > SPIN_LIMIT) __trap(); }
}
__device__ __forceinline__ void bulk_load(uint32_t dst, const void* src, uint32_t bytes, uint32_t bar, uint64_t pol) {
    asm volatile("cp.async.bulk.shared::cluster.global.mbarrier::complete_tx::bytes.L2::cache_hint [%0], [%1], %2, [%3], %4;"
                 ::"r"(dst), "l"(src), "r"(bytes), "r"(bar), "l"(pol) : "memory");
}
__device__ __forceinline__ void tma3d(uint32_t dst, const CUtensorMap* tm, int c0, int c1, int c2, uint32_t bar, uint64_t pol) {
    asm volatile("cp.async.bulk.tensor.3d.shared::cluster.global.mbarrier::complete_tx::bytes.L2::cache_hint [%0], [%1, {%3,%4,%5}], [%2], %6;"
                 ::"r"(dst), "l"(tm), "r"(bar), "r"(c0), "r"(c1), "r"(c2), "l"(pol) : "memory");
}
__device__ __forceinline__ void l2_prefetch(const void* src, uint32_t bytes) {
    asm volatile("cp.async.bulk.prefetch.L2.global [%0], %1;" ::"l"(src), "r"(bytes) : "memory");
}
__device__ __forceinline__ void ldsm4(uint32_t (&r)[4], uint32_t addr) {
    asm volatile("ldmatrix.sync.aligned.m8n8.x4.shared.b16 {%0,%1,%2,%3}, [%4];"
                 : "=r"(r[0]), "=r"(r[1]), "=r"(r[2]), "=r"(r[3]) : "r"(addr));
}
__device__ __forceinline__ void ldsm4t(uint32_t (&r)[4], uint32_t addr) {
    asm volatile("ldmatrix.sync.aligned.m8n8.x4.trans.shared.b16 {%0,%1,%2,%3}, [%4];"
                 : "=r"(r[0]), "=r"(r[1]), "=r"(r[2]), "=r"(r[3]) : "r"(addr));
}
__device__ __forceinline__ void mma16816(float (&d)[4], const uint32_t (&a)[4], uint32_t b0, uint32_t b1) {
    asm("mma.sync.aligned.m16n8k16.row.col.f32.bf16.bf16.f32 {%0,%1,%2,%3}, {%4,%5,%6,%7}, {%8,%9}, {%0,%1,%2,%3};"
        : "+f"(d[0]), "+f"(d[1]), "+f"(d[2]), "+f"(d[3])
        : "r"(a[0]), "r"(a[1]), "r"(a[2]), "r"(a[3]), "r"(b0), "r"(b1));
}
__device__ __forceinline__ void wgmma_tile(float (&d)[4], uint32_t da, uint32_t db, int accumulate) {
    asm volatile("{\n.reg .pred p;\n.reg .b32 x, y;\n.reg .b64 a, b;\nsetp.ne.u32 p, %6, 0;\nwgmma.fence.sync.aligned;\n"
                 "add.u32 x, %4, 0;\nadd.u32 y, %5, 0;\nmov.b64 a, {x, 0x40000040};\nmov.b64 b, {y, 1};\n"
                 "wgmma.mma_async.sync.aligned.m64n8k16.f32.bf16.bf16 {%0,%1,%2,%3}, a, b, p, 1, 1, 1, 0;\n"
                 "add.u32 x, %4, 128;\nadd.u32 y, %5, 8;\nmov.b64 a, {x, 0x40000040};\nmov.b64 b, {y, 1};\n"
                 "wgmma.mma_async.sync.aligned.m64n8k16.f32.bf16.bf16 {%0,%1,%2,%3}, a, b, 1, 1, 1, 1, 0;\n"
                 "add.u32 x, %4, 256;\nadd.u32 y, %5, 16;\nmov.b64 a, {x, 0x40000040};\nmov.b64 b, {y, 1};\n"
                 "wgmma.mma_async.sync.aligned.m64n8k16.f32.bf16.bf16 {%0,%1,%2,%3}, a, b, 1, 1, 1, 1, 0;\n"
                 "add.u32 x, %4, 384;\nadd.u32 y, %5, 24;\nmov.b64 a, {x, 0x40000040};\nmov.b64 b, {y, 1};\n"
                 "wgmma.mma_async.sync.aligned.m64n8k16.f32.bf16.bf16 {%0,%1,%2,%3}, a, b, 1, 1, 1, 1, 0;\n"
                 "add.u32 x, %4, 512;\nadd.u32 y, %5, 32;\nmov.b64 a, {x, 0x40000040};\nmov.b64 b, {y, 1};\n"
                 "wgmma.mma_async.sync.aligned.m64n8k16.f32.bf16.bf16 {%0,%1,%2,%3}, a, b, 1, 1, 1, 1, 0;\n"
                 "add.u32 x, %4, 640;\nadd.u32 y, %5, 40;\nmov.b64 a, {x, 0x40000040};\nmov.b64 b, {y, 1};\n"
                 "wgmma.mma_async.sync.aligned.m64n8k16.f32.bf16.bf16 {%0,%1,%2,%3}, a, b, 1, 1, 1, 1, 0;\n"
                 "add.u32 x, %4, 768;\nadd.u32 y, %5, 48;\nmov.b64 a, {x, 0x40000040};\nmov.b64 b, {y, 1};\n"
                 "wgmma.mma_async.sync.aligned.m64n8k16.f32.bf16.bf16 {%0,%1,%2,%3}, a, b, 1, 1, 1, 1, 0;\n"
                 "add.u32 x, %4, 896;\nadd.u32 y, %5, 56;\nmov.b64 a, {x, 0x40000040};\nmov.b64 b, {y, 1};\n"
                 "wgmma.mma_async.sync.aligned.m64n8k16.f32.bf16.bf16 {%0,%1,%2,%3}, a, b, 1, 1, 1, 1, 0;\n"
                 "wgmma.commit_group.sync.aligned;\n}"
                 : "+f"(d[0]), "+f"(d[1]), "+f"(d[2]), "+f"(d[3]) : "r"(da), "r"(db), "r"(accumulate) : "memory");
}
__device__ __forceinline__ uint32_t lds32(uint32_t a) {
    uint32_t v;
    asm volatile("ld.shared.u32 %0, [%1];" : "=r"(v) : "r"(a));
    return v;
}
__device__ __forceinline__ unsigned ld_acquire(const unsigned* p) {
    unsigned v;
    asm volatile("ld.acquire.gpu.global.u32 %0, [%1];" : "=r"(v) : "l"(p) : "memory");
    return v;
}
__device__ __forceinline__ uint2 ld_relaxed8(const void* p) {
    uint2 v;
    asm volatile("ld.relaxed.gpu.global.v2.u32 {%0,%1}, [%2];" : "=r"(v.x), "=r"(v.y) : "l"(p) : "memory");
    return v;
}
__device__ __forceinline__ unsigned ld_relaxed4(const void* p) {
    unsigned v;
    asm volatile("ld.relaxed.gpu.global.u32 %0, [%1];" : "=r"(v) : "l"(p) : "memory");
    return v;
}
__device__ __forceinline__ unsigned atom_inc(unsigned* p) {
    unsigned v;
    asm volatile("atom.relaxed.gpu.global.inc.u32 %0, [%1], 0x7fffffff;" : "=r"(v) : "l"(p) : "memory");
    return v;
}
__device__ __forceinline__ unsigned long long ld_relaxed64(const void* p) {
    unsigned long long v;
    asm volatile("ld.relaxed.gpu.global.u64 %0, [%1];" : "=l"(v) : "l"(p) : "memory");
    return v;
}
__device__ __forceinline__ void st_relaxed64(void* p, unsigned long long v) {
    asm volatile("st.relaxed.gpu.global.u64 [%0], %1;" ::"l"(p), "l"(v) : "memory");
}
__device__ __forceinline__ float4 ld_relaxed16(const void* p) {
    float4 v;
    asm volatile("ld.relaxed.gpu.global.v4.f32 {%0,%1,%2,%3}, [%4];" : "=f"(v.x), "=f"(v.y), "=f"(v.z), "=f"(v.w) : "l"(p) : "memory");
    return v;
}
__device__ __forceinline__ uint32_t mapa(uint32_t a, uint32_t rank) {
    uint32_t r;
    asm("mapa.shared::cluster.u32 %0, %1, %2;" : "=r"(r) : "r"(a), "r"(rank));
    return r;
}
__device__ __forceinline__ void mbar_spin(uint32_t bar) {
    asm volatile("{\n.reg .pred p, q;\n.reg .u32 n;\nmov.u32 n, 0;\n"
                 "SPIN:\nmbarrier.test_wait.parity.shared::cta.b64 p, [%0], 0;\nadd.u32 n, n, 1;\nsetp.gt.u32 q, n, 0x4000000;\n@q trap;\n"
                 "@!p bra.uni SPIN;\n}" ::"r"(bar) : "memory");
}
__device__ __forceinline__ void mbar_spin_cluster(uint32_t bar) {
    asm volatile("{\n.reg .pred p, q;\n.reg .u32 n;\nmov.u32 n, 0;\n"
                 "SPIN:\nmbarrier.test_wait.parity.relaxed.cluster.shared::cta.b64 p, [%0], 0;\nadd.u32 n, n, 1;\nsetp.gt.u32 q, n, 0x4000000;\n@q trap;\n"
                 "@!p bra.uni SPIN;\nfence.acquire.sync_restrict::shared::cluster.cluster;\n}" ::"r"(bar) : "memory");
}
__device__ __forceinline__ uint32_t now_ns() {
    unsigned long long t;
    asm volatile("mov.u64 %0, %globaltimer;" : "=l"(t));
    return (uint32_t)t;
}
__device__ __forceinline__ void fence_gpu() { asm volatile("fence.acq_rel.gpu;" ::: "memory"); }
__device__ __forceinline__ void red_add_u32(unsigned* p, unsigned v) {
    asm volatile("red.relaxed.gpu.global.add.u32 [%0], %1;" ::"l"(p), "r"(v) : "memory");
}
__device__ __forceinline__ void st_tagged2(void* p, float a, float b, unsigned tag) {
    const unsigned long long hi = (unsigned long long)tag << 32;
    asm volatile("st.relaxed.gpu.global.v2.b64 [%0], {%1,%2};" ::"l"(p), "l"(hi | __float_as_uint(a)), "l"(hi | __float_as_uint(b)) : "memory");
}
__device__ __forceinline__ ulonglong2 ld_tagged2(const void* p) {
    ulonglong2 v;
    asm volatile("ld.relaxed.gpu.global.v2.b64 {%0,%1}, [%2];" : "=l"(v.x), "=l"(v.y) : "l"(p) : "memory");
    return v;
}
__device__ __forceinline__ float4 atom_add_f4(void* p, float a, float b, float c, float d) {
    float4 r;
    asm volatile("atom.relaxed.gpu.global.add.v4.f32 {%0,%1,%2,%3}, [%4], {%5,%6,%7,%8};"
                 : "=f"(r.x), "=f"(r.y), "=f"(r.z), "=f"(r.w) : "l"(p), "f"(a), "f"(b), "f"(c), "f"(d) : "memory");
    return r;
}
__device__ __forceinline__ void red_release_cta_shared(uint32_t a, unsigned v) {
    asm volatile("red.release.cta.shared::cta.add.u32 [%0], %1;" ::"r"(a), "r"(v) : "memory");
}
__device__ __forceinline__ unsigned ld_acquire_cta_shared(uint32_t a) {
    unsigned v;
    asm volatile("ld.acquire.cta.shared::cta.u32 %0, [%1];" : "=r"(v) : "r"(a) : "memory");
    return v;
}
__device__ __forceinline__ void st_release_cta_shared(uint32_t a, unsigned v) {
    asm volatile("st.release.cta.shared::cta.u32 [%0], %1;" ::"r"(a), "r"(v) : "memory");
}
__device__ __forceinline__ void wait_count(const unsigned* p, unsigned target) {
    unsigned n = 0;
    while (ld_acquire(p) < target) { if (++n > SPIN_LIMIT) __trap(); }
}
__device__ __forceinline__ uint32_t pack_bf16(float lo, float hi) {
    uint32_t r;
    asm("cvt.rn.bf16x2.f32 %0, %1, %2;" : "=r"(r) : "f"(hi), "f"(lo));
    return r;
}
__device__ __forceinline__ float bf_lo(uint32_t v) { return __uint_as_float(v << 16); }
__device__ __forceinline__ float bf_hi(uint32_t v) { return __uint_as_float(v & 0xffff0000u); }
__device__ __forceinline__ float ex2(float x) { float y; asm("ex2.approx.ftz.f32 %0, %1;" : "=f"(y) : "f"(x)); return y; }
__device__ __forceinline__ float expsub(float a, float b) { return ex2((a - b) * LOG2E); }
__device__ __forceinline__ float warp_max(float v) {
#pragma unroll
    for (int m = 16; m; m >>= 1) v = fmaxf(v, __shfl_xor_sync(~0u, v, m));
    return v;
}
__device__ __forceinline__ float warp_sum(float v) {
#pragma unroll
    for (int m = 16; m; m >>= 1) v += __shfl_xor_sync(~0u, v, m);
    return v;
}
template <bool CLU>
__device__ __forceinline__ unsigned unit_block(int u) {
    const unsigned x = ((unsigned)u & (NUK - 1)) / UPP;
    const int lg = u < NUK ? min(KMAX, max(KMIN, 29 - __clz(x | 1))) : min(VMAX, max(CLU ? VMINC : 0, 29 - __clz((127 - x) | 1)));
    const unsigned r = x & ((4u << lg) - 1);
    return ((x - r + (r & ((1u << lg) - 1)) * 4 + (r >> lg)) * UPP) | ((unsigned)u & (UPP - 1));
}
__device__ __forceinline__ const char* block_src(const void* base, unsigned blk) {
    const unsigned po = blk / UPP;
    return reinterpret_cast<const char*>(base) + (size_t)(((po & 3) * NH + (po >> 2)) * UPP + blk % UPP) * TILE_BYTES;
}

template <bool CLU>
__device__ __forceinline__ void a_worker(const Params& p, int un, bool once, bool pre, bool hold, int nstatic, uint32_t slot, uint32_t bar,
                                         uint32_t help, unsigned epoch, uint64_t pol) {
    constexpr int NU = 2 * NUK;
    const int lane = threadIdx.x & 31, g = lane >> 2, t = lane & 3;
    const int li = lane & 7;
    uint32_t kaddr[4], vaddr[8];
    {
        const int e = (lane >> 3) & 1, kk = lane >> 4;
#pragma unroll
        for (int s = 0; s < 4; s++) kaddr[s] = slot + (16 * li + e) * 256 + ((2 * s + kk + li) & 7) * 16;
        const int vrow = 4 * (li >> 1) + (li & 1) + 2 * kk;
#pragma unroll
        for (int c = 0; c < 8; c++) vaddr[c] = slot + vrow * 256 + e * 128 + ((c + li) & 7) * 16;
#pragma unroll
        for (int c = 0; c < 8; c++) asm volatile("" : "+r"(vaddr[c]));
    }
    const uint32_t vmask = (g >> 1) != t ? 0u : ((g & 1) ? 0xffff0000u : 0xffffu);
    int kseen = -1;
    unsigned long long H0 = 0, H1 = 0;
    auto header = [&](int v, unsigned vb) {
        if (v >= NU) return;
        const void *a0, *a1;
        if (v < NUK) {
            const unsigned po = vb / UPP;
            a0 = g_qll + (po & 3) * 2048 + (po >> 2) * 64 + lane;
            a1 = reinterpret_cast<const uint2*>(a0) + 32;
        } else {
            const int half = vb / (NUK / 2);
            if (half > kseen) {
                unsigned n = 0;
                while (ld_acquire_cta_shared(help + 12 + 4 * half) == 0) { if (++n > (SPIN_LIMIT << 4)) __trap(); }
                kseen = half;
            }
            a0 = &g_scores[vb * (KEYS / 4) + lane];
            a1 = &g_stats[(vb / UPP) * UPP + lane];
        }
        H0 = ld_relaxed64(a0);
        H1 = ld_relaxed64(a1);
    };
    asm volatile("bar.sync 2, %0;" ::"n"(32 * (NW + XW + 1)) : "memory");
    epoch = __shfl_sync(~0u, epoch, 0);
    if (hold) { unsigned n = 0; while (ld_acquire_cta_shared(help + 24) < 2) { if (++n > (SPIN_LIMIT << 4)) __trap(); } }
    unsigned (*ctl)[32] = g_ctl[epoch & 1];
    const unsigned tag = epoch + 1;
    unsigned nxt = once ? NU : 0;
    int u = -1;
    unsigned bu = 0, bn = unit_block<CLU>(un);
    bool have = false;
    uint32_t phase = 0;
    unsigned kpend = 0;
    const unsigned zero = gridDim.x >> 24;
    uint32_t Q[16];
    float4 oret = make_float4(0.f, 0.f, 0.f, 0.f);
    while (true) {
        const char* nsrc = block_src(un < NUK ? p.kc : p.vc, bn);
        float4* odst = &g_oacc[(bu / UPP) * 32 + lane];
        unsigned* vdst = &g_vdone[(lane & (NREP - 1)) * NH + bu / (4 * UPP)][0];
        float d[8][4];
        CLK(c1);
        asm volatile("" : "+l"(odst));
        if (u >= NUK) {
#pragma unroll
            for (int j = 0; j < 8; j++) { d[j][0] = d[j][1] = d[j][2] = d[j][3] = 0.f; }
            mbar_wait(bar, phase);
            LAND(NUK + bu);
            uint32_t a[2][8][4];
#pragma unroll
            for (int c = 0; c < 8; c++) ldsm4t(a[0][c], vaddr[c]);
#pragma unroll
            for (int j = 0; j < 8; j++) {
                if (j < 7) {
#pragma unroll
                    for (int c = 0; c < 8; c++) ldsm4t(a[(j + 1) & 1][c], vaddr[c] + (j + 1) * 4096);
                }
#pragma unroll
                for (int c = 0; c < 8; c++) mma16816(d[c], a[j & 1][c], Q[2 * j], Q[2 * j + 1]);
            }
            float o[4];
#pragma unroll
            for (int r = 0; r < 2; r++) {
                o[2 * r] = d[0][2 * r] + d[7][2 * r + 1];
                o[2 * r + 1] = d[0][2 * r + 1] + d[1][2 * r];
#pragma unroll
                for (int k = 1; k < 4; k++) {
                    const int src = (lane & 28) | ((t - k) & 3);
                    o[2 * r] += __shfl_sync(~0u, d[2 * k][2 * r] + d[2 * k - 1][2 * r + 1], src);
                    o[2 * r + 1] += __shfl_sync(~0u, d[2 * k][2 * r + 1] + d[2 * k + 1][2 * r], src);
                }
            }
            oret = atom_add_f4(odst, o[0], o[1], o[2], o[3]);
        } else if (u >= 0) {
#pragma unroll
            for (int j = 0; j < 8; j++) { d[j][0] = d[j][1] = d[j][2] = d[j][3] = 0.f; }
            mbar_wait(bar, phase);
            LAND(bu);
            uint32_t a[2][8][4];
#pragma unroll
            for (int j = 0; j < 8; j++) ldsm4(a[0][j], kaddr[0] + (4 * (j & 3) + 2 * (j >> 2)) * 256);
#pragma unroll
            for (int s = 0; s < 8; s++) {
                if (s < 7) {
#pragma unroll
                    for (int j = 0; j < 8; j++)
                        ldsm4(a[(s + 1) & 1][j], kaddr[(s + 1) & 3] + (4 * (j & 3) + 2 * (j >> 2)) * 256 + ((s + 1) >> 2) * 128);
                }
#pragma unroll
                for (int j = 0; j < 8; j++)
                    mma16816(d[j], a[s & 1][j], Q[(s & 4) * 2 + ((2 * s - 2 * j) & 7)], Q[(s & 4) * 2 + ((2 * s + 1 - 2 * j) & 7)]);
            }
        }
        if (u >= 0) phase ^= 1;
        CLK(c2b);
        if (un < NU && lane == 0) {
            if (!once) nxt = atom_inc(&ctl[C_QUEUE][0]);
            if (u >= 0 || !pre) {
                mbar_expect_tx(bar, TILE_BYTES);
                bulk_load(slot, nsrc, TILE_BYTES, bar, pol);
            }
        }
        const uint32_t tiss = now_ns();
        CLK(c3);
        if ((unsigned)u < (unsigned)NUK) {
            const int j0 = (t - (g >> 1)) & 3;
            float v[4];
#pragma unroll
            for (int q = 0; q < 4; q++) {
                const int jq = (q >> 1) * 4, e = (q & 1) * 2;
                const float x0 = (g & 1) ? d[jq + 0][e + 1] : d[jq + 0][e];
                const float x1 = (g & 1) ? d[jq + 1][e + 1] : d[jq + 1][e];
                const float x2 = (g & 1) ? d[jq + 2][e + 1] : d[jq + 2][e];
                const float x3 = (g & 1) ? d[jq + 3][e + 1] : d[jq + 3][e];
                const float y0 = (j0 & 1) ? x1 : x0, y1 = (j0 & 1) ? x3 : x2;
                v[q] = (j0 & 2) ? y1 : y0;
            }
            const uint32_t r0 = pack_bf16(v[0], v[1]), r1 = pack_bf16(v[2], v[3]);
            const uint32_t s0 = pack_bf16(bf_lo(r0) * SCALE, bf_hi(r0) * SCALE);
            const uint32_t s1 = pack_bf16(bf_lo(r1) * SCALE, bf_hi(r1) * SCALE);
            g_scores[bu * (KEYS / 4) + 4 * g + j0] = make_uint2(s0, s1);
            const float f0 = bf_lo(s0), f1 = bf_hi(s0), f2 = bf_lo(s1), f3 = bf_hi(s1);
            const float m = warp_max(fmaxf(fmaxf(f0, f1), fmaxf(f2, f3)));
            const float l = warp_sum((expsub(f0, m) + expsub(f1, m)) + (expsub(f2, m) + expsub(f3, m)));
            if (lane == 0) g_stats[bu] = make_float2(m, l);
            kpend++;
            if (un / (NUK / 2) != u / (NUK / 2)) {
                __syncwarp();
                if (lane == 0) {
                    red_release_cta_shared(help + 4 * (u / (NUK / 2)), kpend);
                    if (un >= NUK) red_release_cta_shared(help + 8, 1u);
                }
                kpend = 0;
            }
        }
        CLK(c4);
        int unn = NU;
        if (un < NU) {
            unsigned n = 0;
            while (true) {
                if (!have) header(un, bn);
                if (un >= NUK || __all_sync(~0u, (uint32_t)(H0 >> 32) == tag && (uint32_t)(H1 >> 32) == tag)) break;
                if (++n > SPIN_LIMIT) __trap();
                have = false;
            }
            if (un >= NUK) {
                const uint32_t s0 = (uint32_t)H0, s1 = (uint32_t)(H0 >> 32);
                const float mu = __uint_as_float((uint32_t)H1);
                const float m = warp_max(mu);
                const float l = warp_sum(__uint_as_float((uint32_t)(H1 >> 32)) * expsub(mu, m));
                const float inv = 1.0f / l;
                const uint32_t w0 = pack_bf16(expsub(bf_lo(s0), m) * inv, expsub(bf_hi(s0), m) * inv);
                const uint32_t w1 = pack_bf16(expsub(bf_lo(s1), m) * inv, expsub(bf_hi(s1), m) * inv);
#pragma unroll
                for (int j = 0; j < 8; j++) {
                    Q[2 * j] = __shfl_sync(~0u, w0, 4 * j + t) & vmask;
                    Q[2 * j + 1] = __shfl_sync(~0u, w1, 4 * j + t) & vmask;
                }
            } else {
#pragma unroll
                for (int j = 0; j < 8; j++) {
                    const int src = (((j + g) & 7) << 2) + t;
                    Q[j] = __shfl_sync(~0u, (uint32_t)H0, src);
                    Q[8 + j] = __shfl_sync(~0u, (uint32_t)H1, src);
                }
            }
            unn = nstatic + (int)__shfl_sync(~0u, nxt, 0);
            if (CLU && !once && unn >= NU && lane == 0)
                asm volatile("st.relaxed.cta.shared::cta.u32 [%0], %1;" ::"r"(help + 28), "r"((tiss + (FJ - (unn - NU)) * 10) | 1u) : "memory");
        }
        if (u >= NUK && lane < (CLU ? 1 : NREP))
            red_add_u32(vdst,
                        1u + ((__float_as_uint(oret.x) | __float_as_uint(oret.y) | __float_as_uint(oret.z) | __float_as_uint(oret.w)) & zero));
        if (un >= NU) break;
        bu = bn;
        have = !(un < NUK && unn >= NUK && !(un >= NUK / 2 && unn < NUK + NUK / 2));
        bn = unit_block<CLU>(unn);
        if (have) header(unn, bn);
        u = un;
        un = unn;
    }
}

__device__ __forceinline__ void k_helper(uint32_t help, unsigned epoch) {
    if ((threadIdx.x & 31) != 0) return;
    unsigned (*ctl)[32] = g_ctl[epoch & 1];
    unsigned sent0 = 0, sent1 = 0, n = 0;
    int seen = 0;
    bool fin = false;
    while (!fin || seen < 2) {
        if (!fin) {
            fin = ld_acquire_cta_shared(help + 8) == NW + XW;
            const unsigned c0 = ld_acquire_cta_shared(help), c1 = ld_acquire_cta_shared(help + 4);
            if (c0 != sent0 || c1 != sent1) {
                fence_gpu();
                if (c0 != sent0) red_add_u32(&ctl[C_KDONE][0], c0 - sent0);
                if (c1 != sent1) red_add_u32(&ctl[C_KDONE + 1][0], c1 - sent1);
                sent0 = c0; sent1 = c1;
            }
        }
        if (seen < 2 && ld_acquire(&ctl[C_KDONE + seen][0]) >= NUK / 2) {
            st_release_cta_shared(help + 12 + 4 * seen, 1u);
            seen++;
        } else {
            __nanosleep(300);
        }
        if (++n > SPIN_LIMIT) __trap();
    }
}

__device__ __forceinline__ void v_poller(uint32_t sbase, int f, int w) {
    const int lane = threadIdx.x & 31;
    const unsigned (*cp)[32] = &g_vdone[((f * NPOLL + w) % NREP) * NH];
    unsigned n = 0;
    while (ld_acquire_cta_shared(sbase + M_HELP + 12) == 0) { __nanosleep(1000); if (++n > SPIN_LIMIT) __trap(); }
    int h = 0;
    bool fast = false;
    while (h < NH) {
        const unsigned r = __ballot_sync(~0u, ld_acquire(&cp[min(h + (lane & 3), NH - 1)][0]) >= 4 * UPP) & 15u;
        if (r & 1) {
            h = min(NH, h + __ffs(~r) - 1);
            __syncwarp();
            if (lane == 0) asm volatile("red.release.cta.shared::cta.max.u32 [%0], %1;" ::"r"(sbase + M_HELP + 20), "r"(h) : "memory");
        }
        if (h < NH - 4) {
            __nanosleep(h ? 300 : 1000);
        } else if (!fast) {
            fast = true;
            const long long t0 = clock64();
            while (clock64() - t0 < w * PGAP) {}
        }
        if (++n > SPIN_LIMIT) __trap();
    }
}
__device__ __forceinline__ void finisher(const Params& p, uint32_t sbase, int f) {
    const int lane = threadIdx.x & 31;
    {
        const char* wg = reinterpret_cast<const char*>(p.wo);
        const uint32_t dst = sbase + 4 * SLOT + (16 * (lane & 7) + (lane >> 3)) * 16;
#pragma unroll 1
        for (int h = -FPF - 4; h < NH; h++) {
            if (lane == 0 && (unsigned)(h + FPF) < (unsigned)NH) l2_prefetch(wg + (size_t)(h + FPF) * 147456 + f * 2048, 2048);
            if (h >= 0) {
#pragma unroll
                for (int r = 0; r < 4; r++)
                    asm volatile("cp.async.cg.shared.global [%0], [%1], 16;" ::"r"(dst + h * 2048 + ((r & 1) * 4 + (r >> 1) * 8) * 16),
                                 "l"(wg + (size_t)(h * 128 + r * 32 + lane) * (DM * 2) + f * 16) : "memory");
            }
            __nanosleep(FSLEEP);
        }
        asm volatile("cp.async.wait_all;" ::: "memory");
        __syncwarp();
    }
    TS(11);
    const float4* vec = g_oacc + ((lane >> 2) & 3) * 32 + (lane >> 4) * 16 + (lane & 3);
    float acc[2][2][4];
#pragma unroll
    for (int i = 0; i < 16; i++) acc[i >> 3][(i >> 2) & 1][i & 3] = 0.f;
    uint32_t* outp = reinterpret_cast<uint32_t*>(p.out + (lane >> 2) * (2 * DM) + f * 8 + (lane & 3) * 2);
    uint32_t wa = sbase + 4 * SLOT + lane * 16;
    auto project = [&](const float4 (&x)[4], const uint32_t (&w)[4][4]) {
#pragma unroll
        for (int s = 0; s < 4; s++) {
            const uint32_t a[4] = {pack_bf16(x[s].x, x[s].y), 0u, pack_bf16(x[s].z, x[s].w), 0u};
            mma16816(acc[0][s & 1], a, w[s >> 1][(s & 1) * 2], w[s >> 1][(s & 1) * 2 + 1]);
            mma16816(acc[1][s & 1], a, w[2 + (s >> 1)][(s & 1) * 2], w[2 + (s >> 1)][(s & 1) * 2 + 1]);
        }
    };
    int h = 0;
    unsigned n = 0;
    while (h < NH) {
        uint32_t w[4][4];
#pragma unroll
        for (int q = 0; q < 4; q++) ldsm4t(w[q], wa + q * 512);
        int ready;
        while ((ready = ld_acquire_cta_shared(sbase + M_HELP + 20)) <= h) {
            if (h < NH - 3) __nanosleep(100);
            if (++n > (SPIN_LIMIT << 4)) __trap();
        }
        float4 x[4], y[4];
#pragma unroll
        for (int s = 0; s < 4; s++) x[s] = ld_relaxed16(vec + s * 4);
        const bool two = ready > h + 1;
        if (two) {
#pragma unroll
            for (int s = 0; s < 4; s++) y[s] = ld_relaxed16(vec + 128 + s * 4);
        }
        project(x, w);
        if (two) {
#pragma unroll
            for (int q = 0; q < 4; q++) ldsm4t(w[q], wa + 2048 + q * 512);
            project(y, w);
        }
        const int nr = two ? 2 : 1;
        h += nr;
        vec += nr * 128;
        wa += nr * 2048;
        const float o0 = acc[0][0][0] + acc[0][1][0] + __shfl_down_sync(~0u, acc[1][0][0] + acc[1][1][0], 16);
        const float o1 = acc[0][0][1] + acc[0][1][1] + __shfl_down_sync(~0u, acc[1][0][1] + acc[1][1][1], 16);
        asm volatile("{\n.reg .pred p;\nsetp.ne.u32 p, %2, 0;\n@p st.global.u32 [%0], %1;\n}" ::"l"(outp), "r"(pack_bf16(o0, o1)),
                     "r"((uint32_t)(lane < 16 && h == NH)) : "memory");
    }
}

__device__ __forceinline__ void out_fetch(uint32_t sbase, int step, int h) {
    const int lane = threadIdx.x & 31, g = lane >> 2;
    float4 x[4];
#pragma unroll
    for (int b = 0; b < 4; b++) x[b] = ld_relaxed16(&g_oacc[(h * 4 + ((b + g) & 3)) * 32 + lane]);
#pragma unroll
    for (int b = 0; b < 4; b++) {
        const uint32_t a = sbase + F_X + step * FXP + g * 128 + ((b + g) & 3) * 16 + (lane & 3) * 4;
        asm volatile("st.shared.u32 [%0], %1;\nst.shared.u32 [%0 + 64], %2;" ::"r"(a), "r"(pack_bf16(x[b].x, x[b].y)), "r"(pack_bf16(x[b].z, x[b].w)) : "memory");
    }
    asm volatile("fence.proxy.async.shared::cta;" ::: "memory");
}
__device__ __forceinline__ void out_early(uint32_t sbase, int rank, unsigned tag) {
    const int lane = threadIdx.x & 31;
    if (lane < 10) {
        mbar_init(sbase + F_BAR + 16 + lane * 8, lane < 7 ? 1 : lane == 7 ? 2 : 4);
        if (lane < 8) mbar_expect_tx(sbase + F_BAR + 16 + lane * 8, 16384);
    }
    asm volatile("fence.mbarrier_init.release.cluster;" ::: "memory");
    unsigned n = 0;
#pragma unroll 1
    for (int i = 0; i < 3; i++) {
        while (ld_acquire(&g_vdone[8 * i + rank][0]) < 4 * UPP) { __nanosleep(500); if (++n > SPIN_LIMIT) __trap(); }
        out_fetch(sbase, 4 + i, 8 * i + rank);
#pragma unroll 1
        for (int j = 0; j < 16 && i == 0;) {
            const ulonglong2 v = ld_tagged2(&g_ctx[((j >> 2) * 8 + rank) * 128 + (j & 3) * 32 + lane]);
            if (__all_sync(~0u, (unsigned)(v.x >> 32) == tag && (unsigned)(v.y >> 32) == tag)) {
                asm volatile("st.shared.v2.u32 [%0], {%1,%2};" ::"r"(sbase + F_X + (j >> 2) * FXP + ((j & 3) * 32 + lane) * 8), "r"((uint32_t)v.x), "r"((uint32_t)v.y) : "memory");
                j++;
            } else {
                __nanosleep(500);
                if (++n > SPIN_LIMIT) __trap();
            }
        }
    }
    __syncwarp();
    if (lane == 0) st_release_cta_shared(sbase + M_HELP + 32, 1u);
}
__device__ __forceinline__ void out_late(uint32_t sbase, int rank) {
    unsigned n = 0;
    while (ld_acquire_cta_shared(sbase + M_HELP + 32) == 0) { if (++n > (SPIN_LIMIT << 4)) __trap(); }
    while (ld_acquire(&g_vdone[24 + rank][0]) < 4 * UPP) { if (++n > SPIN_LIMIT) __trap(); }
    TS(12);
    out_fetch(sbase, 7, 24 + rank);
    __syncwarp();
    if ((threadIdx.x & 31) == 0) asm volatile("mbarrier.arrive.shared::cta.b64 _, [%0];" ::"r"(sbase + F_BAR + 72) : "memory");
    TS(13);
}
__device__ __forceinline__ void out_project(uint32_t sbase, int rank, int w) {
    const int lane = threadIdx.x & 31, g = lane >> 2, t = lane & 3;
    unsigned n = 0;
    while (ld_acquire_cta_shared(sbase + M_HELP + 32) == 0) { __nanosleep(500); if (++n > SPIN_LIMIT) __trap(); }
    asm volatile("barrier.cluster.wait.acquire.aligned;" ::: "memory");
    uint32_t rdst = mapa(sbase + F_RECV + rank * 128 + (g & 3) * 32 + t * 16, 2 * w + (g >> 2)), rbar = mapa(sbase + F_BAR, 2 * w + (g >> 2));
    while (ld_acquire_cta_shared(sbase + M_HELP + 28) == 0) { __nanosleep(200); if (++n > SPIN_LIMIT) __trap(); }
    const uint32_t da = (1u << 16) | (((sbase + F_W) & 0x3ffff) >> 4), db = (4u << 16) | (((sbase + F_X) & 0x3ffff) >> 4);
    float d[4] = {0.f, 0.f, 0.f, 0.f};
#pragma unroll
    for (int i = 0; i < 8; i++) {
        mbar_spin(sbase + F_BAR + 16 + i * 8);
        wgmma_tile(d, da + (i % 6) * 1024, db + i * (FXP / 16), i & 3);
        if (i < 2 || (i & 3) == 3) asm volatile("wgmma.wait_group.sync.aligned 0;" : "+f"(d[0]), "+f"(d[1]), "+f"(d[2]), "+f"(d[3])::"memory");
        if (i < 2) {
            asm volatile("{\n.reg .pred p;\nsetp.eq.u32 p, %1, 0;\n@p mbarrier.arrive.shared::cta.b64 _, [%0];\n}"
                         ::"r"(sbase + F_BAR + 80 + i * 8), "r"(lane) : "memory");
        } else if ((i & 3) == 3) {
            if (t < 2)
                asm volatile("st.async.weak.shared::cluster.mbarrier::complete_tx::bytes.v4.f32 [%0], {%1,%2,%3,%4}, [%5];"
                             ::"r"(rdst), "f"(d[0]), "f"(d[1]), "f"(d[2]), "f"(d[3]), "r"(rbar) : "memory");
            __syncwarp();
            rdst += 1024;
            rbar += 8;
            asm volatile("" : "+r"(rdst), "+r"(rbar));
        }
    }
}
__device__ __forceinline__ void out_issue_sum(const Params& p, uint32_t sbase, int c, int rank, uint64_t pol) {
    const int lane = threadIdx.x & 31;
    if (lane == 0) {
        unsigned n = 0;
        while (ld_acquire_cta_shared(sbase + M_HELP + 32) == 0) { __nanosleep(500); if (++n > SPIN_LIMIT) __trap(); }
        asm volatile("prefetch.tensormap [%0];" ::"l"(&p.tm_wf) : "memory");
        asm volatile("prefetch.tensormap [%0];" ::"l"(&p.tm_wl) : "memory");
        uint32_t t0;
        while ((t0 = ld_acquire_cta_shared(sbase + M_HELP + 28)) == 0) { __nanosleep(100); if (++n > SPIN_LIMIT) __trap(); }
#pragma unroll 1
        for (int i = 0; i < 8; i++) {
            const int h = (i & 3) * 8 + rank;
            if (i >= 6) mbar_wait(sbase + F_BAR + 32 + i * 8, 0);
            while ((int)(now_ns() - t0) < 0) {}
            if (i == 0) TS(16);
            tma3d(sbase + F_W + (i < 6 ? i : i - 6) * 16384, i < 4 ? &p.tm_wf : &p.tm_wl, i < 4 ? 0 : c * 64, i < 4 ? h * 128 : h * 16,
                  i < 4 ? c : 0, sbase + F_BAR + 16 + i * 8, pol);
            t0 += FP;
        }
        TS(17);
    }
    __syncwarp();
    __nv_bfloat16* dst = p.out + (((lane >> 1) & 2) + (lane & 1)) * (2 * DM) + DM + c * 64 + (rank >> 1) * 16 + (lane & 2) * 4 +
                         (rank & 1) * 4 + (lane >> 3);
    uint32_t src = sbase + F_RECV + lane * 4;
#pragma unroll 1
    for (int r = 0; r < 2; r++) {
        asm volatile("" : "+l"(dst), "+r"(src));
        mbar_spin_cluster(sbase + F_BAR + r * 8);
        float x[8];
#pragma unroll
        for (int i = 0; i < 8; i++) asm volatile("ld.shared.f32 %0, [%1];" : "=f"(x[i]) : "r"(src + i * 128) : "memory");
        const float v = ((x[0] + x[1]) + (x[2] + x[3])) + ((x[4] + x[5]) + (x[6] + x[7]));
        asm volatile("st.global.u16 [%0], %1;" ::"l"(dst), "h"((unsigned short)pack_bf16(v, 0.f)) : "memory");
        TS(14 + r);
        dst -= DM;
        src += 1024;
    }
}

constexpr int BS_WUK = 5, BS_Q = 9, BS_CKV = 11, BS_PART = 27, BS_WUV = 29, BS_END = 33;

__device__ __noinline__ void b_issue(const Params& p, int n, int bi, uint32_t sbase, uint64_t pol) {
    if (n >= BS_END || (n >= BS_Q && n < BS_CKV) || (n >= BS_PART && n < BS_WUV)) return;
    const uint32_t bar = sbase + M_BAR + (NSLOT + n % BRING) * 8;
    const CUtensorMap* tm;
    int row, panel = 2 * bi;
    if (n < BS_WUK) { tm = &p.tm_wq; row = n * 128; }
    else if (n < BS_Q) { tm = &p.tm_wuk; row = (n - BS_WUK) * 128; }
    else if (n < BS_PART) {
        tm = &p.tm_ckv; panel = 0;
        row = (bi >> 3) * SK + ((n - BS_CKV) * 8 + (bi & 7)) * 32;
    }
    else { tm = &p.tm_wuv; row = (n - BS_WUV) * 128; }
    mbar_expect_tx(bar, n == 0 ? 32768 + 4 * 1152 : 32768);
    tma3d(sbase + (n % BRING) * SLOT, tm, 0, row, panel, bar, pol);
}
__device__ __forceinline__ void b_issue_xchg(int n, const void* src, uint32_t sbase, uint64_t pol) {
    asm volatile("fence.proxy.async;" ::: "memory");
#pragma unroll
    for (int i = 0; i < 2; i++) {
        const uint32_t bar = sbase + M_BAR + (NSLOT + (n + i) % BRING) * 8;
        mbar_expect_tx(bar, 32768);
        bulk_load(sbase + ((n + i) % BRING) * SLOT, reinterpret_cast<const char*>(src) + i * 32768, 32768, bar, pol);
    }
}
__device__ __forceinline__ void b_wait(int n, uint32_t sbase) {
    mbar_wait(sbase + M_BAR + (NSLOT + n % BRING) * 8, (n / BRING) & 1);
}

__device__ __noinline__ void b_gemm(const Params& p, uint32_t sbase, int n0, int n1, int ktot, uint32_t xh, uint32_t xl, int pitch,
                                    int bi, uint64_t pol) {
    const int tid = threadIdx.x, warp = tid >> 5, lane = tid & 31, g = lane >> 2, t = lane & 3;
    const uint32_t woff = (warp >> 2) * 16384 + (lane & 15) * 128 + ((((warp & 3) * 2 + (lane >> 4)) ^ (lane & 7)) * 16);
    const uint32_t xoff = (g & 3) * pitch + t * 4;
    float acc[2][4];
#pragma unroll
    for (int i = 0; i < 8; i++) acc[i >> 2][i & 3] = 0.f;
#pragma unroll 1
    for (int n = n0; n < n1; n++) {
        b_wait(n, sbase);
        const uint32_t slot = sbase + (n % BRING) * SLOT + woff;
        const int k0 = (n - n0) * 128;
        const int ns = min(8, (ktot - k0) >> 4);
#pragma unroll 2
        for (int s = 0; s < ns; s++) {
            uint32_t a[4], w[4];
            const uint32_t xo = xoff + (k0 + 16 * s) * 2;
            a[0] = lds32(xh + xo); a[2] = lds32(xh + xo + 16);
            a[1] = xl ? lds32(xl + xo) : 0u; a[3] = xl ? lds32(xl + xo + 16) : 0u;
            ldsm4t(w, slot + s * 2048);
            mma16816(acc[0], a, w[0], w[1]);
            mma16816(acc[1], a, w[2], w[3]);
        }
        __syncthreads();
        if (tid == 0) b_issue(p, n + BD, bi, sbase, pol);
    }
    if (g < 4) {
#pragma unroll
        for (int j = 0; j < 2; j++)
            asm volatile("st.shared.u32 [%0], %1;" ::"r"(sbase + M_QB + g * QP + (warp * 16 + j * 8 + t * 2) * 2),
                         "r"(pack_bf16(acc[j][0] + acc[j][2], acc[j][1] + acc[j][3])) : "memory");
    }
    __syncthreads();
}

__device__ __forceinline__ void b_exchange(unsigned* c, int n, const void* src, uint32_t sbase, uint64_t pol) {
    TS(n == BS_Q ? 24 : 28);
    __syncthreads();
    if (threadIdx.x == 0) {
        TS(n == BS_Q ? 25 : 29);
        fence_gpu();
        TS(n == BS_Q ? 26 : 30);
        red_add_u32(c, 1u);
        wait_count(c, NBCTA);
        TS(n == BS_Q ? 27 : 31);
        b_issue_xchg(n, src, sbase, pol);
    }
}

template <bool CLU>
__device__ __noinline__ void b_chain(const Params& p, char* smem, uint32_t sbase, int bi, unsigned epoch, uint64_t pol) {
    const int tid = threadIdx.x, warp = tid >> 5, lane = tid & 31, g = lane >> 2, t = lane & 3;
    unsigned (*ctl)[32] = g_ctl[epoch & 1];
    float* red = reinterpret_cast<float*>(smem + 5 * SLOT);
    __syncthreads();
    b_gemm(p, sbase, 0, BS_WUK, DM, sbase + M_XB, 0, XP, bi, pol);
    TS(6);
    {
        uint32_t Q[16];
#pragma unroll
        for (int c = 0; c < 16; c++) Q[c] = lds32(sbase + M_QB + (g & 3) * QP + c * 16 + t * 4);
        float* qa = reinterpret_cast<float*>(smem + M_QA);
#pragma unroll 1
        for (int n = BS_WUK; n < BS_Q; n++) {
            b_wait(n, sbase);
            const uint32_t base = sbase + (n % BRING) * SLOT + (warp * 16 + (lane & 15)) * 128;
            float d[2][4];
#pragma unroll
            for (int i = 0; i < 8; i++) d[i >> 2][i & 3] = 0.f;
#pragma unroll
            for (int s = 0; s < 8; s++) {
                uint32_t a[4];
                ldsm4(a, base + (s >> 2) * 16384 + (((2 * (s & 3) + (lane >> 4)) ^ (lane & 7)) * 16));
                mma16816(d[s & 1], a, Q[2 * s], Q[2 * s + 1]);
            }
            const int c = (n - BS_WUK) * 128 + warp * 16 + g + 8 * (t >> 1);
            qa[(2 * (t & 1)) * 512 + c] = (t & 2) ? d[0][2] + d[1][2] : d[0][0] + d[1][0];
            qa[(2 * (t & 1) + 1) * 512 + c] = (t & 2) ? d[0][3] + d[1][3] : d[0][1] + d[1][1];
            __syncthreads();
            if (tid == 0) b_issue(p, n + BD, bi, sbase, pol);
        }
#pragma unroll 1
        for (int r = 0; r < 2; r++) {
            const int id = tid + r * 256;
            const int b = id >> 7, c0 = ((id >> 2) & 31) * 16 + (id & 3) * 2;
            const float2 u0 = *reinterpret_cast<const float2*>(qa + b * 512 + c0);
            const float2 u1 = *reinterpret_cast<const float2*>(qa + b * 512 + c0 + 8);
            const uint32_t h0 = pack_bf16(u0.x, u0.y), h1 = pack_bf16(u1.x, u1.y);
            const uint32_t l0 = pack_bf16(u0.x - bf_lo(h0), u0.y - bf_hi(h0)), l1 = pack_bf16(u1.x - bf_lo(h1), u1.y - bf_hi(h1));
            g_qabs[((id >> 2) * 4 + (bi >> 3)) * 32 + (bi & 7) * 4 + (id & 3)] = make_uint4(h0, l0, h1, l1);
        }
    }
    b_exchange(&ctl[C_BBAR][0], BS_Q, &g_qabs[(bi >> 3) * 4096], sbase, pol);
    {
        uint32_t qf[4][4][4];
        b_wait(BS_Q + (warp >> 2), sbase);
        TS(7);
        {
            const uint4* qs = reinterpret_cast<const uint4*>(smem + ((BS_Q + (warp >> 2)) % BRING) * SLOT) + (warp & 3) * 512 + lane;
#pragma unroll
            for (int s = 0; s < 4; s++)
#pragma unroll
                for (int i = 0; i < 4; i++) {
                    const uint4 v = qs[(s * 4 + i) * 32];
                    qf[i][s][0] = v.x; qf[i][s][1] = v.y; qf[i][s][2] = v.z; qf[i][s][3] = v.w;
                }
        }
        __syncthreads();
        if (tid == 0) { b_issue(p, BS_Q + BD, bi, sbase, pol); b_issue(p, BS_Q + 1 + BD, bi, sbase, pol); }
        float acc[2][8][4];
#pragma unroll
        for (int i = 0; i < 2; i++)
#pragma unroll
            for (int j = 0; j < 8; j++) { acc[i][j][0] = acc[i][j][1] = acc[i][j][2] = acc[i][j][3] = 0.f; }
        float mrun = -INFINITY, lrun = 0.f;
        const int head = tid >> 3, kq = tid & 7;
        float* alpha = reinterpret_cast<float*>(smem + M_ALPHA);
        for (int n = BS_CKV; n < BS_PART; n++) {
            b_wait(n, sbase);
            const uint32_t slot = sbase + (n % BRING) * SLOT;
            float sc[4][4][4];
#pragma unroll
            for (int i = 0; i < 4; i++)
#pragma unroll
                for (int j = 0; j < 4; j++) { sc[i][j][0] = sc[i][j][1] = sc[i][j][2] = sc[i][j][3] = 0.f; }
#pragma unroll
            for (int j = 0; j < 4; j++)
#pragma unroll
                for (int sp = 0; sp < 2; sp++) {
                    uint32_t bf[4];
                    ldsm4(bf, slot + warp * 4096 + (8 * j + (lane & 7)) * 128 + (((4 * sp + (lane >> 3)) ^ (lane & 7)) * 16));
#pragma unroll
                    for (int i = 0; i < 4; i++) {
                        mma16816(sc[i][j], qf[i][2 * sp], bf[0], bf[1]);
                        mma16816(sc[i][j], qf[i][2 * sp + 1], bf[2], bf[3]);
                    }
                }
#pragma unroll
            for (int i = 0; i < 4; i++)
#pragma unroll
                for (int j = 0; j < 4; j++)
                    *reinterpret_cast<float2*>(red + warp * 1024 + (8 * i + g) * 32 + ((8 * j) ^ (8 * (g & 3))) + 2 * t) =
                        make_float2(sc[i][j][0] + sc[i][j][2], sc[i][j][1] + sc[i][j][3]);
            __syncthreads();
            if (tid == 0 && n > BS_CKV) b_issue(p, n - 1 + BD, bi, sbase, pol);
            {
                float4 s = make_float4(0.f, 0.f, 0.f, 0.f);
#pragma unroll
                for (int w = 0; w < 8; w++) {
                    const float4 v = *reinterpret_cast<const float4*>(red + w * 1024 + head * 32 + ((4 * kq) ^ (8 * (head & 3))));
                    s.x += v.x; s.y += v.y; s.z += v.z; s.w += v.w;
                }
                const uint32_t r0 = pack_bf16(s.x, s.y), r1 = pack_bf16(s.z, s.w);
                const uint32_t s0 = pack_bf16(bf_lo(r0) * SCALE, bf_hi(r0) * SCALE);
                const uint32_t s1 = pack_bf16(bf_lo(r1) * SCALE, bf_hi(r1) * SCALE);
                const float f0 = bf_lo(s0), f1 = bf_hi(s0), f2 = bf_lo(s1), f3 = bf_hi(s1);
                float mx = fmaxf(fmaxf(f0, f1), fmaxf(f2, f3));
                mx = fmaxf(mx, __shfl_xor_sync(~0u, mx, 1));
                mx = fmaxf(mx, __shfl_xor_sync(~0u, mx, 2));
                mx = fmaxf(mx, __shfl_xor_sync(~0u, mx, 4));
                const float mnew = fmaxf(mrun, mx);
                const float al = expsub(mrun, mnew);
                const float p0 = expsub(f0, mnew), p1 = expsub(f1, mnew), p2 = expsub(f2, mnew), p3 = expsub(f3, mnew);
                lrun = lrun * al + ((p0 + p1) + (p2 + p3));
                mrun = mnew;
                *reinterpret_cast<uint2*>(smem + M_P + head * 80 + kq * 8) = make_uint2(pack_bf16(p0, p1), pack_bf16(p2, p3));
                if (kq == 0) alpha[head] = al;
            }
            __syncthreads();
            {
                uint32_t pf[2][2][4];
#pragma unroll
                for (int i = 0; i < 2; i++)
#pragma unroll
                    for (int ks = 0; ks < 2; ks++)
                        ldsm4(pf[i][ks], sbase + M_P + (16 * i + (lane & 15)) * 80 + (16 * ks + 8 * (lane >> 4)) * 2);
#pragma unroll
                for (int i = 0; i < 2; i++) {
                    const float a0 = alpha[16 * i + g], a1 = alpha[16 * i + 8 + g];
#pragma unroll
                    for (int j = 0; j < 8; j++) { acc[i][j][0] *= a0; acc[i][j][1] *= a0; acc[i][j][2] *= a1; acc[i][j][3] *= a1; }
                }
#pragma unroll
                for (int j = 0; j < 8; j++) {
                    uint32_t bf[4];
                    ldsm4t(bf, slot + warp * 4096 + lane * 128 + ((j ^ (lane & 7)) * 16));
#pragma unroll
                    for (int i = 0; i < 2; i++) {
                        mma16816(acc[i][j], pf[i][0], bf[0], bf[1]);
                        mma16816(acc[i][j], pf[i][1], bf[2], bf[3]);
                    }
                }
            }
        }
        __syncthreads();
        if (tid == 0) b_issue(p, BS_PART - 1 + BD, bi, sbase, pol);
        lrun += __shfl_xor_sync(~0u, lrun, 1);
        lrun += __shfl_xor_sync(~0u, lrun, 2);
        lrun += __shfl_xor_sync(~0u, lrun, 4);
        if (kq == 0) g_bml[head * NBCTA + bi] = make_float2(mrun, lrun);
#pragma unroll
        for (int i = 0; i < 2; i++)
#pragma unroll
            for (int j = 0; j < 8; j++) {
                g_bpart[((16 * i + g) * NBCTA + bi) * 256 + warp * 32 + j * 4 + t] = make_float2(acc[i][j][0], acc[i][j][1]);
                g_bpart[((16 * i + 8 + g) * NBCTA + bi) * 256 + warp * 32 + j * 4 + t] = make_float2(acc[i][j][2], acc[i][j][3]);
            }
    }
#pragma unroll 1
    for (int i = tid; i < NH * 36 && !(CLU); i += 256) g_outb[bi * NH * 36 + i] = make_uint4(0u, epoch, 0u, epoch);
    b_exchange(&ctl[C_BBAR + 1][0], BS_PART, &g_bpart[bi * NBCTA * 256], sbase, pol);
    {
        float* omega = reinterpret_cast<float*>(smem + M_OMEGA);
        if (warp == 0) {
            __syncwarp();
            const uint2 ml = ld_relaxed8(&g_bml[bi * NBCTA + lane]);
            const float ms = __uint_as_float(ml.x);
            float m = ms;
            m = fmaxf(m, __shfl_xor_sync(~0u, m, 1));
            m = fmaxf(m, __shfl_xor_sync(~0u, m, 2));
            m = fmaxf(m, __shfl_xor_sync(~0u, m, 4));
            const float w = expsub(ms, m);
            float l = w * __uint_as_float(ml.y);
            l += __shfl_xor_sync(~0u, l, 1);
            l += __shfl_xor_sync(~0u, l, 2);
            l += __shfl_xor_sync(~0u, l, 4);
            omega[lane] = w / l;
        }
        __syncthreads();
        b_wait(BS_PART, sbase);
        b_wait(BS_PART + 1, sbase);
#pragma unroll 1
        for (int b = 0; b < 4; b++) {
            const float2* ps = reinterpret_cast<const float2*>(smem + ((BS_PART + (b >> 1)) % BRING) * SLOT) + (b & 1) * 2048 + tid;
            float c0 = 0.f, c1 = 0.f;
#pragma unroll
            for (int s = 0; s < 8; s++) {
                const float w = omega[b * 8 + s];
                const float2 v = ps[s * 256];
                c0 = fmaf(w, v.x, c0);
                c1 = fmaf(w, v.y, c1);
            }
            const uint32_t hi = pack_bf16(c0, c1);
            *reinterpret_cast<uint32_t*>(smem + M_CH + b * CP + tid * 4) = hi;
            *reinterpret_cast<uint32_t*>(smem + M_CL + b * CP + tid * 4) = pack_bf16(c0 - bf_lo(hi), c1 - bf_hi(hi));
        }
        __syncthreads();
        if (tid == 0) { b_issue(p, BS_PART + BD, bi, sbase, pol); b_issue(p, BS_PART + 1 + BD, bi, sbase, pol); }
    }
    b_gemm(p, sbase, BS_WUV, BS_END, 512, sbase + M_CH, sbase + M_CL, CP, bi, pol);
    TS(12);
    if (CLU) {
        if (tid < 128) {
            const uint32_t xo = sbase + M_QB + ((tid >> 1) & 3) * QP + (tid >> 3) * 16 + (tid & 1) * 8;
            st_tagged2(&g_ctx[bi * 128 + tid], __uint_as_float(lds32(xo)), __uint_as_float(lds32(xo + 4)), epoch + 1);
        }
        return;
    }
    if (tid == 0) {
#pragma unroll 1
        for (int i = 0; i < 4; i++) {
            mbar_expect_tx(sbase + M_BAR + i * 8, 36864);
            tma3d(sbase + i * 36864, &p.tm_wo, 0, bi * 128 + i * 32, 0, sbase + M_BAR + i * 8, pol);
        }
    }
    TS(8);
    {
        float acc[9][4];
#pragma unroll
        for (int j = 0; j < 9; j++) { acc[j][0] = acc[j][1] = acc[j][2] = acc[j][3] = 0.f; }
#pragma unroll 1
        for (int i = 0; i < 4; i++) {
            const uint32_t xo = sbase + M_QB + (g & 3) * QP + i * 64 + t * 4;
            const uint32_t a0[4] = {lds32(xo), 0u, lds32(xo + 16), 0u}, a1[4] = {lds32(xo + 32), 0u, lds32(xo + 48), 0u};
            mbar_wait(sbase + M_BAR + i * 8, 0);
#pragma unroll
            for (int j = 0; j < 9; j++) {
                const int nt = warp * 9 + j;
                uint32_t w[4];
                ldsm4t(w, sbase + i * 36864 + (nt >> 3) * 4096 + lane * 128 + (((nt & 7) ^ (lane & 7)) * 16));
                mma16816(acc[j], a0, w[0], w[1]);
                mma16816(acc[j], a1, w[2], w[3]);
            }
        }
        if (g < 4) {
#pragma unroll
            for (int j = 0; j < 9; j++) {
                const int c2 = (warp * 9 + j) * 4 + t;
                st_tagged2(&g_outb[((c2 / 9) * NH + bi) * 36 + g * 9 + c2 % 9], acc[j][0], acc[j][1], epoch + 1);
            }
        }
    }
    TS(9);
    {
        const uint4* src = g_outb + (bi * NH + (tid >> 3)) * 36 + (tid & 7);
        float2* part = reinterpret_cast<float2*>(red);
        unsigned n = 0;
        while (true) {
            ulonglong2 v[5];
            bool ok = true;
#pragma unroll
            for (int i = 0; i < 5; i++)
                if (i < 4 || (tid & 7) < 4) v[i] = ld_tagged2(src + i * 8);
#pragma unroll
            for (int i = 0; i < 5; i++)
                if (i < 4 || (tid & 7) < 4) {
                    ok = ok && (unsigned)(v[i].x >> 32) == epoch + 1 && (unsigned)(v[i].y >> 32) == epoch + 1;
                    part[(tid >> 3) * 36 + (tid & 7) + i * 8] = make_float2(__uint_as_float((unsigned)v[i].x), __uint_as_float((unsigned)v[i].y));
                }
            if (ok) break;
            __nanosleep(400);
            if (++n > SPIN_LIMIT) __trap();
        }
        __syncthreads();
        if (tid < 36) {
            float s0 = 0.f, s1 = 0.f;
#pragma unroll 8
            for (int h = 0; h < NH; h++) { const float2 v = part[h * 36 + tid]; s0 += v.x; s1 += v.y; }
            *reinterpret_cast<uint32_t*>(p.out + (tid / 9) * 2 * DM + DM + bi * 18 + (tid % 9) * 2) = pack_bf16(s0, s1);
        }
    }
    TS(10);
}

template <bool CLU>
__global__ void __launch_bounds__(256, 1) fused_decode_kernel(const __grid_constant__ Params p) {
    extern __shared__ __align__(1024) char smem_raw[];
    const uint32_t sbase = (smem_u32(smem_raw) + 1023u) & ~1023u;
    char* smem = smem_raw + (sbase - smem_u32(smem_raw));
    const int tid = threadIdx.x, warp = tid >> 5, lane = tid & 31;
    const int blk = blockIdx.x;
    const bool isB = CLU ? blk < NBCTA : (blk & 3) == 0 && (blk >> 2) < NBCTA;
    const int bi = CLU ? blk : blk >> 2;
    const int nb = CLU ? blk - NBCTA : blk - min(NBCTA, (blk + 3) >> 2);
    const int nnb = gridDim.x - NBCTA;
    const int nstatic = nnb * (NW + XW);
    uint64_t pol;
    asm volatile("createpolicy.fractional.L2::evict_first.b64 %0, 1.0;" : "=l"(pol));
    const uint32_t wbar = sbase + M_BAR + warp * 8, wslot = sbase + warp * SLOT;
    const int u0 = warp * nnb + nb;
    const bool hold = ((blk >> 2) >> KMIN << KMIN) * 4 * UPP < nstatic;
    const uint32_t jbar = sbase + M_BAR + (NSLOT + BRING) * 8;
    if (warp == 7) {
        if (lane == 0 && blk < 128) {
            mbar_init(jbar, 1);
            asm volatile("fence.mbarrier_init.release.cluster;" ::: "memory");
            uint64_t poln;
            asm volatile("createpolicy.fractional.L2::evict_normal.b64 %0, 1.0;" : "=l"(poln));
            mbar_expect_tx(jbar, 36864 + 4 * 1152);
            tma3d(sbase + J0W, &p.tm_j0, blk * 32, 0, 0, jbar, poln);
            bulk_load(sbase + M_XA, p.xa, 4608, jbar, poln);
        }
        if (lane < 16) reinterpret_cast<unsigned*>(smem + M_HELP)[lane] = 0;
        __syncwarp();
        if (!isB) asm volatile("bar.arrive 2, %0;" ::"n"(32 * (NW + XW + 1)) : "memory");
    }
    if (warp < 4 && lane == 0) {
        mbar_init(wbar, 1);
        if (CLU && warp == 3 && !isB) {
#pragma unroll
            for (int i = 0; i < 2; i++) {
                mbar_init(sbase + F_BAR + i * 8, 1);
                mbar_expect_tx(sbase + F_BAR + i * 8, 1024);
            }
        }
        asm volatile("fence.mbarrier_init.release.cluster;" ::: "memory");
        if (warp < NEARLY && !isB && !hold) {
            mbar_expect_tx(wbar, TILE_BYTES);
            bulk_load(wslot, block_src(p.kc, unit_block<CLU>(u0)), TILE_BYTES, wbar, pol);
        }
    }
    unsigned epoch = 0;
    if (lane == 0) epoch = ld_relaxed4(&g_epoch);
    TS(0);
    if (CLU && !isB) asm volatile("barrier.cluster.arrive.relaxed.aligned;" ::: "memory");
    if ((warp >> 1) == 2 && blk < 128) st_relaxed64(&g_qll[((tid - 128) >> 4) * 2048 + blk * 16 + (tid & 15)], 0ull);
    if (isB || warp >= NW + XW) epoch = __shfl_sync(~0u, epoch, 0);
    if (isB && warp == 3) asm volatile("bar.sync 1, 160;" ::: "memory");
    if (isB && tid == 96) {
#pragma unroll 1
        for (int i = 0; i < BRING; i++) mbar_init(sbase + M_BAR + (NSLOT + i) * 8, 1);
        asm volatile("fence.mbarrier_init.release.cluster;" ::: "memory");
        if (hold) { unsigned n = 0; while (ld_acquire_cta_shared(sbase + M_HELP + 24) < 2) { if (++n > (SPIN_LIMIT << 4)) __trap(); } }
#pragma unroll 1
        for (int b = 0; b < 4; b++) bulk_load(sbase + M_XB + b * XP, p.xb + b * DM, 1152, sbase + M_BAR + NSLOT * 8, pol);
#pragma unroll 1
        for (int n = 0; n < BD; n++) b_issue(p, n, bi, sbase, pol);
    }
    if (warp >= 4 && blk < 128) {
        const int g = lane >> 2, t = lane & 3, j = tid - 128;
        asm volatile("bar.sync 1, %0;" ::"r"(isB ? 160 : 128) : "memory");
#pragma unroll 1
        for (int sl = blk, ph = 0;; sl += 128 - gridDim.x, ph = 1) {
        mbar_wait(jbar, ph);
        TS(13);
        float acc[4][4];
#pragma unroll
        for (int i = 0; i < 16; i++) acc[i >> 2][i & 3] = 0.f;
        const uint32_t wa = sbase + J0W + ((warp - 4) * 144 + (lane & 15)) * 64;
        const uint32_t sw = (lane >> 1) & 3, xa = sbase + M_XA + (g & 3) * 1152 + (warp - 4) * 288 + t * 4;
#pragma unroll 3
        for (int s = 0; s < 9; s++) {
            const uint32_t a[4] = {lds32(xa + s * 32), 0u, lds32(xa + s * 32 + 16), 0u};
            uint32_t w0[4], w1[4];
            ldsm4t(w0, wa + s * 1024 + (((lane >> 4) ^ sw) * 16));
            ldsm4t(w1, wa + s * 1024 + (((2 + (lane >> 4)) ^ sw) * 16));
            mma16816(acc[0], a, w0[0], w0[1]);
            mma16816(acc[1], a, w0[2], w0[3]);
            mma16816(acc[2], a, w1[0], w1[1]);
            mma16816(acc[3], a, w1[2], w1[3]);
        }
        float2* j0 = reinterpret_cast<float2*>(smem + M_J0);
        if (g < 4) {
#pragma unroll
            for (int i = 0; i < 4; i++) j0[(warp - 4) * 64 + g * 16 + i * 4 + t] = make_float2(acc[i][0], acc[i][1]);
        }
        asm volatile("bar.sync 1, 128;" ::: "memory");
        const bool again = sl == blk && blk + 128 - (int)gridDim.x >= (int)gridDim.x;
        if (again && tid == 224) {
            mbar_expect_tx(jbar, 36864);
            tma3d(sbase + J0W, &p.tm_j0, (blk + 128 - gridDim.x) * 32, 0, 0, jbar, pol);
        }
        if (warp < 6) {
            const float2 v0 = j0[j], v1 = j0[64 + j], v2 = j0[128 + j], v3 = j0[192 + j];
            st_relaxed64(&g_qll[(j >> 4) * 2048 + sl * 16 + (j & 15)],
                         (unsigned long long)pack_bf16((v0.x + v1.x) + (v2.x + v3.x), (v0.y + v1.y) + (v2.y + v3.y)) |
                             ((unsigned long long)(epoch + 1) << 32));
            __syncwarp();
            if (lane == 0) asm volatile("red.relaxed.cta.shared::cta.add.u32 [%0], 1;" ::"r"(sbase + M_HELP + 24) : "memory");
        } else if (warp == 7) {
            if (blk < C_LINES) g_ctl[(epoch & 1) ^ 1][blk][lane] = 0;
        }
        TS(1);
        if (!again) break;
        asm volatile("bar.sync 1, 128;" ::: "memory");
        }
    }
    if (isB) {
        b_chain<CLU>(p, smem, sbase, bi, epoch, pol);
        return;
    }
    if (warp < NW + XW) {
        a_worker<CLU>(p, u0, warp >= NW + ((nb & 3) < (CLU ? X3C : X3) ? 1 : 0), warp < NEARLY && !hold, hold, nstatic, wslot, wbar, sbase + M_HELP, epoch, pol);
        if (CLU && nb < NFIN) {
            if (warp == 3) out_issue_sum(p, sbase, nb >> 3, nb & 7, pol);
            else if (warp == 0) out_late(sbase, nb & 7);
        }
        return;
    } else if (warp == 7) {
#pragma unroll 1
        for (int i = nb; i < 4 * NH; i += nnb) g_oacc[i * 32 + lane] = make_float4(0.f, 0.f, 0.f, 0.f);
        if (nb < NREP * NH) g_vdone[nb][lane] = 0;
        __syncwarp();
        k_helper(sbase + M_HELP, epoch);
        if (nb == 0 && lane == 0) g_epoch = epoch + 1;
        __syncwarp();
        if (CLU && nb < NFIN) out_early(sbase, nb & 7, epoch + 1);
    } else if (CLU) {
    } else if (warp == 6 && nb < NFIN) {
        finisher(p, sbase, nb);
        TS(4);
    } else if (warp >= 6 - NPOLL && nb < NFIN) {
        v_poller(sbase, nb, warp - (6 - NPOLL));
    }
    if (CLU && nb < NFIN) out_project(sbase, nb & 7, warp - 4);
}

}

typedef CUresult (*EncodeFn)(CUtensorMap*, CUtensorMapDataType, cuuint32_t, void*, const cuuint64_t*, const cuuint64_t*,
                             const cuuint32_t*, const cuuint32_t*, CUtensorMapInterleave, CUtensorMapSwizzle,
                             CUtensorMapL2promotion, CUtensorMapFloatOOBfill);

extern "C" void kernel_launch(void* const* d_in, const int* in_sizes, int n_in, void* d_out, int out_size) {
    (void)in_sizes; (void)n_in; (void)out_size;
    static int nsm = 0, ncl = 0;
    static EncodeFn encode = nullptr;
    cudaLaunchConfig_t cfg = {};
    cudaLaunchAttribute at[1];
    at[0].id = cudaLaunchAttributeClusterDimension;
    at[0].val.clusterDim.x = 8; at[0].val.clusterDim.y = 1; at[0].val.clusterDim.z = 1;
    cfg.blockDim = dim3(256); cfg.dynamicSmemBytes = SMEM_BYTES; cfg.stream = cudaStreamPerThread; cfg.attrs = at; cfg.numAttrs = 1;
    if (nsm == 0) {
        int dev = 0;
        cudaGetDevice(&dev);
        cudaDeviceGetAttribute(&nsm, cudaDevAttrMultiProcessorCount, dev);
        cudaFuncSetAttribute(fused_decode_kernel<false>, cudaFuncAttributeMaxDynamicSharedMemorySize, SMEM_BYTES);
        cudaFuncSetAttribute(fused_decode_kernel<true>, cudaFuncAttributeMaxDynamicSharedMemorySize, SMEM_BYTES);
        cfg.gridDim = dim3(128);
        if (cudaOccupancyMaxActiveClusters(&ncl, fused_decode_kernel<true>, &cfg) != cudaSuccess) { ncl = 0; (void)cudaGetLastError(); }
        if (ncl > MINCL) ncl = MINCL;
        void* fn = nullptr;
        cudaDriverEntryPointQueryResult qr;
        cudaGetDriverEntryPoint("cuTensorMapEncodeTiled", &fn, cudaEnableDefault, &qr);
        encode = (EncodeFn)fn;
    }
    Params p;
    auto panels = [&](CUtensorMap* tm, void* ptr, int rows, int cols, int box_rows, int box_panels) {
        const cuuint64_t gd[3] = {64, (cuuint64_t)rows, (cuuint64_t)(cols / 64)}, gs[2] = {(cuuint64_t)cols * 2, 128};
        const cuuint32_t box[3] = {64, (cuuint32_t)box_rows, (cuuint32_t)box_panels}, es[3] = {1, 1, 1};
        encode(tm, CU_TENSOR_MAP_DATA_TYPE_BFLOAT16, 3, ptr, gd, gs, box, es, CU_TENSOR_MAP_INTERLEAVE_NONE,
               CU_TENSOR_MAP_SWIZZLE_128B, CU_TENSOR_MAP_L2_PROMOTION_L2_256B, CU_TENSOR_MAP_FLOAT_OOB_FILL_NONE);
    };
    panels(&p.tm_wq, d_in[7], DM, 4096, 128, 2);
    panels(&p.tm_wuk, d_in[8], 512, 4096, 128, 2);
    panels(&p.tm_wuv, d_in[9], 512, 4096, 128, 2);
    panels(&p.tm_wo, d_in[10], 4096, DM, 32, 9);
    panels(&p.tm_wf, d_in[10], 4096, DM, 128, 1);
    panels(&p.tm_ckv, d_in[6], 4 * SK, 512, 32, 8);
    {
        const cuuint64_t gd[3] = {4096, 192, 3}, gs[2] = {8192, 192 * 8192};
        const cuuint32_t box[3] = {32, 192, 3}, es[3] = {1, 1, 1};
        encode(&p.tm_j0, CU_TENSOR_MAP_DATA_TYPE_BFLOAT16, 3, d_in[3], gd, gs, box, es, CU_TENSOR_MAP_INTERLEAVE_NONE,
               CU_TENSOR_MAP_SWIZZLE_64B, CU_TENSOR_MAP_L2_PROMOTION_L2_128B, CU_TENSOR_MAP_FLOAT_OOB_FILL_NONE);
    }
    {
        const cuuint64_t gd[3] = {DM, 512, 8}, gs[2] = {8 * DM * 2, DM * 2};
        const cuuint32_t box[3] = {64, 16, 8}, es[3] = {1, 1, 1};
        encode(&p.tm_wl, CU_TENSOR_MAP_DATA_TYPE_BFLOAT16, 3, d_in[4], gd, gs, box, es, CU_TENSOR_MAP_INTERLEAVE_NONE,
               CU_TENSOR_MAP_SWIZZLE_128B, CU_TENSOR_MAP_L2_PROMOTION_L2_256B, CU_TENSOR_MAP_FLOAT_OOB_FILL_NONE);
    }
    p.xa = (const __nv_bfloat16*)d_in[0];
    p.kc = (const __nv_bfloat16*)d_in[1];
    p.vc = (const __nv_bfloat16*)d_in[2];
    p.wo = (const __nv_bfloat16*)d_in[4];
    p.xb = (const __nv_bfloat16*)d_in[5];
    p.wob = (const __nv_bfloat16*)d_in[10];
    p.out = (__nv_bfloat16*)d_out;
    if (ncl >= MINCL) {
        cfg.gridDim = dim3(8 * ncl);
        cudaLaunchKernelEx(&cfg, fused_decode_kernel<true>, p);
    } else {
        fused_decode_kernel<false><<<nsm, 256, SMEM_BYTES, cudaStreamPerThread>>>(p);
    }
}
```

```cpp
#include <cuda_runtime.h>
#include <cuda.h>
#include <cuda_bf16.h>
#include <stdint.h>

namespace {

constexpr int NH = 32, SK = 4096, DM = 576;
constexpr int KEYS = 128;
constexpr int UPP = SK / KEYS;
constexpr int NUK = 4 * NH * UPP;
constexpr int TILE_BYTES = KEYS * 256;
#define NWORK 2
constexpr int NW = NWORK;
constexpr int NBCTA = 32;
constexpr int MINCL = 15;
constexpr int NFIN = 72;
constexpr int SLOT = 32768;
constexpr int NSLOT = 6;
constexpr int BRING = 5;
constexpr int J0W = 5 * SLOT;
constexpr int MISC = NSLOT * SLOT + 4096;
constexpr int XP = 1168, CP = 1040, QP = 272;
constexpr int M_XA = MISC;
constexpr int M_XB = M_XA + 4 * XP;
constexpr int M_CH = M_XB + 4 * XP;
constexpr int M_CL = M_CH + 4 * CP;
constexpr int M_QB = M_CL + 4 * CP;
constexpr int M_QA = M_CH;
constexpr int M_J0 = M_QB + 4 * QP;
constexpr int M_P = M_J0 + 2048;
constexpr int M_ALPHA = M_P + 2560;
constexpr int M_OMEGA = M_ALPHA + 128;
constexpr int M_BAR = M_OMEGA + 128;
constexpr int M_HELP = M_BAR + 128;
constexpr int F_W = 3 * SLOT;
constexpr int F_X = NSLOT * SLOT, FXP = 1088;
constexpr int F_RECV = F_X + 8 * FXP;
constexpr int F_BAR = M_P;
constexpr int SMEM_BYTES = M_HELP + 128 + 1024;
static_assert(F_RECV + 2048 <= M_J0, "output phase layout");
static_assert(SMEM_BYTES <= 232448 && M_BAR % 8 == 0 && M_QA % 16 == 0 && M_P % 16 == 0, "smem layout");
#define XW 2
#define X3 1
#define X3C 2
#define NEARLY 2
#define BD 4
#define FPF 3
#define FSLEEP 800
#define VMINC 2
#define FJ 270
#define FP 384
#define NPOLL 2
#define PGAP 200
static_assert(NW + XW == 4 && 4 % NEARLY == 0 && BD <= BRING, "slots 4 and 5 hold the finisher weights");
constexpr int KMIN = 2, KMAX = 4, VMAX = 4;
constexpr float SCALE = 0.08838834764831845f;
constexpr float LOG2E = 1.4426950408889634f;
constexpr unsigned SPIN_LIMIT = 1u << 24;

#define NREP 2
constexpr int C_QUEUE = 0, C_KDONE = 1, C_BBAR = 3, C_LINES = 5;

struct First { const char* ptr[4]; };
struct Params {
    const __nv_bfloat16 *kc, *xa, *vc, *wo, *xb, *wob;
    __nv_bfloat16* out;
    CUtensorMap tm_j0;
    CUtensorMap tm_wq, tm_wuk, tm_ckv, tm_wuv, tm_wo;
    CUtensorMap tm_wl;
    CUtensorMap tm_wf;
};

__device__ unsigned g_epoch;
__device__ unsigned g_ctl[2][C_LINES][32];
__device__ uint2 g_qll[4 * 2048];
__device__ uint2 g_scores[128 * SK / 4];
__device__ float2 g_stats[128 * UPP];
__device__ float4 g_oacc[128 * 32];
__device__ unsigned g_vdone[NREP * NH][32];
__device__ uint4 g_qabs[4 * 8 * 4 * 4 * 32];
__device__ float2 g_bpart[NBCTA * NH * 256];
__device__ float2 g_bml[NBCTA * NH];
__device__ uint4 g_ctx[NH * 128];
__device__ uint4 g_outb[NBCTA * NH * 36];

#define TS(i)
#define TSV(i, v)
#define LAND(i)
#define CLK(x)
#define ACC(a, x, y)

__device__ __forceinline__ uint32_t smem_u32(const void* p) { return (uint32_t)__cvta_generic_to_shared(p); }
__device__ __forceinline__ void mbar_init(uint32_t bar, uint32_t cnt) {
    asm volatile("mbarrier.init.shared::cta.b64 [%0], %1;" ::"r"(bar), "r"(cnt) : "memory");
}
__device__ __forceinline__ void mbar_expect_tx(uint32_t bar, uint32_t bytes) {
    asm volatile("mbarrier.arrive.expect_tx.shared::cta.b64 _, [%0], %1;" ::"r"(bar), "r"(bytes) : "memory");
}
__device__ __forceinline__ bool mbar_try(uint32_t bar, uint32_t parity) {
    uint32_t ok;
    asm volatile("{\n.reg .pred p;\nmbarrier.try_wait.parity.shared::cta.b64 p, [%1], %2;\nselp.u32 %0, 1, 0, p;\n}\n"
                 : "=r"(ok) : "r"(bar), "r"(parity) : "memory");
    return ok;
}
__device__ __forceinline__ void mbar_wait(uint32_t bar, uint32_t parity) {
    unsigned n = 0;
    while (!mbar_try(bar, parity)) { if (++n > SPIN_LIMIT) __trap(); }
}
__device__ __forceinline__ void bulk_load(uint32_t dst, const void* src, uint32_t bytes, uint32_t bar, uint64_t pol) {
    asm volatile("cp.async.bulk.shared::cluster.global.mbarrier::complete_tx::bytes.L2::cache_hint [%0], [%1], %2, [%3], %4;"
                 ::"r"(dst), "l"(src), "r"(bytes), "r"(bar), "l"(pol) : "memory");
}
__device__ __forceinline__ void tma3d(uint32_t dst, const CUtensorMap* tm, int c0, int c1, int c2, uint32_t bar, uint64_t pol) {
    asm volatile("cp.async.bulk.tensor.3d.shared::cluster.global.mbarrier::complete_tx::bytes.L2::cache_hint [%0], [%1, {%3,%4,%5}], [%2], %6;"
                 ::"r"(dst), "l"(tm), "r"(bar), "r"(c0), "r"(c1), "r"(c2), "l"(pol) : "memory");
}
__device__ __forceinline__ void l2_prefetch(const void* src, uint32_t bytes) {
    asm volatile("cp.async.bulk.prefetch.L2.global [%0], %1;" ::"l"(src), "r"(bytes) : "memory");
}
__device__ __forceinline__ void ldsm4(uint32_t (&r)[4], uint32_t addr) {
    asm volatile("ldmatrix.sync.aligned.m8n8.x4.shared.b16 {%0,%1,%2,%3}, [%4];"
                 : "=r"(r[0]), "=r"(r[1]), "=r"(r[2]), "=r"(r[3]) : "r"(addr));
}
__device__ __forceinline__ void ldsm4t(uint32_t (&r)[4], uint32_t addr) {
    asm volatile("ldmatrix.sync.aligned.m8n8.x4.trans.shared.b16 {%0,%1,%2,%3}, [%4];"
                 : "=r"(r[0]), "=r"(r[1]), "=r"(r[2]), "=r"(r[3]) : "r"(addr));
}
__device__ __forceinline__ void mma16816(float (&d)[4], const uint32_t (&a)[4], uint32_t b0, uint32_t b1) {
    asm("mma.sync.aligned.m16n8k16.row.col.f32.bf16.bf16.f32 {%0,%1,%2,%3}, {%4,%5,%6,%7}, {%8,%9}, {%0,%1,%2,%3};"
        : "+f"(d[0]), "+f"(d[1]), "+f"(d[2]), "+f"(d[3])
        : "r"(a[0]), "r"(a[1]), "r"(a[2]), "r"(a[3]), "r"(b0), "r"(b1));
}
__device__ __forceinline__ void wgmma_tile(float (&d)[4], uint32_t da, uint32_t db, int accumulate) {
    asm volatile("{\n.reg .pred p;\n.reg .b32 x, y;\n.reg .b64 a, b;\nsetp.ne.u32 p, %6, 0;\nwgmma.fence.sync.aligned;\n"
                 "add.u32 x, %4, 0;\nadd.u32 y, %5, 0;\nmov.b64 a, {x, 0x40000040};\nmov.b64 b, {y, 1};\n"
                 "wgmma.mma_async.sync.aligned.m64n8k16.f32.bf16.bf16 {%0,%1,%2,%3}, a, b, p, 1, 1, 1, 0;\n"
                 "add.u32 x, %4, 128;\nadd.u32 y, %5, 8;\nmov.b64 a, {x, 0x40000040};\nmov.b64 b, {y, 1};\n"
                 "wgmma.mma_async.sync.aligned.m64n8k16.f32.bf16.bf16 {%0,%1,%2,%3}, a, b, 1, 1, 1, 1, 0;\n"
                 "add.u32 x, %4, 256;\nadd.u32 y, %5, 16;\nmov.b64 a, {x, 0x40000040};\nmov.b64 b, {y, 1};\n"
                 "wgmma.mma_async.sync.aligned.m64n8k16.f32.bf16.bf16 {%0,%1,%2,%3}, a, b, 1, 1, 1, 1, 0;\n"
                 "add.u32 x, %4, 384;\nadd.u32 y, %5, 24;\nmov.b64 a, {x, 0x40000040};\nmov.b64 b, {y, 1};\n"
                 "wgmma.mma_async.sync.aligned.m64n8k16.f32.bf16.bf16 {%0,%1,%2,%3}, a, b, 1, 1, 1, 1, 0;\n"
                 "add.u32 x, %4, 512;\nadd.u32 y, %5, 32;\nmov.b64 a, {x, 0x40000040};\nmov.b64 b, {y, 1};\n"
                 "wgmma.mma_async.sync.aligned.m64n8k16.f32.bf16.bf16 {%0,%1,%2,%3}, a, b, 1, 1, 1, 1, 0;\n"
                 "add.u32 x, %4, 640;\nadd.u32 y, %5, 40;\nmov.b64 a, {x, 0x40000040};\nmov.b64 b, {y, 1};\n"
                 "wgmma.mma_async.sync.aligned.m64n8k16.f32.bf16.bf16 {%0,%1,%2,%3}, a, b, 1, 1, 1, 1, 0;\n"
                 "add.u32 x, %4, 768;\nadd.u32 y, %5, 48;\nmov.b64 a, {x, 0x40000040};\nmov.b64 b, {y, 1};\n"
                 "wgmma.mma_async.sync.aligned.m64n8k16.f32.bf16.bf16 {%0,%1,%2,%3}, a, b, 1, 1, 1, 1, 0;\n"
                 "add.u32 x, %4, 896;\nadd.u32 y, %5, 56;\nmov.b64 a, {x, 0x40000040};\nmov.b64 b, {y, 1};\n"
                 "wgmma.mma_async.sync.aligned.m64n8k16.f32.bf16.bf16 {%0,%1,%2,%3}, a, b, 1, 1, 1, 1, 0;\n"
                 "wgmma.commit_group.sync.aligned;\n}"
                 : "+f"(d[0]), "+f"(d[1]), "+f"(d[2]), "+f"(d[3]) : "r"(da), "r"(db), "r"(accumulate) : "memory");
}
__device__ __forceinline__ uint32_t lds32(uint32_t a) {
    uint32_t v;
    asm volatile("ld.shared.u32 %0, [%1];" : "=r"(v) : "r"(a));
    return v;
}
__device__ __forceinline__ unsigned ld_acquire(const unsigned* p) {
    unsigned v;
    asm volatile("ld.acquire.gpu.global.u32 %0, [%1];" : "=r"(v) : "l"(p) : "memory");
    return v;
}
__device__ __forceinline__ uint2 ld_relaxed8(const void* p) {
    uint2 v;
    asm volatile("ld.relaxed.gpu.global.v2.u32 {%0,%1}, [%2];" : "=r"(v.x), "=r"(v.y) : "l"(p) : "memory");
    return v;
}
__device__ __forceinline__ unsigned ld_relaxed4(const void* p) {
    unsigned v;
    asm volatile("ld.relaxed.gpu.global.u32 %0, [%1];" : "=r"(v) : "l"(p) : "memory");
    return v;
}
__device__ __forceinline__ unsigned atom_inc(unsigned* p) {
    unsigned v;
    asm volatile("atom.relaxed.gpu.global.inc.u32 %0, [%1], 0x7fffffff;" : "=r"(v) : "l"(p) : "memory");
    return v;
}
__device__ __forceinline__ unsigned long long ld_relaxed64(const void* p) {
    unsigned long long v;
    asm volatile("ld.relaxed.gpu.global.u64 %0, [%1];" : "=l"(v) : "l"(p) : "memory");
    return v;
}
__device__ __forceinline__ void st_relaxed64(void* p, unsigned long long v) {
    asm volatile("st.relaxed.gpu.global.u64 [%0], %1;" ::"l"(p), "l"(v) : "memory");
}
__device__ __forceinline__ float4 ld_relaxed16(const void* p) {
    float4 v;
    asm volatile("ld.relaxed.gpu.global.v4.f32 {%0,%1,%2,%3}, [%4];" : "=f"(v.x), "=f"(v.y), "=f"(v.z), "=f"(v.w) : "l"(p) : "memory");
    return v;
}
__device__ __forceinline__ uint32_t mapa(uint32_t a, uint32_t rank) {
    uint32_t r;
    asm("mapa.shared::cluster.u32 %0, %1, %2;" : "=r"(r) : "r"(a), "r"(rank));
    return r;
}
__device__ __forceinline__ void mbar_spin(uint32_t bar) {
    asm volatile("{\n.reg .pred p, q;\n.reg .u32 n;\nmov.u32 n, 0;\n"
                 "SPIN:\nmbarrier.test_wait.parity.shared::cta.b64 p, [%0], 0;\nadd.u32 n, n, 1;\nsetp.gt.u32 q, n, 0x4000000;\n@q trap;\n"
                 "@!p bra.uni SPIN;\n}" ::"r"(bar) : "memory");
}
__device__ __forceinline__ void mbar_spin_cluster(uint32_t bar) {
    asm volatile("{\n.reg .pred p, q;\n.reg .u32 n;\nmov.u32 n, 0;\n"
                 "SPIN:\nmbarrier.test_wait.parity.relaxed.cluster.shared::cta.b64 p, [%0], 0;\nadd.u32 n, n, 1;\nsetp.gt.u32 q, n, 0x4000000;\n@q trap;\n"
                 "@!p bra.uni SPIN;\nfence.acquire.sync_restrict::shared::cluster.cluster;\n}" ::"r"(bar) : "memory");
}
__device__ __forceinline__ uint32_t now_ns() {
    unsigned long long t;
    asm volatile("mov.u64 %0, %globaltimer;" : "=l"(t));
    return (uint32_t)t;
}
__device__ __forceinline__ void fence_gpu() { asm volatile("fence.acq_rel.gpu;" ::: "memory"); }
__device__ __forceinline__ void red_add_u32(unsigned* p, unsigned v) {
    asm volatile("red.relaxed.gpu.global.add.u32 [%0], %1;" ::"l"(p), "r"(v) : "memory");
}
__device__ __forceinline__ void st_tagged2(void* p, float a, float b, unsigned tag) {
    const unsigned long long hi = (unsigned long long)tag << 32;
    asm volatile("st.relaxed.gpu.global.v2.b64 [%0], {%1,%2};" ::"l"(p), "l"(hi | __float_as_uint(a)), "l"(hi | __float_as_uint(b)) : "memory");
}
__device__ __forceinline__ ulonglong2 ld_tagged2(const void* p) {
    ulonglong2 v;
    asm volatile("ld.relaxed.gpu.global.v2.b64 {%0,%1}, [%2];" : "=l"(v.x), "=l"(v.y) : "l"(p) : "memory");
    return v;
}
__device__ __forceinline__ float4 atom_add_f4(void* p, float a, float b, float c, float d) {
    float4 r;
    asm volatile("atom.relaxed.gpu.global.add.v4.f32 {%0,%1,%2,%3}, [%4], {%5,%6,%7,%8};"
                 : "=f"(r.x), "=f"(r.y), "=f"(r.z), "=f"(r.w) : "l"(p), "f"(a), "f"(b), "f"(c), "f"(d) : "memory");
    return r;
}
__device__ __forceinline__ void red_release_cta_shared(uint32_t a, unsigned v) {
    asm volatile("red.release.cta.shared::cta.add.u32 [%0], %1;" ::"r"(a), "r"(v) : "memory");
}
__device__ __forceinline__ unsigned ld_acquire_cta_shared(uint32_t a) {
    unsigned v;
    asm volatile("ld.acquire.cta.shared::cta.u32 %0, [%1];" : "=r"(v) : "r"(a) : "memory");
    return v;
}
__device__ __forceinline__ void st_release_cta_shared(uint32_t a, unsigned v) {
    asm volatile("st.release.cta.shared::cta.u32 [%0], %1;" ::"r"(a), "r"(v) : "memory");
}
__device__ __forceinline__ void wait_count(const unsigned* p, unsigned target) {
    unsigned n = 0;
    while (ld_acquire(p) < target) { if (++n > SPIN_LIMIT) __trap(); }
}
__device__ __forceinline__ uint32_t pack_bf16(float lo, float hi) {
    uint32_t r;
    asm("cvt.rn.bf16x2.f32 %0, %1, %2;" : "=r"(r) : "f"(hi), "f"(lo));
    return r;
}
__device__ __forceinline__ float bf_lo(uint32_t v) { return __uint_as_float(v << 16); }
__device__ __forceinline__ float bf_hi(uint32_t v) { return __uint_as_float(v & 0xffff0000u); }
__device__ __forceinline__ float ex2(float x) { float y; asm("ex2.approx.ftz.f32 %0, %1;" : "=f"(y) : "f"(x)); return y; }
__device__ __forceinline__ float expsub(float a, float b) { return ex2((a - b) * LOG2E); }
__device__ __forceinline__ float warp_max(float v) {
#pragma unroll
    for (int m = 16; m; m >>= 1) v = fmaxf(v, __shfl_xor_sync(~0u, v, m));
    return v;
}
__device__ __forceinline__ float warp_sum(float v) {
#pragma unroll
    for (int m = 16; m; m >>= 1) v += __shfl_xor_sync(~0u, v, m);
    return v;
}
template <bool CLU>
__device__ __forceinline__ unsigned unit_block(int u) {
    const unsigned x = ((unsigned)u & (NUK - 1)) / UPP;
    const int lg = u < NUK ? min(KMAX, max(KMIN, 29 - __clz(x | 1))) : min(VMAX, max(CLU ? VMINC : 0, 29 - __clz((127 - x) | 1)));
    const unsigned r = x & ((4u << lg) - 1);
    return ((x - r + (r & ((1u << lg) - 1)) * 4 + (r >> lg)) * UPP) | ((unsigned)u & (UPP - 1));
}
__device__ __forceinline__ const char* block_src(const void* base, unsigned blk) {
    const unsigned po = blk / UPP;
    return reinterpret_cast<const char*>(base) + (size_t)(((po & 3) * NH + (po >> 2)) * UPP + blk % UPP) * TILE_BYTES;
}

template <bool CLU>
__device__ __forceinline__ void a_worker(const Params& p, int un, bool once, bool hold, int nstatic, uint32_t slot, uint32_t bar, uint32_t wb,
                                         uint32_t help, unsigned epoch, uint64_t pol) {
    constexpr int NU = 2 * NUK;
    const int lane = threadIdx.x & 31, g = lane >> 2, t = lane & 3;
    const int li = lane & 7;
    uint32_t kaddr[4], vaddr[8];
    {
        const int e = (lane >> 3) & 1, kk = lane >> 4;
#pragma unroll
        for (int s = 0; s < 4; s++) kaddr[s] = slot + (16 * li + e) * 256 + ((2 * s + kk + li) & 7) * 16;
        const int vrow = 4 * (li >> 1) + (li & 1) + 2 * kk;
#pragma unroll
        for (int c = 0; c < 8; c++) vaddr[c] = slot + vrow * 256 + e * 128 + ((c + li) & 7) * 16;
#pragma unroll
        for (int c = 0; c < 8; c++) asm volatile("" : "+r"(vaddr[c]));
    }
    const uint32_t vmask = (g >> 1) != t ? 0u : ((g & 1) ? 0xffff0000u : 0xffffu);
    int kseen = -1;
    unsigned long long H0 = 0, H1 = 0;
    auto header = [&](int v, unsigned vb) {
        if (v >= NU) return;
        const void *a0, *a1;
        if (v < NUK) {
            const unsigned po = vb / UPP;
            a0 = g_qll + (po & 3) * 2048 + (po >> 2) * 64 + lane;
            a1 = reinterpret_cast<const uint2*>(a0) + 32;
        } else {
            const int half = vb / (NUK / 2);
            if (half > kseen) {
                unsigned n = 0;
                while (ld_acquire_cta_shared(help + 12 + 4 * half) == 0) { if (++n > (SPIN_LIMIT << 4)) __trap(); }
                kseen = half;
            }
            a0 = &g_scores[vb * (KEYS / 4) + lane];
            a1 = &g_stats[(vb / UPP) * UPP + lane];
        }
        H0 = ld_relaxed64(a0);
        H1 = ld_relaxed64(a1);
    };
    epoch = __shfl_sync(~0u, epoch, 0);
    if (hold) { unsigned n = 0; while (ld_acquire_cta_shared(help + 24) < 2) { if (++n > (SPIN_LIMIT << 4)) __trap(); } }
    unsigned (*ctl)[32] = g_ctl[epoch & 1];
    const unsigned tag = epoch + 1;
    unsigned nxt = once ? NU : 0;
    int u = -1;
    unsigned bu = 0, bn = unit_block<CLU>(un);
    bool have = false;
    uint32_t phase = 0;
    unsigned kpend = 0;
    const unsigned zero = gridDim.x >> 24;
    uint32_t Q[16];
    float4 oret = make_float4(0.f, 0.f, 0.f, 0.f);
    while (true) {
        const char* nsrc = block_src(un < NUK ? p.kc : p.vc, bn);
        float4* odst = &g_oacc[(bu / UPP) * 32 + lane];
        unsigned* vdst = &g_vdone[(lane & (NREP - 1)) * NH + bu / (4 * UPP)][0];
        float d[8][4];
        CLK(c1);
        asm volatile("" : "+l"(odst));
        if (u >= NUK) {
#pragma unroll
            for (int j = 0; j < 8; j++) { d[j][0] = d[j][1] = d[j][2] = d[j][3] = 0.f; }
            mbar_wait(wb, phase);
            LAND(NUK + bu);
            uint32_t a[2][8][4];
#pragma unroll
            for (int c = 0; c < 8; c++) ldsm4t(a[0][c], vaddr[c]);
#pragma unroll
            for (int j = 0; j < 8; j++) {
                if (j < 7) {
#pragma unroll
                    for (int c = 0; c < 8; c++) ldsm4t(a[(j + 1) & 1][c], vaddr[c] + (j + 1) * 4096);
                }
#pragma unroll
                for (int c = 0; c < 8; c++) mma16816(d[c], a[j & 1][c], Q[2 * j], Q[2 * j + 1]);
            }
            float o[4];
#pragma unroll
            for (int r = 0; r < 2; r++) {
                o[2 * r] = d[0][2 * r] + d[7][2 * r + 1];
                o[2 * r + 1] = d[0][2 * r + 1] + d[1][2 * r];
#pragma unroll
                for (int k = 1; k < 4; k++) {
                    const int src = (lane & 28) | ((t - k) & 3);
                    o[2 * r] += __shfl_sync(~0u, d[2 * k][2 * r] + d[2 * k - 1][2 * r + 1], src);
                    o[2 * r + 1] += __shfl_sync(~0u, d[2 * k][2 * r + 1] + d[2 * k + 1][2 * r], src);
                }
            }
            oret = atom_add_f4(odst, o[0], o[1], o[2], o[3]);
        } else if (u >= 0) {
#pragma unroll
            for (int j = 0; j < 8; j++) { d[j][0] = d[j][1] = d[j][2] = d[j][3] = 0.f; }
            mbar_wait(wb, phase);
            LAND(bu);
            uint32_t a[2][8][4];
#pragma unroll
            for (int j = 0; j < 8; j++) ldsm4(a[0][j], kaddr[0] + (4 * (j & 3) + 2 * (j >> 2)) * 256);
#pragma unroll
            for (int s = 0; s < 8; s++) {
                if (s < 7) {
#pragma unroll
                    for (int j = 0; j < 8; j++)
                        ldsm4(a[(s + 1) & 1][j], kaddr[(s + 1) & 3] + (4 * (j & 3) + 2 * (j >> 2)) * 256 + ((s + 1) >> 2) * 128);
                }
#pragma unroll
                for (int j = 0; j < 8; j++)
                    mma16816(d[j], a[s & 1][j], Q[(s & 4) * 2 + ((2 * s - 2 * j) & 7)], Q[(s & 4) * 2 + ((2 * s + 1 - 2 * j) & 7)]);
            }
        }
        const bool pre = wb != bar;
        if (u >= 0) { phase = pre ? 0 : phase ^ 1; wb = bar; }
        CLK(c2b);
        if (un < NU && lane == 0) {
            if (!once) nxt = atom_inc(&ctl[C_QUEUE][0]);
            if (u >= 0 || !pre) {
                mbar_expect_tx(bar, TILE_BYTES);
                bulk_load(slot, nsrc, TILE_BYTES, bar, pol);
            }
        }
        const uint32_t tiss = now_ns();
        CLK(c3);
        if ((unsigned)u < (unsigned)NUK) {
            const int j0 = (t - (g >> 1)) & 3;
            float v[4];
#pragma unroll
            for (int q = 0; q < 4; q++) {
                const int jq = (q >> 1) * 4, e = (q & 1) * 2;
                const float x0 = (g & 1) ? d[jq + 0][e + 1] : d[jq + 0][e];
                const float x1 = (g & 1) ? d[jq + 1][e + 1] : d[jq + 1][e];
                const float x2 = (g & 1) ? d[jq + 2][e + 1] : d[jq + 2][e];
                const float x3 = (g & 1) ? d[jq + 3][e + 1] : d[jq + 3][e];
                const float y0 = (j0 & 1) ? x1 : x0, y1 = (j0 & 1) ? x3 : x2;
                v[q] = (j0 & 2) ? y1 : y0;
            }
            const uint32_t r0 = pack_bf16(v[0], v[1]), r1 = pack_bf16(v[2], v[3]);
            const uint32_t s0 = pack_bf16(bf_lo(r0) * SCALE, bf_hi(r0) * SCALE);
            const uint32_t s1 = pack_bf16(bf_lo(r1) * SCALE, bf_hi(r1) * SCALE);
            g_scores[bu * (KEYS / 4) + 4 * g + j0] = make_uint2(s0, s1);
            const float f0 = bf_lo(s0), f1 = bf_hi(s0), f2 = bf_lo(s1), f3 = bf_hi(s1);
            const float m = warp_max(fmaxf(fmaxf(f0, f1), fmaxf(f2, f3)));
            const float l = warp_sum((expsub(f0, m) + expsub(f1, m)) + (expsub(f2, m) + expsub(f3, m)));
            if (lane == 0) g_stats[bu] = make_float2(m, l);
            kpend++;
            if (un / (NUK / 2) != u / (NUK / 2)) {
                __syncwarp();
                if (lane == 0) {
                    red_release_cta_shared(help + 4 * (u / (NUK / 2)), kpend);
                    if (un >= NUK) red_release_cta_shared(help + 8, 1u);
                }
                kpend = 0;
            }
        }
        CLK(c4);
        int unn = NU;
        if (un < NU) {
            unsigned n = 0;
            while (true) {
                if (!have) header(un, bn);
                if (un >= NUK || __all_sync(~0u, (uint32_t)(H0 >> 32) == tag && (uint32_t)(H1 >> 32) == tag)) break;
                if (++n > SPIN_LIMIT) __trap();
                have = false;
            }
            if (un >= NUK) {
                const uint32_t s0 = (uint32_t)H0, s1 = (uint32_t)(H0 >> 32);
                const float mu = __uint_as_float((uint32_t)H1);
                const float m = warp_max(mu);
                const float l = warp_sum(__uint_as_float((uint32_t)(H1 >> 32)) * expsub(mu, m));
                const float inv = 1.0f / l;
                const uint32_t w0 = pack_bf16(expsub(bf_lo(s0), m) * inv, expsub(bf_hi(s0), m) * inv);
                const uint32_t w1 = pack_bf16(expsub(bf_lo(s1), m) * inv, expsub(bf_hi(s1), m) * inv);
#pragma unroll
                for (int j = 0; j < 8; j++) {
                    Q[2 * j] = __shfl_sync(~0u, w0, 4 * j + t) & vmask;
                    Q[2 * j + 1] = __shfl_sync(~0u, w1, 4 * j + t) & vmask;
                }
            } else {
#pragma unroll
                for (int j = 0; j < 8; j++) {
                    const int src = (((j + g) & 7) << 2) + t;
                    Q[j] = __shfl_sync(~0u, (uint32_t)H0, src);
                    Q[8 + j] = __shfl_sync(~0u, (uint32_t)H1, src);
                }
            }
            unn = nstatic + (int)__shfl_sync(~0u, nxt, 0);
            if (CLU && !once && unn >= NU && lane == 0)
                asm volatile("st.relaxed.cta.shared::cta.u32 [%0], %1;" ::"r"(help + 28), "r"((tiss + (FJ - (unn - NU)) * 10) | 1u) : "memory");
        }
        if (u >= NUK && lane < (CLU ? 1 : NREP))
            red_add_u32(vdst,
                        1u + ((__float_as_uint(oret.x) | __float_as_uint(oret.y) | __float_as_uint(oret.z) | __float_as_uint(oret.w)) & zero));
        if (un >= NU) break;
        bu = bn;
        have = !(un < NUK && unn >= NUK && !(un >= NUK / 2 && unn < NUK + NUK / 2));
        bn = unit_block<CLU>(unn);
        if (have) header(unn, bn);
        u = un;
        un = unn;
    }
}

__device__ __forceinline__ void k_helper(uint32_t help, unsigned epoch) {
    if ((threadIdx.x & 31) != 0) return;
    unsigned (*ctl)[32] = g_ctl[epoch & 1];
    unsigned sent0 = 0, sent1 = 0, n = 0;
    int seen = 0;
    bool fin = false;
    while (!fin || seen < 2) {
        if (!fin) {
            fin = ld_acquire_cta_shared(help + 8) == NW + XW;
            const unsigned c0 = ld_acquire_cta_shared(help), c1 = ld_acquire_cta_shared(help + 4);
            if (c0 != sent0 || c1 != sent1) {
                fence_gpu();
                if (c0 != sent0) red_add_u32(&ctl[C_KDONE][0], c0 - sent0);
                if (c1 != sent1) red_add_u32(&ctl[C_KDONE + 1][0], c1 - sent1);
                sent0 = c0; sent1 = c1;
            }
        }
        if (seen < 2 && ld_acquire(&ctl[C_KDONE + seen][0]) >= NUK / 2) {
            st_release_cta_shared(help + 12 + 4 * seen, 1u);
            seen++;
        } else {
            __nanosleep(300);
        }
        if (++n > SPIN_LIMIT) __trap();
    }
}

__device__ __forceinline__ void v_poller(uint32_t sbase, int f, int w) {
    const int lane = threadIdx.x & 31;
    const unsigned (*cp)[32] = &g_vdone[((f * NPOLL + w) % NREP) * NH];
    unsigned n = 0;
    while (ld_acquire_cta_shared(sbase + M_HELP + 12) == 0) { __nanosleep(1000); if (++n > SPIN_LIMIT) __trap(); }
    int h = 0;
    bool fast = false;
    while (h < NH) {
        const unsigned r = __ballot_sync(~0u, ld_acquire(&cp[min(h + (lane & 3), NH - 1)][0]) >= 4 * UPP) & 15u;
        if (r & 1) {
            h = min(NH, h + __ffs(~r) - 1);
            __syncwarp();
            if (lane == 0) asm volatile("red.release.cta.shared::cta.max.u32 [%0], %1;" ::"r"(sbase + M_HELP + 20), "r"(h) : "memory");
        }
        if (h < NH - 4) {
            __nanosleep(h ? 300 : 1000);
        } else if (!fast) {
            fast = true;
            const long long t0 = clock64();
            while (clock64() - t0 < w * PGAP) {}
        }
        if (++n > SPIN_LIMIT) __trap();
    }
}
__device__ __forceinline__ void finisher(const Params& p, uint32_t sbase, int f) {
    const int lane = threadIdx.x & 31;
    {
        const char* wg = reinterpret_cast<const char*>(p.wo);
        const uint32_t dst = sbase + 4 * SLOT + (16 * (lane & 7) + (lane >> 3)) * 16;
#pragma unroll 1
        for (int h = -FPF - 4; h < NH; h++) {
            if (lane == 0 && (unsigned)(h + FPF) < (unsigned)NH) l2_prefetch(wg + (size_t)(h + FPF) * 147456 + f * 2048, 2048);
            if (h >= 0) {
#pragma unroll
                for (int r = 0; r < 4; r++)
                    asm volatile("cp.async.cg.shared.global [%0], [%1], 16;" ::"r"(dst + h * 2048 + ((r & 1) * 4 + (r >> 1) * 8) * 16),
                                 "l"(wg + (size_t)(h * 128 + r * 32 + lane) * (DM * 2) + f * 16) : "memory");
            }
            __nanosleep(FSLEEP);
        }
        asm volatile("cp.async.wait_all;" ::: "memory");
        __syncwarp();
    }
    TS(11);
    const float4* vec = g_oacc + ((lane >> 2) & 3) * 32 + (lane >> 4) * 16 + (lane & 3);
    float acc[2][2][4];
#pragma unroll
    for (int i = 0; i < 16; i++) acc[i >> 3][(i >> 2) & 1][i & 3] = 0.f;
    uint32_t* outp = reinterpret_cast<uint32_t*>(p.out + (lane >> 2) * (2 * DM) + f * 8 + (lane & 3) * 2);
    uint32_t wa = sbase + 4 * SLOT + lane * 16;
    auto project = [&](const float4 (&x)[4], const uint32_t (&w)[4][4]) {
#pragma unroll
        for (int s = 0; s < 4; s++) {
            const uint32_t a[4] = {pack_bf16(x[s].x, x[s].y), 0u, pack_bf16(x[s].z, x[s].w), 0u};
            mma16816(acc[0][s & 1], a, w[s >> 1][(s & 1) * 2], w[s >> 1][(s & 1) * 2 + 1]);
            mma16816(acc[1][s & 1], a, w[2 + (s >> 1)][(s & 1) * 2], w[2 + (s >> 1)][(s & 1) * 2 + 1]);
        }
    };
    int h = 0;
    unsigned n = 0;
    while (h < NH) {
        uint32_t w[4][4];
#pragma unroll
        for (int q = 0; q < 4; q++) ldsm4t(w[q], wa + q * 512);
        int ready;
        while ((ready = ld_acquire_cta_shared(sbase + M_HELP + 20)) <= h) {
            if (h < NH - 3) __nanosleep(100);
            if (++n > (SPIN_LIMIT << 4)) __trap();
        }
        float4 x[4], y[4];
#pragma unroll
        for (int s = 0; s < 4; s++) x[s] = ld_relaxed16(vec + s * 4);
        const bool two = ready > h + 1;
        if (two) {
#pragma unroll
            for (int s = 0; s < 4; s++) y[s] = ld_relaxed16(vec + 128 + s * 4);
        }
        project(x, w);
        if (two) {
#pragma unroll
            for (int q = 0; q < 4; q++) ldsm4t(w[q], wa + 2048 + q * 512);
            project(y, w);
        }
        const int nr = two ? 2 : 1;
        h += nr;
        vec += nr * 128;
        wa += nr * 2048;
        const float o0 = acc[0][0][0] + acc[0][1][0] + __shfl_down_sync(~0u, acc[1][0][0] + acc[1][1][0], 16);
        const float o1 = acc[0][0][1] + acc[0][1][1] + __shfl_down_sync(~0u, acc[1][0][1] + acc[1][1][1], 16);
        asm volatile("{\n.reg .pred p;\nsetp.ne.u32 p, %2, 0;\n@p st.global.u32 [%0], %1;\n}" ::"l"(outp), "r"(pack_bf16(o0, o1)),
                     "r"((uint32_t)(lane < 16 && h == NH)) : "memory");
    }
}

__device__ __forceinline__ void out_fetch(uint32_t sbase, int step, int h) {
    const int lane = threadIdx.x & 31, g = lane >> 2;
    float4 x[4];
#pragma unroll
    for (int b = 0; b < 4; b++) x[b] = ld_relaxed16(&g_oacc[(h * 4 + ((b + g) & 3)) * 32 + lane]);
#pragma unroll
    for (int b = 0; b < 4; b++) {
        const uint32_t a = sbase + F_X + step * FXP + g * 128 + ((b + g) & 3) * 16 + (lane & 3) * 4;
        asm volatile("st.shared.u32 [%0], %1;\nst.shared.u32 [%0 + 64], %2;" ::"r"(a), "r"(pack_bf16(x[b].x, x[b].y)), "r"(pack_bf16(x[b].z, x[b].w)) : "memory");
    }
    asm volatile("fence.proxy.async.shared::cta;" ::: "memory");
}
__device__ __forceinline__ void out_early(uint32_t sbase, int rank, unsigned tag) {
    const int lane = threadIdx.x & 31;
    if (lane < 10) {
        mbar_init(sbase + F_BAR + 16 + lane * 8, lane < 7 ? 1 : lane == 7 ? 2 : 4);
        if (lane < 8) mbar_expect_tx(sbase + F_BAR + 16 + lane * 8, 16384);
    }
    asm volatile("fence.mbarrier_init.release.cluster;" ::: "memory");
    unsigned n = 0;
#pragma unroll 1
    for (int i = 0; i < 3; i++) {
        while (ld_acquire(&g_vdone[8 * i + rank][0]) < 4 * UPP) { __nanosleep(500); if (++n > SPIN_LIMIT) __trap(); }
        out_fetch(sbase, 4 + i, 8 * i + rank);
#pragma unroll 1
        for (int j = 0; j < 16 && i == 0;) {
            const ulonglong2 v = ld_tagged2(&g_ctx[((j >> 2) * 8 + rank) * 128 + (j & 3) * 32 + lane]);
            if (__all_sync(~0u, (unsigned)(v.x >> 32) == tag && (unsigned)(v.y >> 32) == tag)) {
                asm volatile("st.shared.v2.u32 [%0], {%1,%2};" ::"r"(sbase + F_X + (j >> 2) * FXP + ((j & 3) * 32 + lane) * 8), "r"((uint32_t)v.x), "r"((uint32_t)v.y) : "memory");
                j++;
            } else {
                __nanosleep(500);
                if (++n > SPIN_LIMIT) __trap();
            }
        }
    }
    __syncwarp();
    if (lane == 0) st_release_cta_shared(sbase + M_HELP + 32, 1u);
}
__device__ __forceinline__ void out_late(uint32_t sbase, int rank) {
    unsigned n = 0;
    while (ld_acquire_cta_shared(sbase + M_HELP + 32) == 0) { if (++n > (SPIN_LIMIT << 4)) __trap(); }
    while (ld_acquire(&g_vdone[24 + rank][0]) < 4 * UPP) { if (++n > SPIN_LIMIT) __trap(); }
    TS(12);
    out_fetch(sbase, 7, 24 + rank);
    __syncwarp();
    if ((threadIdx.x & 31) == 0) asm volatile("mbarrier.arrive.shared::cta.b64 _, [%0];" ::"r"(sbase + F_BAR + 72) : "memory");
    TS(13);
}
__device__ __forceinline__ void out_project(uint32_t sbase, int rank, int w) {
    const int lane = threadIdx.x & 31, g = lane >> 2, t = lane & 3;
    unsigned n = 0;
    while (ld_acquire_cta_shared(sbase + M_HELP + 32) == 0) { __nanosleep(500); if (++n > SPIN_LIMIT) __trap(); }
    asm volatile("barrier.cluster.wait.acquire.aligned;" ::: "memory");
    uint32_t rdst = mapa(sbase + F_RECV + rank * 128 + (g & 3) * 32 + t * 16, 2 * w + (g >> 2)), rbar = mapa(sbase + F_BAR, 2 * w + (g >> 2));
    while (ld_acquire_cta_shared(sbase + M_HELP + 28) == 0) { __nanosleep(200); if (++n > SPIN_LIMIT) __trap(); }
    const uint32_t da = (1u << 16) | (((sbase + F_W) & 0x3ffff) >> 4), db = (4u << 16) | (((sbase + F_X) & 0x3ffff) >> 4);
    float d[4] = {0.f, 0.f, 0.f, 0.f};
#pragma unroll
    for (int i = 0; i < 8; i++) {
        mbar_spin(sbase + F_BAR + 16 + i * 8);
        wgmma_tile(d, da + (i % 6) * 1024, db + i * (FXP / 16), i & 3);
        if (i < 2 || (i & 3) == 3) asm volatile("wgmma.wait_group.sync.aligned 0;" : "+f"(d[0]), "+f"(d[1]), "+f"(d[2]), "+f"(d[3])::"memory");
        if (i < 2) {
            asm volatile("{\n.reg .pred p;\nsetp.eq.u32 p, %1, 0;\n@p mbarrier.arrive.shared::cta.b64 _, [%0];\n}"
                         ::"r"(sbase + F_BAR + 80 + i * 8), "r"(lane) : "memory");
        } else if ((i & 3) == 3) {
            if (t < 2)
                asm volatile("st.async.weak.shared::cluster.mbarrier::complete_tx::bytes.v4.f32 [%0], {%1,%2,%3,%4}, [%5];"
                             ::"r"(rdst), "f"(d[0]), "f"(d[1]), "f"(d[2]), "f"(d[3]), "r"(rbar) : "memory");
            __syncwarp();
            rdst += 1024;
            rbar += 8;
            asm volatile("" : "+r"(rdst), "+r"(rbar));
        }
    }
}
__device__ __forceinline__ void out_issue_sum(const Params& p, uint32_t sbase, int c, int rank, uint64_t pol) {
    const int lane = threadIdx.x & 31;
    if (lane == 0) {
        unsigned n = 0;
        while (ld_acquire_cta_shared(sbase + M_HELP + 32) == 0) { __nanosleep(500); if (++n > SPIN_LIMIT) __trap(); }
        asm volatile("prefetch.tensormap [%0];" ::"l"(&p.tm_wf) : "memory");
        asm volatile("prefetch.tensormap [%0];" ::"l"(&p.tm_wl) : "memory");
        uint32_t t0;
        while ((t0 = ld_acquire_cta_shared(sbase + M_HELP + 28)) == 0) { __nanosleep(100); if (++n > SPIN_LIMIT) __trap(); }
#pragma unroll 1
        for (int i = 0; i < 8; i++) {
            const int h = (i & 3) * 8 + rank;
            if (i >= 6) mbar_wait(sbase + F_BAR + 32 + i * 8, 0);
            while ((int)(now_ns() - t0) < 0) {}
            if (i == 0) TS(16);
            tma3d(sbase + F_W + (i < 6 ? i : i - 6) * 16384, i < 4 ? &p.tm_wf : &p.tm_wl, i < 4 ? 0 : c * 64, i < 4 ? h * 128 : h * 16,
                  i < 4 ? c : 0, sbase + F_BAR + 16 + i * 8, pol);
            t0 += FP;
        }
        TS(17);
    }
    __syncwarp();
    __nv_bfloat16* dst = p.out + (((lane >> 1) & 2) + (lane & 1)) * (2 * DM) + DM + c * 64 + (rank >> 1) * 16 + (lane & 2) * 4 +
                         (rank & 1) * 4 + (lane >> 3);
    uint32_t src = sbase + F_RECV + lane * 4;
#pragma unroll 1
    for (int r = 0; r < 2; r++) {
        asm volatile("" : "+l"(dst), "+r"(src));
        mbar_spin_cluster(sbase + F_BAR + r * 8);
        float x[8];
#pragma unroll
        for (int i = 0; i < 8; i++) asm volatile("ld.shared.f32 %0, [%1];" : "=f"(x[i]) : "r"(src + i * 128) : "memory");
        const float v = ((x[0] + x[1]) + (x[2] + x[3])) + ((x[4] + x[5]) + (x[6] + x[7]));
        asm volatile("st.global.u16 [%0], %1;" ::"l"(dst), "h"((unsigned short)pack_bf16(v, 0.f)) : "memory");
        TS(14 + r);
        dst -= DM;
        src += 1024;
    }
}

constexpr int BS_WUK = 5, BS_Q = 9, BS_CKV = 11, BS_PART = 27, BS_WUV = 29, BS_END = 33;

__device__ __noinline__ void b_issue(const Params& p, int n, int bi, uint32_t sbase, uint64_t pol) {
    if (n >= BS_END || (n >= BS_Q && n < BS_CKV) || (n >= BS_PART && n < BS_WUV)) return;
    const uint32_t bar = sbase + M_BAR + (NSLOT + n % BRING) * 8;
    const CUtensorMap* tm;
    int row, panel = 2 * bi;
    if (n < BS_WUK) { tm = &p.tm_wq; row = n * 128; }
    else if (n < BS_Q) { tm = &p.tm_wuk; row = (n - BS_WUK) * 128; }
    else if (n < BS_PART) {
        tm = &p.tm_ckv; panel = 0;
        row = (bi >> 3) * SK + ((n - BS_CKV) * 8 + (bi & 7)) * 32;
    }
    else { tm = &p.tm_wuv; row = (n - BS_WUV) * 128; }
    mbar_expect_tx(bar, n == 0 ? 32768 + 4 * 1152 : 32768);
    tma3d(sbase + (n % BRING) * SLOT, tm, 0, row, panel, bar, pol);
}
__device__ __forceinline__ void b_issue_xchg(int n, const void* src, uint32_t sbase, uint64_t pol) {
    asm volatile("fence.proxy.async;" ::: "memory");
#pragma unroll
    for (int i = 0; i < 2; i++) {
        const uint32_t bar = sbase + M_BAR + (NSLOT + (n + i) % BRING) * 8;
        mbar_expect_tx(bar, 32768);
        bulk_load(sbase + ((n + i) % BRING) * SLOT, reinterpret_cast<const char*>(src) + i * 32768, 32768, bar, pol);
    }
}
__device__ __forceinline__ void b_wait(int n, uint32_t sbase) {
    mbar_wait(sbase + M_BAR + (NSLOT + n % BRING) * 8, (n / BRING) & 1);
}

__device__ __noinline__ void b_gemm(const Params& p, uint32_t sbase, int n0, int n1, int ktot, uint32_t xh, uint32_t xl, int pitch,
                                    int bi, uint64_t pol) {
    const int tid = threadIdx.x, warp = tid >> 5, lane = tid & 31, g = lane >> 2, t = lane & 3;
    const uint32_t woff = (warp >> 2) * 16384 + (lane & 15) * 128 + ((((warp & 3) * 2 + (lane >> 4)) ^ (lane & 7)) * 16);
    const uint32_t xoff = (g & 3) * pitch + t * 4;
    float acc[2][4];
#pragma unroll
    for (int i = 0; i < 8; i++) acc[i >> 2][i & 3] = 0.f;
#pragma unroll 1
    for (int n = n0; n < n1; n++) {
        b_wait(n, sbase);
        const uint32_t slot = sbase + (n % BRING) * SLOT + woff;
        const int k0 = (n - n0) * 128;
        const int ns = min(8, (ktot - k0) >> 4);
#pragma unroll 2
        for (int s = 0; s < ns; s++) {
            uint32_t a[4], w[4];
            const uint32_t xo = xoff + (k0 + 16 * s) * 2;
            a[0] = lds32(xh + xo); a[2] = lds32(xh + xo + 16);
            a[1] = xl ? lds32(xl + xo) : 0u; a[3] = xl ? lds32(xl + xo + 16) : 0u;
            ldsm4t(w, slot + s * 2048);
            mma16816(acc[0], a, w[0], w[1]);
            mma16816(acc[1], a, w[2], w[3]);
        }
        __syncthreads();
        if (tid == 0) b_issue(p, n + BD, bi, sbase, pol);
    }
    if (g < 4) {
#pragma unroll
        for (int j = 0; j < 2; j++)
            asm volatile("st.shared.u32 [%0], %1;" ::"r"(sbase + M_QB + g * QP + (warp * 16 + j * 8 + t * 2) * 2),
                         "r"(pack_bf16(acc[j][0] + acc[j][2], acc[j][1] + acc[j][3])) : "memory");
    }
    __syncthreads();
}

__device__ __forceinline__ void b_exchange(unsigned* c, int n, const void* src, uint32_t sbase, uint64_t pol) {
    TS(n == BS_Q ? 24 : 28);
    __syncthreads();
    if (threadIdx.x == 0) {
        TS(n == BS_Q ? 25 : 29);
        fence_gpu();
        TS(n == BS_Q ? 26 : 30);
        red_add_u32(c, 1u);
        wait_count(c, NBCTA);
        TS(n == BS_Q ? 27 : 31);
        b_issue_xchg(n, src, sbase, pol);
    }
}

template <bool CLU>
__device__ __noinline__ void b_chain(const Params& p, char* smem, uint32_t sbase, int bi, unsigned epoch, uint64_t pol) {
    const int tid = threadIdx.x, warp = tid >> 5, lane = tid & 31, g = lane >> 2, t = lane & 3;
    unsigned (*ctl)[32] = g_ctl[epoch & 1];
    float* red = reinterpret_cast<float*>(smem + 5 * SLOT);
    b_gemm(p, sbase, 0, BS_WUK, DM, sbase + M_XB, 0, XP, bi, pol);
    TS(6);
    {
        uint32_t Q[16];
#pragma unroll
        for (int c = 0; c < 16; c++) Q[c] = lds32(sbase + M_QB + (g & 3) * QP + c * 16 + t * 4);
        float* qa = reinterpret_cast<float*>(smem + M_QA);
#pragma unroll 1
        for (int n = BS_WUK; n < BS_Q; n++) {
            b_wait(n, sbase);
            const uint32_t base = sbase + (n % BRING) * SLOT + (warp * 16 + (lane & 15)) * 128;
            float d[2][4];
#pragma unroll
            for (int i = 0; i < 8; i++) d[i >> 2][i & 3] = 0.f;
#pragma unroll
            for (int s = 0; s < 8; s++) {
                uint32_t a[4];
                ldsm4(a, base + (s >> 2) * 16384 + (((2 * (s & 3) + (lane >> 4)) ^ (lane & 7)) * 16));
                mma16816(d[s & 1], a, Q[2 * s], Q[2 * s + 1]);
            }
            const int c = (n - BS_WUK) * 128 + warp * 16 + g + 8 * (t >> 1);
            qa[(2 * (t & 1)) * 512 + c] = (t & 2) ? d[0][2] + d[1][2] : d[0][0] + d[1][0];
            qa[(2 * (t & 1) + 1) * 512 + c] = (t & 2) ? d[0][3] + d[1][3] : d[0][1] + d[1][1];
            __syncthreads();
            if (tid == 0) b_issue(p, n + BD, bi, sbase, pol);
        }
#pragma unroll 1
        for (int r = 0; r < 2; r++) {
            const int id = tid + r * 256;
            const int b = id >> 7, c0 = ((id >> 2) & 31) * 16 + (id & 3) * 2;
            const float2 u0 = *reinterpret_cast<const float2*>(qa + b * 512 + c0);
            const float2 u1 = *reinterpret_cast<const float2*>(qa + b * 512 + c0 + 8);
            const uint32_t h0 = pack_bf16(u0.x, u0.y), h1 = pack_bf16(u1.x, u1.y);
            const uint32_t l0 = pack_bf16(u0.x - bf_lo(h0), u0.y - bf_hi(h0)), l1 = pack_bf16(u1.x - bf_lo(h1), u1.y - bf_hi(h1));
            g_qabs[((id >> 2) * 4 + (bi >> 3)) * 32 + (bi & 7) * 4 + (id & 3)] = make_uint4(h0, l0, h1, l1);
        }
    }
    b_exchange(&ctl[C_BBAR][0], BS_Q, &g_qabs[(bi >> 3) * 4096], sbase, pol);
    {
        uint32_t qf[4][4][4];
        b_wait(BS_Q + (warp >> 2), sbase);
        TS(7);
        {
            const uint4* qs = reinterpret_cast<const uint4*>(smem + ((BS_Q + (warp >> 2)) % BRING) * SLOT) + (warp & 3) * 512 + lane;
#pragma unroll
            for (int s = 0; s < 4; s++)
#pragma unroll
                for (int i = 0; i < 4; i++) {
                    const uint4 v = qs[(s * 4 + i) * 32];
                    qf[i][s][0] = v.x; qf[i][s][1] = v.y; qf[i][s][2] = v.z; qf[i][s][3] = v.w;
                }
        }
        __syncthreads();
        if (tid == 0) { b_issue(p, BS_Q + BD, bi, sbase, pol); b_issue(p, BS_Q + 1 + BD, bi, sbase, pol); }
        float acc[2][8][4];
#pragma unroll
        for (int i = 0; i < 2; i++)
#pragma unroll
            for (int j = 0; j < 8; j++) { acc[i][j][0] = acc[i][j][1] = acc[i][j][2] = acc[i][j][3] = 0.f; }
        float mrun = -INFINITY, lrun = 0.f;
        const int head = tid >> 3, kq = tid & 7;
        float* alpha = reinterpret_cast<float*>(smem + M_ALPHA);
        for (int n = BS_CKV; n < BS_PART; n++) {
            b_wait(n, sbase);
            const uint32_t slot = sbase + (n % BRING) * SLOT;
            float sc[4][4][4];
#pragma unroll
            for (int i = 0; i < 4; i++)
#pragma unroll
                for (int j = 0; j < 4; j++) { sc[i][j][0] = sc[i][j][1] = sc[i][j][2] = sc[i][j][3] = 0.f; }
#pragma unroll
            for (int j = 0; j < 4; j++)
#pragma unroll
                for (int sp = 0; sp < 2; sp++) {
                    uint32_t bf[4];
                    ldsm4(bf, slot + warp * 4096 + (8 * j + (lane & 7)) * 128 + (((4 * sp + (lane >> 3)) ^ (lane & 7)) * 16));
#pragma unroll
                    for (int i = 0; i < 4; i++) {
                        mma16816(sc[i][j], qf[i][2 * sp], bf[0], bf[1]);
                        mma16816(sc[i][j], qf[i][2 * sp + 1], bf[2], bf[3]);
                    }
                }
#pragma unroll
            for (int i = 0; i < 4; i++)
#pragma unroll
                for (int j = 0; j < 4; j++)
                    *reinterpret_cast<float2*>(red + warp * 1024 + (8 * i + g) * 32 + ((8 * j) ^ (8 * (g & 3))) + 2 * t) =
                        make_float2(sc[i][j][0] + sc[i][j][2], sc[i][j][1] + sc[i][j][3]);
            __syncthreads();
            if (tid == 0 && n > BS_CKV) b_issue(p, n - 1 + BD, bi, sbase, pol);
            {
                float4 s = make_float4(0.f, 0.f, 0.f, 0.f);
#pragma unroll
                for (int w = 0; w < 8; w++) {
                    const float4 v = *reinterpret_cast<const float4*>(red + w * 1024 + head * 32 + ((4 * kq) ^ (8 * (head & 3))));
                    s.x += v.x; s.y += v.y; s.z += v.z; s.w += v.w;
                }
                const uint32_t r0 = pack_bf16(s.x, s.y), r1 = pack_bf16(s.z, s.w);
                const uint32_t s0 = pack_bf16(bf_lo(r0) * SCALE, bf_hi(r0) * SCALE);
                const uint32_t s1 = pack_bf16(bf_lo(r1) * SCALE, bf_hi(r1) * SCALE);
                const float f0 = bf_lo(s0), f1 = bf_hi(s0), f2 = bf_lo(s1), f3 = bf_hi(s1);
                float mx = fmaxf(fmaxf(f0, f1), fmaxf(f2, f3));
                mx = fmaxf(mx, __shfl_xor_sync(~0u, mx, 1));
                mx = fmaxf(mx, __shfl_xor_sync(~0u, mx, 2));
                mx = fmaxf(mx, __shfl_xor_sync(~0u, mx, 4));
                const float mnew = fmaxf(mrun, mx);
                const float al = expsub(mrun, mnew);
                const float p0 = expsub(f0, mnew), p1 = expsub(f1, mnew), p2 = expsub(f2, mnew), p3 = expsub(f3, mnew);
                lrun = lrun * al + ((p0 + p1) + (p2 + p3));
                mrun = mnew;
                *reinterpret_cast<uint2*>(smem + M_P + head * 80 + kq * 8) = make_uint2(pack_bf16(p0, p1), pack_bf16(p2, p3));
                if (kq == 0) alpha[head] = al;
            }
            __syncthreads();
            {
                uint32_t pf[2][2][4];
#pragma unroll
                for (int i = 0; i < 2; i++)
#pragma unroll
                    for (int ks = 0; ks < 2; ks++)
                        ldsm4(pf[i][ks], sbase + M_P + (16 * i + (lane & 15)) * 80 + (16 * ks + 8 * (lane >> 4)) * 2);
#pragma unroll
                for (int i = 0; i < 2; i++) {
                    const float a0 = alpha[16 * i + g], a1 = alpha[16 * i + 8 + g];
#pragma unroll
                    for (int j = 0; j < 8; j++) { acc[i][j][0] *= a0; acc[i][j][1] *= a0; acc[i][j][2] *= a1; acc[i][j][3] *= a1; }
                }
#pragma unroll
                for (int j = 0; j < 8; j++) {
                    uint32_t bf[4];
                    ldsm4t(bf, slot + warp * 4096 + lane * 128 + ((j ^ (lane & 7)) * 16));
#pragma unroll
                    for (int i = 0; i < 2; i++) {
                        mma16816(acc[i][j], pf[i][0], bf[0], bf[1]);
                        mma16816(acc[i][j], pf[i][1], bf[2], bf[3]);
                    }
                }
            }
        }
        __syncthreads();
        if (tid == 0) b_issue(p, BS_PART - 1 + BD, bi, sbase, pol);
        lrun += __shfl_xor_sync(~0u, lrun, 1);
        lrun += __shfl_xor_sync(~0u, lrun, 2);
        lrun += __shfl_xor_sync(~0u, lrun, 4);
        if (kq == 0) g_bml[head * NBCTA + bi] = make_float2(mrun, lrun);
#pragma unroll
        for (int i = 0; i < 2; i++)
#pragma unroll
            for (int j = 0; j < 8; j++) {
                g_bpart[((16 * i + g) * NBCTA + bi) * 256 + warp * 32 + j * 4 + t] = make_float2(acc[i][j][0], acc[i][j][1]);
                g_bpart[((16 * i + 8 + g) * NBCTA + bi) * 256 + warp * 32 + j * 4 + t] = make_float2(acc[i][j][2], acc[i][j][3]);
            }
    }
#pragma unroll 1
    for (int i = tid; i < NH * 36 && !(CLU); i += 256) g_outb[bi * NH * 36 + i] = make_uint4(0u, epoch, 0u, epoch);
    b_exchange(&ctl[C_BBAR + 1][0], BS_PART, &g_bpart[bi * NBCTA * 256], sbase, pol);
    {
        float* omega = reinterpret_cast<float*>(smem + M_OMEGA);
        if (warp == 0) {
            __syncwarp();
            const uint2 ml = ld_relaxed8(&g_bml[bi * NBCTA + lane]);
            const float ms = __uint_as_float(ml.x);
            float m = ms;
            m = fmaxf(m, __shfl_xor_sync(~0u, m, 1));
            m = fmaxf(m, __shfl_xor_sync(~0u, m, 2));
            m = fmaxf(m, __shfl_xor_sync(~0u, m, 4));
            const float w = expsub(ms, m);
            float l = w * __uint_as_float(ml.y);
            l += __shfl_xor_sync(~0u, l, 1);
            l += __shfl_xor_sync(~0u, l, 2);
            l += __shfl_xor_sync(~0u, l, 4);
            omega[lane] = w / l;
        }
        __syncthreads();
        b_wait(BS_PART, sbase);
        b_wait(BS_PART + 1, sbase);
#pragma unroll 1
        for (int b = 0; b < 4; b++) {
            const float2* ps = reinterpret_cast<const float2*>(smem + ((BS_PART + (b >> 1)) % BRING) * SLOT) + (b & 1) * 2048 + tid;
            float c0 = 0.f, c1 = 0.f;
#pragma unroll
            for (int s = 0; s < 8; s++) {
                const float w = omega[b * 8 + s];
                const float2 v = ps[s * 256];
                c0 = fmaf(w, v.x, c0);
                c1 = fmaf(w, v.y, c1);
            }
            const uint32_t hi = pack_bf16(c0, c1);
            *reinterpret_cast<uint32_t*>(smem + M_CH + b * CP + tid * 4) = hi;
            *reinterpret_cast<uint32_t*>(smem + M_CL + b * CP + tid * 4) = pack_bf16(c0 - bf_lo(hi), c1 - bf_hi(hi));
        }
        __syncthreads();
        if (tid == 0) { b_issue(p, BS_PART + BD, bi, sbase, pol); b_issue(p, BS_PART + 1 + BD, bi, sbase, pol); }
    }
    b_gemm(p, sbase, BS_WUV, BS_END, 512, sbase + M_CH, sbase + M_CL, CP, bi, pol);
    TS(12);
    if (CLU) {
        if (tid < 128) {
            const uint32_t xo = sbase + M_QB + ((tid >> 1) & 3) * QP + (tid >> 3) * 16 + (tid & 1) * 8;
            st_tagged2(&g_ctx[bi * 128 + tid], __uint_as_float(lds32(xo)), __uint_as_float(lds32(xo + 4)), epoch + 1);
        }
        return;
    }
    if (tid == 0) {
#pragma unroll 1
        for (int i = 0; i < 4; i++) {
            mbar_expect_tx(sbase + M_BAR + i * 8, 36864);
            tma3d(sbase + i * 36864, &p.tm_wo, 0, bi * 128 + i * 32, 0, sbase + M_BAR + i * 8, pol);
        }
    }
    TS(8);
    {
        float acc[9][4];
#pragma unroll
        for (int j = 0; j < 9; j++) { acc[j][0] = acc[j][1] = acc[j][2] = acc[j][3] = 0.f; }
#pragma unroll 1
        for (int i = 0; i < 4; i++) {
            const uint32_t xo = sbase + M_QB + (g & 3) * QP + i * 64 + t * 4;
            const uint32_t a0[4] = {lds32(xo), 0u, lds32(xo + 16), 0u}, a1[4] = {lds32(xo + 32), 0u, lds32(xo + 48), 0u};
            mbar_wait(sbase + M_BAR + i * 8, 0);
#pragma unroll
            for (int j = 0; j < 9; j++) {
                const int nt = warp * 9 + j;
                uint32_t w[4];
                ldsm4t(w, sbase + i * 36864 + (nt >> 3) * 4096 + lane * 128 + (((nt & 7) ^ (lane & 7)) * 16));
                mma16816(acc[j], a0, w[0], w[1]);
                mma16816(acc[j], a1, w[2], w[3]);
            }
        }
        if (g < 4) {
#pragma unroll
            for (int j = 0; j < 9; j++) {
                const int c2 = (warp * 9 + j) * 4 + t;
                st_tagged2(&g_outb[((c2 / 9) * NH + bi) * 36 + g * 9 + c2 % 9], acc[j][0], acc[j][1], epoch + 1);
            }
        }
    }
    TS(9);
    {
        const uint4* src = g_outb + (bi * NH + (tid >> 3)) * 36 + (tid & 7);
        float2* part = reinterpret_cast<float2*>(red);
        unsigned n = 0;
        while (true) {
            ulonglong2 v[5];
            bool ok = true;
#pragma unroll
            for (int i = 0; i < 5; i++)
                if (i < 4 || (tid & 7) < 4) v[i] = ld_tagged2(src + i * 8);
#pragma unroll
            for (int i = 0; i < 5; i++)
                if (i < 4 || (tid & 7) < 4) {
                    ok = ok && (unsigned)(v[i].x >> 32) == epoch + 1 && (unsigned)(v[i].y >> 32) == epoch + 1;
                    part[(tid >> 3) * 36 + (tid & 7) + i * 8] = make_float2(__uint_as_float((unsigned)v[i].x), __uint_as_float((unsigned)v[i].y));
                }
            if (ok) break;
            __nanosleep(400);
            if (++n > SPIN_LIMIT) __trap();
        }
        __syncthreads();
        if (tid < 36) {
            float s0 = 0.f, s1 = 0.f;
#pragma unroll 8
            for (int h = 0; h < NH; h++) { const float2 v = part[h * 36 + tid]; s0 += v.x; s1 += v.y; }
            *reinterpret_cast<uint32_t*>(p.out + (tid / 9) * 2 * DM + DM + bi * 18 + (tid % 9) * 2) = pack_bf16(s0, s1);
        }
    }
    TS(10);
}

template <bool CLU>
__global__ void __launch_bounds__(256, 1) fused_decode_kernel(const __grid_constant__ First f, const __grid_constant__ Params p) {
    extern __shared__ __align__(1024) char smem_raw[];
    const uint32_t sbase = (smem_u32(smem_raw) + 1023u) & ~1023u;
    char* smem = smem_raw + (sbase - smem_u32(smem_raw));
    const int tid = threadIdx.x, warp = tid >> 5, lane = tid & 31;
    const int blk = blockIdx.x;
    const bool isB = CLU ? blk < NBCTA : (blk & 3) == 0 && (blk >> 2) < NBCTA;
    const int bi = CLU ? blk : blk >> 2;
    const int nb = CLU ? blk - NBCTA : blk - min(NBCTA, (blk + 3) >> 2);
    const int nblk = CLU ? 8 * MINCL : gridDim.x, nnb = nblk - NBCTA;
    const int nstatic = nnb * (NW + XW);
    uint64_t pol, poln;
    asm volatile("createpolicy.fractional.L2::evict_first.b64 %0, 1.0;" : "=l"(pol));
    asm volatile("createpolicy.fractional.L2::evict_normal.b64 %0, 1.0;" : "=l"(poln));
    const uint32_t wbar = sbase + M_BAR + warp * 8, wslot = sbase + warp * SLOT;
    const bool hold = ((blk >> 2) >> KMIN << KMIN) * 4 * UPP < nstatic;
    const uint32_t jbar = sbase + M_BAR + (NSLOT + BRING) * 8, fbar = sbase + M_BAR + 4 * 8;
    const char* eptr = f.ptr[3 + (tid >> 10)];
    asm volatile("" : "+l"(eptr));
    if (warp < 4) {
        if (lane == 0) {
            if (warp == 0) {
                mbar_init(jbar, 1);
                asm volatile("fence.mbarrier_init.release.cluster;" ::: "memory");
                mbar_expect_tx(jbar, 36864 + 4 * 1152);
                if (CLU || blk < 128) tma3d(sbase + J0W, &p.tm_j0, blk * 32, 0, 0, jbar, poln);
            } else if (warp & 1) {
                if (warp & 2) {
#pragma unroll
                    for (int i = 0; i < NSLOT + BRING; i++) mbar_init(sbase + M_BAR + i * 8, 1);
                    mbar_expect_tx(fbar, NEARLY * TILE_BYTES);
                } else if (CLU && !isB) {
#pragma unroll
                    for (int i = 0; i < 2; i++) {
                        mbar_init(sbase + F_BAR + i * 8, 1);
                        mbar_expect_tx(sbase + F_BAR + i * 8, 1024);
                    }
                }
                asm volatile("fence.mbarrier_init.release.cluster;" ::: "memory");
            } else {
#pragma unroll
                for (int i = 0; i < 4; i++) asm volatile("st.shared.v4.u32 [%0], {%1,%1,%1,%1};" ::"r"(sbase + M_HELP + i * 16), "r"(0) : "memory");
            }
        }
    } else if (!isB) {
        const unsigned t = tid - 128;
        const char* const* q = f.ptr + (tid >> 10);
        asm volatile("{\n.reg .pred p;\nsetp.ne.u32 p, %1, 0;\n@p prefetch.global.L2 [%0];\n}"
                     ::"l"(q[0] + (nb * 8 + (t >> 4)) * 8192 + (t & 15) * 128), "r"((uint32_t)(nb < DM / 8)) : "memory");
        asm volatile("{\n.reg .pred p;\nsetp.ne.u32 p, %1, 0;\n@p prefetch.global.L2 [%0];\n}"
                     ::"l"(q[2] + t * 128), "r"((uint32_t)(nb == DM / 8 && t < 36)) : "memory");
    } else if (tid == 128) {
        asm volatile("prefetch.tensormap [%0];" ::"l"(&p.tm_j0) : "memory");
        asm volatile("prefetch.tensormap [%0];" ::"l"(&p.tm_wq) : "memory");
    }
    __syncthreads();
    if (tid == 128) {
        if (CLU || blk < 128) bulk_load(sbase + M_XA, f.ptr[2], 4608, jbar, poln);
        if (!isB && !hold)
            bulk_load(sbase, f.ptr[1] + (size_t)((nb * NEARLY >> 7) * (NH * UPP) + (nb * NEARLY & 127)) * TILE_BYTES, NEARLY * TILE_BYTES, fbar, pol);
    }
    const int u0 = ((warp / NEARLY) * nnb + nb) * NEARLY + warp % NEARLY;
    unsigned epoch = 0;
    if (lane == 0) epoch = ld_relaxed4(eptr);
    TS(0);
    if (CLU && !isB) asm volatile("barrier.cluster.arrive.relaxed.aligned;" ::: "memory");
    if ((warp >> 1) == 2 && blk < 128) st_relaxed64(&g_qll[((tid - 128) >> 4) * 2048 + blk * 16 + (tid & 15)], 0ull);
    if (isB || warp >= NW + XW) epoch = __shfl_sync(~0u, epoch, 0);
    if (isB && tid == 96) {
        if (hold) { unsigned n = 0; while (ld_acquire_cta_shared(sbase + M_HELP + 24) < 2) { if (++n > (SPIN_LIMIT << 4)) __trap(); } }
#pragma unroll 1
        for (int b = 0; b < 4; b++) bulk_load(sbase + M_XB + b * XP, p.xb + b * DM, 1152, sbase + M_BAR + NSLOT * 8, pol);
#pragma unroll 1
        for (int n = 0; n < BD; n++) b_issue(p, n, bi, sbase, pol);
    }
    if (warp >= 4 && blk < 128) {
        const int g = lane >> 2, t = lane & 3, j = tid - 128;
#pragma unroll 1
        for (int sl = blk, ph = 0;; sl += 128 - nblk, ph = 1) {
        mbar_wait(jbar, ph);
        TS(13);
        float acc[4][4];
#pragma unroll
        for (int i = 0; i < 16; i++) acc[i >> 2][i & 3] = 0.f;
        const uint32_t wa = sbase + J0W + ((warp - 4) * 144 + (lane & 15)) * 64;
        const uint32_t sw = (lane >> 1) & 3, xa = sbase + M_XA + (g & 3) * 1152 + (warp - 4) * 288 + t * 4;
#pragma unroll 3
        for (int s = 0; s < 9; s++) {
            const uint32_t a[4] = {lds32(xa + s * 32), 0u, lds32(xa + s * 32 + 16), 0u};
            uint32_t w0[4], w1[4];
            ldsm4t(w0, wa + s * 1024 + (((lane >> 4) ^ sw) * 16));
            ldsm4t(w1, wa + s * 1024 + (((2 + (lane >> 4)) ^ sw) * 16));
            mma16816(acc[0], a, w0[0], w0[1]);
            mma16816(acc[1], a, w0[2], w0[3]);
            mma16816(acc[2], a, w1[0], w1[1]);
            mma16816(acc[3], a, w1[2], w1[3]);
        }
        float2* j0 = reinterpret_cast<float2*>(smem + M_J0);
        if (g < 4) {
#pragma unroll
            for (int i = 0; i < 4; i++) j0[(warp - 4) * 64 + g * 16 + i * 4 + t] = make_float2(acc[i][0], acc[i][1]);
        }
        asm volatile("bar.sync 1, 128;" ::: "memory");
        const bool again = sl == blk && blk + 128 - nblk >= nblk;
        if (again && tid == 224) {
            mbar_expect_tx(jbar, 36864);
            tma3d(sbase + J0W, &p.tm_j0, (blk + 128 - nblk) * 32, 0, 0, jbar, pol);
        }
        if (warp < 6) {
            const float2 v0 = j0[j], v1 = j0[64 + j], v2 = j0[128 + j], v3 = j0[192 + j];
            st_relaxed64(&g_qll[(j >> 4) * 2048 + sl * 16 + (j & 15)],
                         (unsigned long long)pack_bf16((v0.x + v1.x) + (v2.x + v3.x), (v0.y + v1.y) + (v2.y + v3.y)) |
                             ((unsigned long long)(epoch + 1) << 32));
            __syncwarp();
            if (lane == 0) asm volatile("red.relaxed.cta.shared::cta.add.u32 [%0], 1;" ::"r"(sbase + M_HELP + 24) : "memory");
        } else if (warp == 7) {
            if (blk < C_LINES) g_ctl[(epoch & 1) ^ 1][blk][lane] = 0;
        }
        TS(1);
        if (!again) break;
        asm volatile("bar.sync 1, 128;" ::: "memory");
        }
    }
    if (isB) {
        b_chain<CLU>(p, smem, sbase, bi, epoch, pol);
        return;
    }
    if (warp < NW + XW) {
        a_worker<CLU>(p, u0, warp >= NW + ((nb & 3) < (CLU ? X3C : X3) ? 1 : 0), hold, nstatic, wslot, wbar, warp < NEARLY && !hold ? fbar : wbar,
                      sbase + M_HELP, epoch, pol);
        if (CLU && nb < NFIN) {
            if (warp == 3) out_issue_sum(p, sbase, nb >> 3, nb & 7, pol);
            else if (warp == 0) out_late(sbase, nb & 7);
        }
        return;
    } else if (warp == 7) {
#pragma unroll 1
        for (int i = nb; i < 4 * NH; i += nnb) g_oacc[i * 32 + lane] = make_float4(0.f, 0.f, 0.f, 0.f);
        if (nb < NREP * NH) g_vdone[nb][lane] = 0;
        __syncwarp();
        k_helper(sbase + M_HELP, epoch);
        if (nb == 0 && lane == 0) g_epoch = epoch + 1;
        __syncwarp();
        if (CLU && nb < NFIN) out_early(sbase, nb & 7, epoch + 1);
    } else if (CLU) {
    } else if (warp == 6 && nb < NFIN) {
        finisher(p, sbase, nb);
        TS(4);
    } else if (warp >= 6 - NPOLL && nb < NFIN) {
        v_poller(sbase, nb, warp - (6 - NPOLL));
    }
    if (CLU && nb < NFIN) out_project(sbase, nb & 7, warp - 4);
}

}

typedef CUresult (*EncodeFn)(CUtensorMap*, CUtensorMapDataType, cuuint32_t, void*, const cuuint64_t*, const cuuint64_t*,
                             const cuuint32_t*, const cuuint32_t*, CUtensorMapInterleave, CUtensorMapSwizzle,
                             CUtensorMapL2promotion, CUtensorMapFloatOOBfill);

extern "C" void kernel_launch(void* const* d_in, const int* in_sizes, int n_in, void* d_out, int out_size) {
    (void)in_sizes; (void)n_in; (void)out_size;
    static int nsm = 0, ncl = 0;
    static EncodeFn encode = nullptr;
    static const char* epoch_ptr = nullptr;
    cudaLaunchConfig_t cfg = {};
    cudaLaunchAttribute at[1];
    at[0].id = cudaLaunchAttributeClusterDimension;
    at[0].val.clusterDim.x = 8; at[0].val.clusterDim.y = 1; at[0].val.clusterDim.z = 1;
    cfg.blockDim = dim3(256); cfg.dynamicSmemBytes = SMEM_BYTES; cfg.stream = cudaStreamPerThread; cfg.attrs = at; cfg.numAttrs = 1;
    if (nsm == 0) {
        int dev = 0;
        cudaGetDevice(&dev);
        cudaDeviceGetAttribute(&nsm, cudaDevAttrMultiProcessorCount, dev);
        cudaFuncSetAttribute(fused_decode_kernel<false>, cudaFuncAttributeMaxDynamicSharedMemorySize, SMEM_BYTES);
        cudaFuncSetAttribute(fused_decode_kernel<true>, cudaFuncAttributeMaxDynamicSharedMemorySize, SMEM_BYTES);
        cfg.gridDim = dim3(128);
        if (cudaOccupancyMaxActiveClusters(&ncl, fused_decode_kernel<true>, &cfg) != cudaSuccess) { ncl = 0; (void)cudaGetLastError(); }
        if (ncl > MINCL) ncl = MINCL;
        cudaGetSymbolAddress((void**)&epoch_ptr, g_epoch);
        void* fn = nullptr;
        cudaDriverEntryPointQueryResult qr;
        cudaGetDriverEntryPoint("cuTensorMapEncodeTiled", &fn, cudaEnableDefault, &qr);
        encode = (EncodeFn)fn;
    }
    Params p;
    auto panels = [&](CUtensorMap* tm, void* ptr, int rows, int cols, int box_rows, int box_panels) {
        const cuuint64_t gd[3] = {64, (cuuint64_t)rows, (cuuint64_t)(cols / 64)}, gs[2] = {(cuuint64_t)cols * 2, 128};
        const cuuint32_t box[3] = {64, (cuuint32_t)box_rows, (cuuint32_t)box_panels}, es[3] = {1, 1, 1};
        encode(tm, CU_TENSOR_MAP_DATA_TYPE_BFLOAT16, 3, ptr, gd, gs, box, es, CU_TENSOR_MAP_INTERLEAVE_NONE,
               CU_TENSOR_MAP_SWIZZLE_128B, CU_TENSOR_MAP_L2_PROMOTION_L2_256B, CU_TENSOR_MAP_FLOAT_OOB_FILL_NONE);
    };
    panels(&p.tm_wq, d_in[7], DM, 4096, 128, 2);
    panels(&p.tm_wuk, d_in[8], 512, 4096, 128, 2);
    panels(&p.tm_wuv, d_in[9], 512, 4096, 128, 2);
    panels(&p.tm_wo, d_in[10], 4096, DM, 32, 9);
    panels(&p.tm_wf, d_in[10], 4096, DM, 128, 1);
    panels(&p.tm_ckv, d_in[6], 4 * SK, 512, 32, 8);
    {
        const cuuint64_t gd[3] = {4096, 192, 3}, gs[2] = {8192, 192 * 8192};
        const cuuint32_t box[3] = {32, 192, 3}, es[3] = {1, 1, 1};
        encode(&p.tm_j0, CU_TENSOR_MAP_DATA_TYPE_BFLOAT16, 3, d_in[3], gd, gs, box, es, CU_TENSOR_MAP_INTERLEAVE_NONE,
               CU_TENSOR_MAP_SWIZZLE_64B, CU_TENSOR_MAP_L2_PROMOTION_L2_128B, CU_TENSOR_MAP_FLOAT_OOB_FILL_NONE);
    }
    {
        const cuuint64_t gd[3] = {DM, 512, 8}, gs[2] = {8 * DM * 2, DM * 2};
        const cuuint32_t box[3] = {64, 16, 8}, es[3] = {1, 1, 1};
        encode(&p.tm_wl, CU_TENSOR_MAP_DATA_TYPE_BFLOAT16, 3, d_in[4], gd, gs, box, es, CU_TENSOR_MAP_INTERLEAVE_NONE,
               CU_TENSOR_MAP_SWIZZLE_128B, CU_TENSOR_MAP_L2_PROMOTION_L2_256B, CU_TENSOR_MAP_FLOAT_OOB_FILL_NONE);
    }
    p.xa = (const __nv_bfloat16*)d_in[0];
    p.kc = (const __nv_bfloat16*)d_in[1];
    p.vc = (const __nv_bfloat16*)d_in[2];
    p.wo = (const __nv_bfloat16*)d_in[4];
    p.xb = (const __nv_bfloat16*)d_in[5];
    p.wob = (const __nv_bfloat16*)d_in[10];
    p.out = (__nv_bfloat16*)d_out;
    const First f = {{(const char*)d_in[3], (const char*)d_in[1], (const char*)d_in[0], epoch_ptr}};
    if (ncl >= MINCL) {
        cfg.gridDim = dim3(8 * ncl);
        cudaLaunchKernelEx(&cfg, fused_decode_kernel<true>, f, p);
    } else {
        fused_decode_kernel<false><<<nsm, 256, SMEM_BYTES, cudaStreamPerThread>>>(f, p);
    }
}
```

```cpp
#include <cuda_runtime.h>
#include <cuda.h>
#include <cuda_bf16.h>
#include <stdint.h>

namespace {

constexpr int NH = 32, SK = 4096, DM = 576;
constexpr int KEYS = 128;
constexpr int UPP = SK / KEYS;
constexpr int NUK = 4 * NH * UPP;
constexpr int TILE_BYTES = KEYS * 256;
#define NWORK 2
constexpr int NW = NWORK;
constexpr int NBCTA = 32;
constexpr int MINCL = 15;
constexpr int NFIN = 72;
constexpr int SLOT = 32768;
constexpr int NSLOT = 6;
constexpr int BRING = 5;
constexpr int J0W = 5 * SLOT;
constexpr int MISC = NSLOT * SLOT + 4096;
constexpr int XP = 1168, CP = 1040, QP = 272;
constexpr int M_XA = MISC;
constexpr int M_XB = M_XA + 4 * XP;
constexpr int M_CH = M_XB + 4 * XP;
constexpr int M_CL = M_CH + 4 * CP;
constexpr int M_QB = M_CL + 4 * CP;
constexpr int M_QA = M_CH;
constexpr int M_J0 = M_QB + 4 * QP;
constexpr int M_P = M_J0 + 2048;
constexpr int M_ALPHA = M_P + 2560;
constexpr int M_OMEGA = M_ALPHA + 128;
constexpr int M_BAR = M_OMEGA + 128;
constexpr int M_HELP = M_BAR + 128;
constexpr int F_W = 3 * SLOT;
constexpr int F_X = NSLOT * SLOT, FXP = 1088;
constexpr int F_RECV = F_X + 8 * FXP;
constexpr int F_BAR = M_P;
constexpr int SMEM_BYTES = M_HELP + 128 + 1024;
static_assert(F_RECV + 2048 <= M_J0, "output phase layout");
static_assert(SMEM_BYTES <= 232448 && M_BAR % 8 == 0 && M_QA % 16 == 0 && M_P % 16 == 0, "smem layout");
#define XW 2
#define X3 1
#define X3C 2
#define NEARLY 2
#define BD 4
#define FPF 3
#define FSLEEP 800
#define VMINC 2
#define FJ 265
#define FP 384
#define NPOLL 2
#define PGAP 200
static_assert(NW + XW == 4 && 4 % NEARLY == 0 && BD <= BRING, "slots 4 and 5 hold the finisher weights");
constexpr int KMIN = 2, KMAX = 4, VMAX = 4;
constexpr float SCALE = 0.08838834764831845f;
constexpr float LOG2E = 1.4426950408889634f;
constexpr unsigned SPIN_LIMIT = 1u << 24;

#define NREP 2
constexpr int C_QUEUE = 0, C_KDONE = 1, C_BBAR = 3, C_LINES = 5;

struct First { const char* ptr[4]; };
struct Params {
    const __nv_bfloat16 *kc, *vc, *wo, *xb;
    __nv_bfloat16* out;
    CUtensorMap tm_j0;
    CUtensorMap tm_wq, tm_wuk, tm_ckv, tm_wuv, tm_wo;
    CUtensorMap tm_wl;
    CUtensorMap tm_wf;
};

__device__ unsigned g_epoch;
__device__ unsigned g_ctl[2][C_LINES][32];
__device__ uint2 g_qll[4 * 2048];
__device__ uint2 g_scores[128 * SK / 4];
__device__ float2 g_stats[128 * UPP];
__device__ float4 g_oacc[128 * 32];
__device__ unsigned g_vdone[NREP * NH][32];
__device__ uint4 g_qabs[4 * 8 * 4 * 4 * 32];
__device__ float2 g_bpart[NBCTA * NH * 256];
__device__ float2 g_bml[NBCTA * NH];
__device__ uint4 g_ctx[NH * 128];
__device__ uint4 g_outb[NBCTA * NH * 36];

#define TS(i)
#define TSV(i, v)
#define LAND(i)
#define CLK(x)
#define ACC(a, x, y)

__device__ __forceinline__ uint32_t smem_u32(const void* p) { return (uint32_t)__cvta_generic_to_shared(p); }
__device__ __forceinline__ void mbar_init(uint32_t bar, uint32_t cnt) {
    asm volatile("mbarrier.init.shared::cta.b64 [%0], %1;" ::"r"(bar), "r"(cnt) : "memory");
}
__device__ __forceinline__ void mbar_expect_tx(uint32_t bar, uint32_t bytes) {
    asm volatile("mbarrier.arrive.expect_tx.shared::cta.b64 _, [%0], %1;" ::"r"(bar), "r"(bytes) : "memory");
}
__device__ __forceinline__ bool mbar_try(uint32_t bar, uint32_t parity) {
    uint32_t ok;
    asm volatile("{\n.reg .pred p;\nmbarrier.try_wait.parity.shared::cta.b64 p, [%1], %2;\nselp.u32 %0, 1, 0, p;\n}\n"
                 : "=r"(ok) : "r"(bar), "r"(parity) : "memory");
    return ok;
}
__device__ __forceinline__ void mbar_wait(uint32_t bar, uint32_t parity) {
    unsigned n = 0;
    while (!mbar_try(bar, parity)) { if (++n > SPIN_LIMIT) __trap(); }
}
__device__ __forceinline__ void bulk_load(uint32_t dst, const void* src, uint32_t bytes, uint32_t bar, uint64_t pol) {
    asm volatile("cp.async.bulk.shared::cluster.global.mbarrier::complete_tx::bytes.L2::cache_hint [%0], [%1], %2, [%3], %4;"
                 ::"r"(dst), "l"(src), "r"(bytes), "r"(bar), "l"(pol) : "memory");
}
__device__ __forceinline__ void tma3d(uint32_t dst, const CUtensorMap* tm, int c0, int c1, int c2, uint32_t bar, uint64_t pol) {
    asm volatile("cp.async.bulk.tensor.3d.shared::cluster.global.mbarrier::complete_tx::bytes.L2::cache_hint [%0], [%1, {%3,%4,%5}], [%2], %6;"
                 ::"r"(dst), "l"(tm), "r"(bar), "r"(c0), "r"(c1), "r"(c2), "l"(pol) : "memory");
}
__device__ __forceinline__ void l2_prefetch(const void* src, uint32_t bytes) {
    asm volatile("cp.async.bulk.prefetch.L2.global [%0], %1;" ::"l"(src), "r"(bytes) : "memory");
}
__device__ __forceinline__ void ldsm4(uint32_t (&r)[4], uint32_t addr) {
    asm volatile("ldmatrix.sync.aligned.m8n8.x4.shared.b16 {%0,%1,%2,%3}, [%4];"
                 : "=r"(r[0]), "=r"(r[1]), "=r"(r[2]), "=r"(r[3]) : "r"(addr));
}
__device__ __forceinline__ void ldsm4t(uint32_t (&r)[4], uint32_t addr) {
    asm volatile("ldmatrix.sync.aligned.m8n8.x4.trans.shared.b16 {%0,%1,%2,%3}, [%4];"
                 : "=r"(r[0]), "=r"(r[1]), "=r"(r[2]), "=r"(r[3]) : "r"(addr));
}
__device__ __forceinline__ void mma16816(float (&d)[4], const uint32_t (&a)[4], uint32_t b0, uint32_t b1) {
    asm("mma.sync.aligned.m16n8k16.row.col.f32.bf16.bf16.f32 {%0,%1,%2,%3}, {%4,%5,%6,%7}, {%8,%9}, {%0,%1,%2,%3};"
        : "+f"(d[0]), "+f"(d[1]), "+f"(d[2]), "+f"(d[3])
        : "r"(a[0]), "r"(a[1]), "r"(a[2]), "r"(a[3]), "r"(b0), "r"(b1));
}
__device__ __forceinline__ void wgmma_tile(float (&d)[4], uint32_t da, uint32_t db, int accumulate) {
    asm volatile("{\n.reg .pred p;\n.reg .b32 x, y;\n.reg .b64 a, b;\nsetp.ne.u32 p, %6, 0;\nwgmma.fence.sync.aligned;\n"
                 "add.u32 x, %4, 0;\nadd.u32 y, %5, 0;\nmov.b64 a, {x, 0x40000040};\nmov.b64 b, {y, 1};\n"
                 "wgmma.mma_async.sync.aligned.m64n8k16.f32.bf16.bf16 {%0,%1,%2,%3}, a, b, p, 1, 1, 1, 0;\n"
                 "add.u32 x, %4, 128;\nadd.u32 y, %5, 8;\nmov.b64 a, {x, 0x40000040};\nmov.b64 b, {y, 1};\n"
                 "wgmma.mma_async.sync.aligned.m64n8k16.f32.bf16.bf16 {%0,%1,%2,%3}, a, b, 1, 1, 1, 1, 0;\n"
                 "add.u32 x, %4, 256;\nadd.u32 y, %5, 16;\nmov.b64 a, {x, 0x40000040};\nmov.b64 b, {y, 1};\n"
                 "wgmma.mma_async.sync.aligned.m64n8k16.f32.bf16.bf16 {%0,%1,%2,%3}, a, b, 1, 1, 1, 1, 0;\n"
                 "add.u32 x, %4, 384;\nadd.u32 y, %5, 24;\nmov.b64 a, {x, 0x40000040};\nmov.b64 b, {y, 1};\n"
                 "wgmma.mma_async.sync.aligned.m64n8k16.f32.bf16.bf16 {%0,%1,%2,%3}, a, b, 1, 1, 1, 1, 0;\n"
                 "add.u32 x, %4, 512;\nadd.u32 y, %5, 32;\nmov.b64 a, {x, 0x40000040};\nmov.b64 b, {y, 1};\n"
                 "wgmma.mma_async.sync.aligned.m64n8k16.f32.bf16.bf16 {%0,%1,%2,%3}, a, b, 1, 1, 1, 1, 0;\n"
                 "add.u32 x, %4, 640;\nadd.u32 y, %5, 40;\nmov.b64 a, {x, 0x40000040};\nmov.b64 b, {y, 1};\n"
                 "wgmma.mma_async.sync.aligned.m64n8k16.f32.bf16.bf16 {%0,%1,%2,%3}, a, b, 1, 1, 1, 1, 0;\n"
                 "add.u32 x, %4, 768;\nadd.u32 y, %5, 48;\nmov.b64 a, {x, 0x40000040};\nmov.b64 b, {y, 1};\n"
                 "wgmma.mma_async.sync.aligned.m64n8k16.f32.bf16.bf16 {%0,%1,%2,%3}, a, b, 1, 1, 1, 1, 0;\n"
                 "add.u32 x, %4, 896;\nadd.u32 y, %5, 56;\nmov.b64 a, {x, 0x40000040};\nmov.b64 b, {y, 1};\n"
                 "wgmma.mma_async.sync.aligned.m64n8k16.f32.bf16.bf16 {%0,%1,%2,%3}, a, b, 1, 1, 1, 1, 0;\n"
                 "wgmma.commit_group.sync.aligned;\n}"
                 : "+f"(d[0]), "+f"(d[1]), "+f"(d[2]), "+f"(d[3]) : "r"(da), "r"(db), "r"(accumulate) : "memory");
}
__device__ __forceinline__ uint32_t lds32(uint32_t a) {
    uint32_t v;
    asm volatile("ld.shared.u32 %0, [%1];" : "=r"(v) : "r"(a));
    return v;
}
__device__ __forceinline__ unsigned ld_acquire(const unsigned* p) {
    unsigned v;
    asm volatile("ld.acquire.gpu.global.u32 %0, [%1];" : "=r"(v) : "l"(p) : "memory");
    return v;
}
__device__ __forceinline__ uint2 ld_relaxed8(const void* p) {
    uint2 v;
    asm volatile("ld.relaxed.gpu.global.v2.u32 {%0,%1}, [%2];" : "=r"(v.x), "=r"(v.y) : "l"(p) : "memory");
    return v;
}
__device__ __forceinline__ unsigned ld_relaxed4(const void* p) {
    unsigned v;
    asm volatile("ld.relaxed.gpu.global.u32 %0, [%1];" : "=r"(v) : "l"(p) : "memory");
    return v;
}
__device__ __forceinline__ unsigned atom_inc(unsigned* p) {
    unsigned v;
    asm volatile("atom.relaxed.gpu.global.inc.u32 %0, [%1], 0x7fffffff;" : "=r"(v) : "l"(p) : "memory");
    return v;
}
__device__ __forceinline__ unsigned long long ld_relaxed64(const void* p) {
    unsigned long long v;
    asm volatile("ld.relaxed.gpu.global.u64 %0, [%1];" : "=l"(v) : "l"(p) : "memory");
    return v;
}
__device__ __forceinline__ void st_relaxed64(void* p, unsigned long long v) {
    asm volatile("st.relaxed.gpu.global.u64 [%0], %1;" ::"l"(p), "l"(v) : "memory");
}
__device__ __forceinline__ float4 ld_relaxed16(const void* p) {
    float4 v;
    asm volatile("ld.relaxed.gpu.global.v4.f32 {%0,%1,%2,%3}, [%4];" : "=f"(v.x), "=f"(v.y), "=f"(v.z), "=f"(v.w) : "l"(p) : "memory");
    return v;
}
__device__ __forceinline__ uint32_t mapa(uint32_t a, uint32_t rank) {
    uint32_t r;
    asm("mapa.shared::cluster.u32 %0, %1, %2;" : "=r"(r) : "r"(a), "r"(rank));
    return r;
}
__device__ __forceinline__ void mbar_spin(uint32_t bar) {
    asm volatile("{\n.reg .pred p, q;\n.reg .u32 n;\nmov.u32 n, 0;\n"
                 "SPIN:\nmbarrier.test_wait.parity.shared::cta.b64 p, [%0], 0;\nadd.u32 n, n, 1;\nsetp.gt.u32 q, n, 0x4000000;\n@q trap;\n"
                 "@!p bra.uni SPIN;\n}" ::"r"(bar) : "memory");
}
__device__ __forceinline__ void mbar_spin_cluster(uint32_t bar) {
    asm volatile("{\n.reg .pred p, q;\n.reg .u32 n;\nmov.u32 n, 0;\n"
                 "SPIN:\nmbarrier.test_wait.parity.relaxed.cluster.shared::cta.b64 p, [%0], 0;\nadd.u32 n, n, 1;\nsetp.gt.u32 q, n, 0x4000000;\n@q trap;\n"
                 "@!p bra.uni SPIN;\nfence.acquire.sync_restrict::shared::cluster.cluster;\n}" ::"r"(bar) : "memory");
}
__device__ __forceinline__ uint32_t now_ns() {
    unsigned long long t;
    asm volatile("mov.u64 %0, %globaltimer;" : "=l"(t));
    return (uint32_t)t;
}
__device__ __forceinline__ void fence_gpu() { asm volatile("fence.acq_rel.gpu;" ::: "memory"); }
__device__ __forceinline__ void red_add_u32(unsigned* p, unsigned v) {
    asm volatile("red.relaxed.gpu.global.add.u32 [%0], %1;" ::"l"(p), "r"(v) : "memory");
}
__device__ __forceinline__ void st_tagged2(void* p, float a, float b, unsigned tag) {
    const unsigned long long hi = (unsigned long long)tag << 32;
    asm volatile("st.relaxed.gpu.global.v2.b64 [%0], {%1,%2};" ::"l"(p), "l"(hi | __float_as_uint(a)), "l"(hi | __float_as_uint(b)) : "memory");
}
__device__ __forceinline__ ulonglong2 ld_tagged2(const void* p) {
    ulonglong2 v;
    asm volatile("ld.relaxed.gpu.global.v2.b64 {%0,%1}, [%2];" : "=l"(v.x), "=l"(v.y) : "l"(p) : "memory");
    return v;
}
__device__ __forceinline__ float4 atom_add_f4(void* p, float a, float b, float c, float d) {
    float4 r;
    asm volatile("atom.relaxed.gpu.global.add.v4.f32 {%0,%1,%2,%3}, [%4], {%5,%6,%7,%8};"
                 : "=f"(r.x), "=f"(r.y), "=f"(r.z), "=f"(r.w) : "l"(p), "f"(a), "f"(b), "f"(c), "f"(d) : "memory");
    return r;
}
__device__ __forceinline__ void red_release_cta_shared(uint32_t a, unsigned v) {
    asm volatile("red.release.cta.shared::cta.add.u32 [%0], %1;" ::"r"(a), "r"(v) : "memory");
}
__device__ __forceinline__ unsigned ld_acquire_cta_shared(uint32_t a) {
    unsigned v;
    asm volatile("ld.acquire.cta.shared::cta.u32 %0, [%1];" : "=r"(v) : "r"(a) : "memory");
    return v;
}
__device__ __forceinline__ void st_release_cta_shared(uint32_t a, unsigned v) {
    asm volatile("st.release.cta.shared::cta.u32 [%0], %1;" ::"r"(a), "r"(v) : "memory");
}
__device__ __forceinline__ void wait_count(const unsigned* p, unsigned target) {
    unsigned n = 0;
    while (ld_acquire(p) < target) { if (++n > SPIN_LIMIT) __trap(); }
}
__device__ __forceinline__ uint32_t pack_bf16(float lo, float hi) {
    uint32_t r;
    asm("cvt.rn.bf16x2.f32 %0, %1, %2;" : "=r"(r) : "f"(hi), "f"(lo));
    return r;
}
__device__ __forceinline__ float bf_lo(uint32_t v) { return __uint_as_float(v << 16); }
__device__ __forceinline__ float bf_hi(uint32_t v) { return __uint_as_float(v & 0xffff0000u); }
__device__ __forceinline__ float ex2(float x) { float y; asm("ex2.approx.ftz.f32 %0, %1;" : "=f"(y) : "f"(x)); return y; }
__device__ __forceinline__ float expsub(float a, float b) { return ex2((a - b) * LOG2E); }
__device__ __forceinline__ float warp_max(float v) {
#pragma unroll
    for (int m = 16; m; m >>= 1) v = fmaxf(v, __shfl_xor_sync(~0u, v, m));
    return v;
}
__device__ __forceinline__ float warp_sum(float v) {
#pragma unroll
    for (int m = 16; m; m >>= 1) v += __shfl_xor_sync(~0u, v, m);
    return v;
}
template <bool CLU>
__device__ __forceinline__ unsigned unit_block(int u) {
    const unsigned x = ((unsigned)u & (NUK - 1)) / UPP;
    const int lg = u < NUK ? min(KMAX, max(KMIN, 29 - __clz(x | 1))) : min(VMAX, max(CLU ? VMINC : 0, 29 - __clz((127 - x) | 1)));
    const unsigned r = x & ((4u << lg) - 1);
    return ((x - r + (r & ((1u << lg) - 1)) * 4 + (r >> lg)) * UPP) | ((unsigned)u & (UPP - 1));
}
__device__ __forceinline__ const char* block_src(const void* base, unsigned blk) {
    const unsigned po = blk / UPP;
    return reinterpret_cast<const char*>(base) + (size_t)(((po & 3) * NH + (po >> 2)) * UPP + blk % UPP) * TILE_BYTES;
}

template <bool CLU>
__device__ __forceinline__ void a_worker(const Params& p, int un, bool once, bool hold, int nstatic, uint32_t slot, uint32_t bar, uint32_t wb,
                                         uint32_t help, unsigned epoch, uint64_t pol) {
    constexpr int NU = 2 * NUK;
    const int lane = threadIdx.x & 31, g = lane >> 2, t = lane & 3;
    const int li = lane & 7;
    uint32_t kaddr[4], vaddr[8];
    {
        const int e = (lane >> 3) & 1, kk = lane >> 4;
#pragma unroll
        for (int s = 0; s < 4; s++) kaddr[s] = slot + (16 * li + e) * 256 + ((2 * s + kk + li) & 7) * 16;
        const int vrow = 4 * (li >> 1) + (li & 1) + 2 * kk;
#pragma unroll
        for (int c = 0; c < 8; c++) vaddr[c] = slot + vrow * 256 + e * 128 + ((c + li) & 7) * 16;
#pragma unroll
        for (int c = 0; c < 8; c++) asm volatile("" : "+r"(vaddr[c]));
    }
    const uint32_t vmask = (g >> 1) != t ? 0u : ((g & 1) ? 0xffff0000u : 0xffffu);
    int kseen = -1;
    unsigned long long H0 = 0, H1 = 0;
    auto header = [&](int v, unsigned vb) {
        if (v >= NU) return;
        const void *a0, *a1;
        if (v < NUK) {
            const unsigned po = vb / UPP;
            a0 = g_qll + (po & 3) * 2048 + (po >> 2) * 64 + lane;
            a1 = reinterpret_cast<const uint2*>(a0) + 32;
        } else {
            const int half = vb / (NUK / 2);
            if (half > kseen) {
                unsigned n = 0;
                while (ld_acquire_cta_shared(help + 12 + 4 * half) == 0) { if (++n > (SPIN_LIMIT << 4)) __trap(); }
                kseen = half;
            }
            a0 = &g_scores[vb * (KEYS / 4) + lane];
            a1 = &g_stats[(vb / UPP) * UPP + lane];
        }
        H0 = ld_relaxed64(a0);
        H1 = ld_relaxed64(a1);
    };
    epoch = __shfl_sync(~0u, epoch, 0);
    if (hold) { unsigned n = 0; while (ld_acquire_cta_shared(help + 24) < 2) { if (++n > (SPIN_LIMIT << 4)) __trap(); } }
    unsigned (*ctl)[32] = g_ctl[epoch & 1];
    const unsigned tag = epoch + 1;
    unsigned nxt = once ? NU : 0;
    int u = -1;
    unsigned bu = 0, bn = unit_block<CLU>(un);
    bool have = false;
    uint32_t phase = 0;
    unsigned kpend = 0;
    const unsigned zero = gridDim.x >> 24;
    uint32_t Q[16];
    float4 oret = make_float4(0.f, 0.f, 0.f, 0.f);
    while (true) {
        const char* nsrc = block_src(un < NUK ? p.kc : p.vc, bn);
        float4* odst = &g_oacc[(bu / UPP) * 32 + lane];
        unsigned* vdst = &g_vdone[(lane & (NREP - 1)) * NH + bu / (4 * UPP)][0];
        float d[8][4];
        CLK(c1);
        asm volatile("" : "+l"(odst));
        if (u >= NUK) {
#pragma unroll
            for (int j = 0; j < 8; j++) { d[j][0] = d[j][1] = d[j][2] = d[j][3] = 0.f; }
            mbar_wait(wb, phase);
            LAND(NUK + bu);
            uint32_t a[2][8][4];
#pragma unroll
            for (int c = 0; c < 8; c++) ldsm4t(a[0][c], vaddr[c]);
#pragma unroll
            for (int j = 0; j < 8; j++) {
                if (j < 7) {
#pragma unroll
                    for (int c = 0; c < 8; c++) ldsm4t(a[(j + 1) & 1][c], vaddr[c] + (j + 1) * 4096);
                }
#pragma unroll
                for (int c = 0; c < 8; c++) mma16816(d[c], a[j & 1][c], Q[2 * j], Q[2 * j + 1]);
            }
            float o[4];
#pragma unroll
            for (int r = 0; r < 2; r++) {
                o[2 * r] = d[0][2 * r] + d[7][2 * r + 1];
                o[2 * r + 1] = d[0][2 * r + 1] + d[1][2 * r];
#pragma unroll
                for (int k = 1; k < 4; k++) {
                    const int src = (lane & 28) | ((t - k) & 3);
                    o[2 * r] += __shfl_sync(~0u, d[2 * k][2 * r] + d[2 * k - 1][2 * r + 1], src);
                    o[2 * r + 1] += __shfl_sync(~0u, d[2 * k][2 * r + 1] + d[2 * k + 1][2 * r], src);
                }
            }
            oret = atom_add_f4(odst, o[0], o[1], o[2], o[3]);
        } else if (u >= 0) {
#pragma unroll
            for (int j = 0; j < 8; j++) { d[j][0] = d[j][1] = d[j][2] = d[j][3] = 0.f; }
            mbar_wait(wb, phase);
            LAND(bu);
            uint32_t a[2][8][4];
#pragma unroll
            for (int j = 0; j < 8; j++) ldsm4(a[0][j], kaddr[0] + (4 * (j & 3) + 2 * (j >> 2)) * 256);
#pragma unroll
            for (int s = 0; s < 8; s++) {
                if (s < 7) {
#pragma unroll
                    for (int j = 0; j < 8; j++)
                        ldsm4(a[(s + 1) & 1][j], kaddr[(s + 1) & 3] + (4 * (j & 3) + 2 * (j >> 2)) * 256 + ((s + 1) >> 2) * 128);
                }
#pragma unroll
                for (int j = 0; j < 8; j++)
                    mma16816(d[j], a[s & 1][j], Q[(s & 4) * 2 + ((2 * s - 2 * j) & 7)], Q[(s & 4) * 2 + ((2 * s + 1 - 2 * j) & 7)]);
            }
        }
        const bool pre = wb != bar;
        if (u >= 0) { phase = pre ? 0 : phase ^ 1; wb = bar; }
        CLK(c2b);
        if (un < NU && lane == 0) {
            if (!once) nxt = atom_inc(&ctl[C_QUEUE][0]);
            if (u >= 0 || !pre) {
                mbar_expect_tx(bar, TILE_BYTES);
                bulk_load(slot, nsrc, TILE_BYTES, bar, pol);
            }
        }
        const uint32_t tiss = now_ns();
        CLK(c3);
        if ((unsigned)u < (unsigned)NUK) {
            const int j0 = (t - (g >> 1)) & 3;
            float v[4];
#pragma unroll
            for (int q = 0; q < 4; q++) {
                const int jq = (q >> 1) * 4, e = (q & 1) * 2;
                const float x0 = (g & 1) ? d[jq + 0][e + 1] : d[jq + 0][e];
                const float x1 = (g & 1) ? d[jq + 1][e + 1] : d[jq + 1][e];
                const float x2 = (g & 1) ? d[jq + 2][e + 1] : d[jq + 2][e];
                const float x3 = (g & 1) ? d[jq + 3][e + 1] : d[jq + 3][e];
                const float y0 = (j0 & 1) ? x1 : x0, y1 = (j0 & 1) ? x3 : x2;
                v[q] = (j0 & 2) ? y1 : y0;
            }
            const uint32_t r0 = pack_bf16(v[0], v[1]), r1 = pack_bf16(v[2], v[3]);
            const uint32_t s0 = pack_bf16(bf_lo(r0) * SCALE, bf_hi(r0) * SCALE);
            const uint32_t s1 = pack_bf16(bf_lo(r1) * SCALE, bf_hi(r1) * SCALE);
            g_scores[bu * (KEYS / 4) + 4 * g + j0] = make_uint2(s0, s1);
            const float f0 = bf_lo(s0), f1 = bf_hi(s0), f2 = bf_lo(s1), f3 = bf_hi(s1);
            const float m = warp_max(fmaxf(fmaxf(f0, f1), fmaxf(f2, f3)));
            const float l = warp_sum((expsub(f0, m) + expsub(f1, m)) + (expsub(f2, m) + expsub(f3, m)));
            if (lane == 0) g_stats[bu] = make_float2(m, l);
            kpend++;
            if (un / (NUK / 2) != u / (NUK / 2)) {
                __syncwarp();
                if (lane == 0) {
                    red_release_cta_shared(help + 4 * (u / (NUK / 2)), kpend);
                    if (un >= NUK) red_release_cta_shared(help + 8, 1u);
                }
                kpend = 0;
            }
        }
        CLK(c4);
        int unn = NU;
        if (un < NU) {
            unsigned n = 0;
            while (true) {
                if (!have) header(un, bn);
                if (un >= NUK || __all_sync(~0u, (uint32_t)(H0 >> 32) == tag && (uint32_t)(H1 >> 32) == tag)) break;
                if (++n > SPIN_LIMIT) __trap();
                have = false;
            }
            if (un >= NUK) {
                const uint32_t s0 = (uint32_t)H0, s1 = (uint32_t)(H0 >> 32);
                const float mu = __uint_as_float((uint32_t)H1);
                const float m = warp_max(mu);
                const float l = warp_sum(__uint_as_float((uint32_t)(H1 >> 32)) * expsub(mu, m));
                const float inv = 1.0f / l;
                const uint32_t w0 = pack_bf16(expsub(bf_lo(s0), m) * inv, expsub(bf_hi(s0), m) * inv);
                const uint32_t w1 = pack_bf16(expsub(bf_lo(s1), m) * inv, expsub(bf_hi(s1), m) * inv);
#pragma unroll
                for (int j = 0; j < 8; j++) {
                    Q[2 * j] = __shfl_sync(~0u, w0, 4 * j + t) & vmask;
                    Q[2 * j + 1] = __shfl_sync(~0u, w1, 4 * j + t) & vmask;
                }
            } else {
#pragma unroll
                for (int j = 0; j < 8; j++) {
                    const int src = (((j + g) & 7) << 2) + t;
                    Q[j] = __shfl_sync(~0u, (uint32_t)H0, src);
                    Q[8 + j] = __shfl_sync(~0u, (uint32_t)H1, src);
                }
            }
            unn = nstatic + (int)__shfl_sync(~0u, nxt, 0);
            if (CLU && !once && unn >= NU && lane == 0)
                asm volatile("st.relaxed.cta.shared::cta.u32 [%0], %1;" ::"r"(help + 28), "r"((tiss + (FJ - (unn - NU)) * 10) | 1u) : "memory");
        }
        if (u >= NUK && lane < (CLU ? 1 : NREP))
            red_add_u32(vdst,
                        1u + ((__float_as_uint(oret.x) | __float_as_uint(oret.y) | __float_as_uint(oret.z) | __float_as_uint(oret.w)) & zero));
        if (un >= NU) break;
        bu = bn;
        have = !(un < NUK && unn >= NUK && !(un >= NUK / 2 && unn < NUK + NUK / 2));
        bn = unit_block<CLU>(unn);
        if (have) header(unn, bn);
        u = un;
        un = unn;
    }
}

__device__ __forceinline__ void k_helper(uint32_t help, unsigned epoch) {
    if ((threadIdx.x & 31) != 0) return;
    unsigned (*ctl)[32] = g_ctl[epoch & 1];
    unsigned sent0 = 0, sent1 = 0, n = 0;
    int seen = 0;
    bool fin = false;
    while (!fin || seen < 2) {
        if (!fin) {
            fin = ld_acquire_cta_shared(help + 8) == NW + XW;
            const unsigned c0 = ld_acquire_cta_shared(help), c1 = ld_acquire_cta_shared(help + 4);
            if (c0 != sent0 || c1 != sent1) {
                fence_gpu();
                if (c0 != sent0) red_add_u32(&ctl[C_KDONE][0], c0 - sent0);
                if (c1 != sent1) red_add_u32(&ctl[C_KDONE + 1][0], c1 - sent1);
                sent0 = c0; sent1 = c1;
            }
        }
        if (seen < 2 && ld_acquire(&ctl[C_KDONE + seen][0]) >= NUK / 2) {
            st_release_cta_shared(help + 12 + 4 * seen, 1u);
            seen++;
        } else {
            __nanosleep(300);
        }
        if (++n > SPIN_LIMIT) __trap();
    }
}

__device__ __forceinline__ void v_poller(uint32_t sbase, int f, int w) {
    const int lane = threadIdx.x & 31;
    const unsigned (*cp)[32] = &g_vdone[((f * NPOLL + w) % NREP) * NH];
    unsigned n = 0;
    while (ld_acquire_cta_shared(sbase + M_HELP + 12) == 0) { __nanosleep(1000); if (++n > SPIN_LIMIT) __trap(); }
    int h = 0;
    bool fast = false;
    while (h < NH) {
        const unsigned r = __ballot_sync(~0u, ld_acquire(&cp[min(h + (lane & 3), NH - 1)][0]) >= 4 * UPP) & 15u;
        if (r & 1) {
            h = min(NH, h + __ffs(~r) - 1);
            __syncwarp();
            if (lane == 0) asm volatile("red.release.cta.shared::cta.max.u32 [%0], %1;" ::"r"(sbase + M_HELP + 20), "r"(h) : "memory");
        }
        if (h < NH - 4) {
            __nanosleep(h ? 300 : 1000);
        } else if (!fast) {
            fast = true;
            const long long t0 = clock64();
            while (clock64() - t0 < w * PGAP) {}
        }
        if (++n > SPIN_LIMIT) __trap();
    }
}
__device__ __forceinline__ void finisher(const Params& p, uint32_t sbase, int f) {
    const int lane = threadIdx.x & 31;
    {
        const char* wg = reinterpret_cast<const char*>(p.wo);
        const uint32_t dst = sbase + 4 * SLOT + (16 * (lane & 7) + (lane >> 3)) * 16;
#pragma unroll 1
        for (int h = -FPF - 4; h < NH; h++) {
            if (lane == 0 && (unsigned)(h + FPF) < (unsigned)NH) l2_prefetch(wg + (size_t)(h + FPF) * 147456 + f * 2048, 2048);
            if (h >= 0) {
#pragma unroll
                for (int r = 0; r < 4; r++)
                    asm volatile("cp.async.cg.shared.global [%0], [%1], 16;" ::"r"(dst + h * 2048 + ((r & 1) * 4 + (r >> 1) * 8) * 16),
                                 "l"(wg + (size_t)(h * 128 + r * 32 + lane) * (DM * 2) + f * 16) : "memory");
            }
            __nanosleep(FSLEEP);
        }
        asm volatile("cp.async.wait_all;" ::: "memory");
        __syncwarp();
    }
    TS(11);
    const float4* vec = g_oacc + ((lane >> 2) & 3) * 32 + (lane >> 4) * 16 + (lane & 3);
    float acc[2][2][4];
#pragma unroll
    for (int i = 0; i < 16; i++) acc[i >> 3][(i >> 2) & 1][i & 3] = 0.f;
    uint32_t* outp = reinterpret_cast<uint32_t*>(p.out + (lane >> 2) * (2 * DM) + f * 8 + (lane & 3) * 2);
    uint32_t wa = sbase + 4 * SLOT + lane * 16;
    auto project = [&](const float4 (&x)[4], const uint32_t (&w)[4][4]) {
#pragma unroll
        for (int s = 0; s < 4; s++) {
            const uint32_t a[4] = {pack_bf16(x[s].x, x[s].y), 0u, pack_bf16(x[s].z, x[s].w), 0u};
            mma16816(acc[0][s & 1], a, w[s >> 1][(s & 1) * 2], w[s >> 1][(s & 1) * 2 + 1]);
            mma16816(acc[1][s & 1], a, w[2 + (s >> 1)][(s & 1) * 2], w[2 + (s >> 1)][(s & 1) * 2 + 1]);
        }
    };
    int h = 0;
    unsigned n = 0;
    while (h < NH) {
        uint32_t w[4][4];
#pragma unroll
        for (int q = 0; q < 4; q++) ldsm4t(w[q], wa + q * 512);
        int ready;
        while ((ready = ld_acquire_cta_shared(sbase + M_HELP + 20)) <= h) {
            if (h < NH - 3) __nanosleep(100);
            if (++n > (SPIN_LIMIT << 4)) __trap();
        }
        float4 x[4], y[4];
#pragma unroll
        for (int s = 0; s < 4; s++) x[s] = ld_relaxed16(vec + s * 4);
        const bool two = ready > h + 1;
        if (two) {
#pragma unroll
            for (int s = 0; s < 4; s++) y[s] = ld_relaxed16(vec + 128 + s * 4);
        }
        project(x, w);
        if (two) {
#pragma unroll
            for (int q = 0; q < 4; q++) ldsm4t(w[q], wa + 2048 + q * 512);
            project(y, w);
        }
        const int nr = two ? 2 : 1;
        h += nr;
        vec += nr * 128;
        wa += nr * 2048;
        const float o0 = acc[0][0][0] + acc[0][1][0] + __shfl_down_sync(~0u, acc[1][0][0] + acc[1][1][0], 16);
        const float o1 = acc[0][0][1] + acc[0][1][1] + __shfl_down_sync(~0u, acc[1][0][1] + acc[1][1][1], 16);
        asm volatile("{\n.reg .pred p;\nsetp.ne.u32 p, %2, 0;\n@p st.global.u32 [%0], %1;\n}" ::"l"(outp), "r"(pack_bf16(o0, o1)),
                     "r"((uint32_t)(lane < 16 && h == NH)) : "memory");
    }
}

__device__ __forceinline__ void out_fetch(uint32_t sbase, int step, int h) {
    const int lane = threadIdx.x & 31, g = lane >> 2;
    float4 x[4];
#pragma unroll
    for (int b = 0; b < 4; b++) x[b] = ld_relaxed16(&g_oacc[(h * 4 + ((b + g) & 3)) * 32 + lane]);
#pragma unroll
    for (int b = 0; b < 4; b++) {
        const uint32_t a = sbase + F_X + step * FXP + g * 128 + ((b + g) & 3) * 16 + (lane & 3) * 4;
        asm volatile("st.shared.u32 [%0], %1;\nst.shared.u32 [%0 + 64], %2;" ::"r"(a), "r"(pack_bf16(x[b].x, x[b].y)), "r"(pack_bf16(x[b].z, x[b].w)) : "memory");
    }
    asm volatile("fence.proxy.async.shared::cta;" ::: "memory");
}
__device__ __forceinline__ void out_early(uint32_t sbase, int rank, unsigned tag) {
    const int lane = threadIdx.x & 31;
    if (lane < 10) {
        mbar_init(sbase + F_BAR + 16 + lane * 8, lane < 7 ? 1 : lane == 7 ? 2 : 4);
        if (lane < 8) mbar_expect_tx(sbase + F_BAR + 16 + lane * 8, 16384);
    }
    asm volatile("fence.mbarrier_init.release.cluster;" ::: "memory");
    unsigned n = 0;
#pragma unroll 1
    for (int i = 0; i < 3; i++) {
        while (ld_acquire(&g_vdone[8 * i + rank][0]) < 4 * UPP) { __nanosleep(500); if (++n > SPIN_LIMIT) __trap(); }
        out_fetch(sbase, 4 + i, 8 * i + rank);
#pragma unroll 1
        for (int j = 0; j < 16 && i == 0;) {
            const ulonglong2 v = ld_tagged2(&g_ctx[((j >> 2) * 8 + rank) * 128 + (j & 3) * 32 + lane]);
            if (__all_sync(~0u, (unsigned)(v.x >> 32) == tag && (unsigned)(v.y >> 32) == tag)) {
                asm volatile("st.shared.v2.u32 [%0], {%1,%2};" ::"r"(sbase + F_X + (j >> 2) * FXP + ((j & 3) * 32 + lane) * 8), "r"((uint32_t)v.x), "r"((uint32_t)v.y) : "memory");
                j++;
            } else {
                __nanosleep(500);
                if (++n > SPIN_LIMIT) __trap();
            }
        }
    }
    __syncwarp();
    if (lane == 0) st_release_cta_shared(sbase + M_HELP + 32, 1u);
}
__device__ __forceinline__ void out_late(uint32_t sbase, int rank) {
    unsigned n = 0;
    while (ld_acquire_cta_shared(sbase + M_HELP + 32) == 0) { if (++n > (SPIN_LIMIT << 4)) __trap(); }
    while (ld_acquire(&g_vdone[24 + rank][0]) < 4 * UPP) { if (++n > SPIN_LIMIT) __trap(); }
    TS(12);
    out_fetch(sbase, 7, 24 + rank);
    __syncwarp();
    if ((threadIdx.x & 31) == 0) asm volatile("mbarrier.arrive.shared::cta.b64 _, [%0];" ::"r"(sbase + F_BAR + 72) : "memory");
    TS(13);
}
__device__ __forceinline__ void out_project(uint32_t sbase, int rank, int w) {
    const int lane = threadIdx.x & 31, g = lane >> 2, t = lane & 3;
    unsigned n = 0;
    while (ld_acquire_cta_shared(sbase + M_HELP + 32) == 0) { __nanosleep(500); if (++n > SPIN_LIMIT) __trap(); }
    asm volatile("barrier.cluster.wait.acquire.aligned;" ::: "memory");
    uint32_t rdst = mapa(sbase + F_RECV + rank * 128 + (g & 3) * 32 + t * 16, 2 * w + (g >> 2)), rbar = mapa(sbase + F_BAR, 2 * w + (g >> 2));
    while (ld_acquire_cta_shared(sbase + M_HELP + 28) == 0) { __nanosleep(200); if (++n > SPIN_LIMIT) __trap(); }
    const uint32_t da = (1u << 16) | (((sbase + F_W) & 0x3ffff) >> 4), db = (4u << 16) | (((sbase + F_X) & 0x3ffff) >> 4);
    float d[4] = {0.f, 0.f, 0.f, 0.f};
#pragma unroll
    for (int i = 0; i < 8; i++) {
        mbar_spin(sbase + F_BAR + 16 + i * 8);
        wgmma_tile(d, da + (i % 6) * 1024, db + i * (FXP / 16), i & 3);
        if (i < 2 || (i & 3) == 3) asm volatile("wgmma.wait_group.sync.aligned 0;" : "+f"(d[0]), "+f"(d[1]), "+f"(d[2]), "+f"(d[3])::"memory");
        if (i < 2) {
            asm volatile("{\n.reg .pred p;\nsetp.eq.u32 p, %1, 0;\n@p mbarrier.arrive.shared::cta.b64 _, [%0];\n}"
                         ::"r"(sbase + F_BAR + 80 + i * 8), "r"(lane) : "memory");
        } else if ((i & 3) == 3) {
            if (t < 2)
                asm volatile("st.async.weak.shared::cluster.mbarrier::complete_tx::bytes.v4.f32 [%0], {%1,%2,%3,%4}, [%5];"
                             ::"r"(rdst), "f"(d[0]), "f"(d[1]), "f"(d[2]), "f"(d[3]), "r"(rbar) : "memory");
            __syncwarp();
            rdst += 1024;
            rbar += 8;
            asm volatile("" : "+r"(rdst), "+r"(rbar));
        }
    }
}
__device__ __forceinline__ void out_issue_sum(const Params& p, uint32_t sbase, int c, int rank, uint64_t pol) {
    const int lane = threadIdx.x & 31;
    if (lane == 0) {
        unsigned n = 0;
        while (ld_acquire_cta_shared(sbase + M_HELP + 32) == 0) { __nanosleep(500); if (++n > SPIN_LIMIT) __trap(); }
        asm volatile("prefetch.tensormap [%0];" ::"l"(&p.tm_wf) : "memory");
        asm volatile("prefetch.tensormap [%0];" ::"l"(&p.tm_wl) : "memory");
        uint32_t t0;
        while ((t0 = ld_acquire_cta_shared(sbase + M_HELP + 28)) == 0) { __nanosleep(100); if (++n > SPIN_LIMIT) __trap(); }
#pragma unroll 1
        for (int i = 0; i < 8; i++) {
            const int h = (i & 3) * 8 + rank;
            if (i >= 6) mbar_wait(sbase + F_BAR + 32 + i * 8, 0);
            for (int k = 0; k < 4096 && (int)(now_ns() - t0) < 0; k++) {}
            if (i == 0) TS(16);
            tma3d(sbase + F_W + (i < 6 ? i : i - 6) * 16384, i < 4 ? &p.tm_wf : &p.tm_wl, i < 4 ? 0 : c * 64, i < 4 ? h * 128 : h * 16,
                  i < 4 ? c : 0, sbase + F_BAR + 16 + i * 8, pol);
            t0 += FP;
        }
        TS(17);
    }
    __syncwarp();
    __nv_bfloat16* dst = p.out + (((lane >> 1) & 2) + (lane & 1)) * (2 * DM) + DM + c * 64 + (rank >> 1) * 16 + (lane & 2) * 4 +
                         (rank & 1) * 4 + (lane >> 3);
    uint32_t src = sbase + F_RECV + lane * 4;
#pragma unroll 1
    for (int r = 0; r < 2; r++) {
        asm volatile("" : "+l"(dst), "+r"(src));
        mbar_spin_cluster(sbase + F_BAR + r * 8);
        float x[8];
#pragma unroll
        for (int i = 0; i < 8; i++) asm volatile("ld.shared.f32 %0, [%1];" : "=f"(x[i]) : "r"(src + i * 128) : "memory");
        const float v = ((x[0] + x[1]) + (x[2] + x[3])) + ((x[4] + x[5]) + (x[6] + x[7]));
        asm volatile("st.global.u16 [%0], %1;" ::"l"(dst), "h"((unsigned short)pack_bf16(v, 0.f)) : "memory");
        TS(14 + r);
        dst -= DM;
        src += 1024;
    }
}

constexpr int BS_WUK = 5, BS_Q = 9, BS_CKV = 11, BS_PART = 27, BS_WUV = 29, BS_END = 33;

__device__ __noinline__ void b_issue(const Params& p, int n, int bi, uint32_t sbase, uint64_t pol) {
    if (n >= BS_END || (n >= BS_Q && n < BS_CKV) || (n >= BS_PART && n < BS_WUV)) return;
    const uint32_t bar = sbase + M_BAR + (NSLOT + n % BRING) * 8;
    const CUtensorMap* tm;
    int row, panel = 2 * bi;
    if (n < BS_WUK) { tm = &p.tm_wq; row = n * 128; }
    else if (n < BS_Q) { tm = &p.tm_wuk; row = (n - BS_WUK) * 128; }
    else if (n < BS_PART) {
        tm = &p.tm_ckv; panel = 0;
        row = (bi >> 3) * SK + ((n - BS_CKV) * 8 + (bi & 7)) * 32;
    }
    else { tm = &p.tm_wuv; row = (n - BS_WUV) * 128; }
    mbar_expect_tx(bar, n == 0 ? 32768 + 4 * 1152 : 32768);
    tma3d(sbase + (n % BRING) * SLOT, tm, 0, row, panel, bar, pol);
}
__device__ __forceinline__ void b_issue_xchg(int n, const void* src, uint32_t sbase, uint64_t pol) {
    asm volatile("fence.proxy.async;" ::: "memory");
#pragma unroll
    for (int i = 0; i < 2; i++) {
        const uint32_t bar = sbase + M_BAR + (NSLOT + (n + i) % BRING) * 8;
        mbar_expect_tx(bar, 32768);
        bulk_load(sbase + ((n + i) % BRING) * SLOT, reinterpret_cast<const char*>(src) + i * 32768, 32768, bar, pol);
    }
}
__device__ __forceinline__ void b_wait(int n, uint32_t sbase) {
    mbar_wait(sbase + M_BAR + (NSLOT + n % BRING) * 8, (n / BRING) & 1);
}

__device__ __noinline__ void b_gemm(const Params& p, uint32_t sbase, int n0, int n1, int ktot, uint32_t xh, uint32_t xl, int pitch,
                                    int bi, uint64_t pol) {
    const int tid = threadIdx.x, warp = tid >> 5, lane = tid & 31, g = lane >> 2, t = lane & 3;
    const uint32_t woff = (warp >> 2) * 16384 + (lane & 15) * 128 + ((((warp & 3) * 2 + (lane >> 4)) ^ (lane & 7)) * 16);
    const uint32_t xoff = (g & 3) * pitch + t * 4;
    float acc[2][4];
#pragma unroll
    for (int i = 0; i < 8; i++) acc[i >> 2][i & 3] = 0.f;
#pragma unroll 1
    for (int n = n0; n < n1; n++) {
        b_wait(n, sbase);
        const uint32_t slot = sbase + (n % BRING) * SLOT + woff;
        const int k0 = (n - n0) * 128;
        const int ns = min(8, (ktot - k0) >> 4);
#pragma unroll 2
        for (int s = 0; s < ns; s++) {
            uint32_t a[4], w[4];
            const uint32_t xo = xoff + (k0 + 16 * s) * 2;
            a[0] = lds32(xh + xo); a[2] = lds32(xh + xo + 16);
            a[1] = xl ? lds32(xl + xo) : 0u; a[3] = xl ? lds32(xl + xo + 16) : 0u;
            ldsm4t(w, slot + s * 2048);
            mma16816(acc[0], a, w[0], w[1]);
            mma16816(acc[1], a, w[2], w[3]);
        }
        __syncthreads();
        if (tid == 0) b_issue(p, n + BD, bi, sbase, pol);
    }
    if (g < 4) {
#pragma unroll
        for (int j = 0; j < 2; j++)
            asm volatile("st.shared.u32 [%0], %1;" ::"r"(sbase + M_QB + g * QP + (warp * 16 + j * 8 + t * 2) * 2),
                         "r"(pack_bf16(acc[j][0] + acc[j][2], acc[j][1] + acc[j][3])) : "memory");
    }
    __syncthreads();
}

__device__ __forceinline__ void b_exchange(unsigned* c, int n, const void* src, uint32_t sbase, uint64_t pol) {
    TS(n == BS_Q ? 24 : 28);
    __syncthreads();
    if (threadIdx.x == 0) {
        TS(n == BS_Q ? 25 : 29);
        fence_gpu();
        TS(n == BS_Q ? 26 : 30);
        red_add_u32(c, 1u);
        wait_count(c, NBCTA);
        TS(n == BS_Q ? 27 : 31);
        b_issue_xchg(n, src, sbase, pol);
    }
}

template <bool CLU>
__device__ __noinline__ void b_chain(const Params& p, char* smem, uint32_t sbase, int bi, unsigned epoch, uint64_t pol) {
    const int tid = threadIdx.x, warp = tid >> 5, lane = tid & 31, g = lane >> 2, t = lane & 3;
    unsigned (*ctl)[32] = g_ctl[epoch & 1];
    float* red = reinterpret_cast<float*>(smem + 5 * SLOT);
    b_gemm(p, sbase, 0, BS_WUK, DM, sbase + M_XB, 0, XP, bi, pol);
    TS(6);
    {
        uint32_t Q[16];
#pragma unroll
        for (int c = 0; c < 16; c++) Q[c] = lds32(sbase + M_QB + (g & 3) * QP + c * 16 + t * 4);
        float* qa = reinterpret_cast<float*>(smem + M_QA);
#pragma unroll 1
        for (int n = BS_WUK; n < BS_Q; n++) {
            b_wait(n, sbase);
            const uint32_t base = sbase + (n % BRING) * SLOT + (warp * 16 + (lane & 15)) * 128;
            float d[2][4];
#pragma unroll
            for (int i = 0; i < 8; i++) d[i >> 2][i & 3] = 0.f;
#pragma unroll
            for (int s = 0; s < 8; s++) {
                uint32_t a[4];
                ldsm4(a, base + (s >> 2) * 16384 + (((2 * (s & 3) + (lane >> 4)) ^ (lane & 7)) * 16));
                mma16816(d[s & 1], a, Q[2 * s], Q[2 * s + 1]);
            }
            const int c = (n - BS_WUK) * 128 + warp * 16 + g + 8 * (t >> 1);
            qa[(2 * (t & 1)) * 512 + c] = (t & 2) ? d[0][2] + d[1][2] : d[0][0] + d[1][0];
            qa[(2 * (t & 1) + 1) * 512 + c] = (t & 2) ? d[0][3] + d[1][3] : d[0][1] + d[1][1];
            __syncthreads();
            if (tid == 0) b_issue(p, n + BD, bi, sbase, pol);
        }
#pragma unroll 1
        for (int r = 0; r < 2; r++) {
            const int id = tid + r * 256;
            const int b = id >> 7, c0 = ((id >> 2) & 31) * 16 + (id & 3) * 2;
            const float2 u0 = *reinterpret_cast<const float2*>(qa + b * 512 + c0);
            const float2 u1 = *reinterpret_cast<const float2*>(qa + b * 512 + c0 + 8);
            const uint32_t h0 = pack_bf16(u0.x, u0.y), h1 = pack_bf16(u1.x, u1.y);
            const uint32_t l0 = pack_bf16(u0.x - bf_lo(h0), u0.y - bf_hi(h0)), l1 = pack_bf16(u1.x - bf_lo(h1), u1.y - bf_hi(h1));
            g_qabs[((id >> 2) * 4 + (bi >> 3)) * 32 + (bi & 7) * 4 + (id & 3)] = make_uint4(h0, l0, h1, l1);
        }
    }
    b_exchange(&ctl[C_BBAR][0], BS_Q, &g_qabs[(bi >> 3) * 4096], sbase, pol);
    {
        uint32_t qf[4][4][4];
        b_wait(BS_Q + (warp >> 2), sbase);
        TS(7);
        {
            const uint4* qs = reinterpret_cast<const uint4*>(smem + ((BS_Q + (warp >> 2)) % BRING) * SLOT) + (warp & 3) * 512 + lane;
#pragma unroll
            for (int s = 0; s < 4; s++)
#pragma unroll
                for (int i = 0; i < 4; i++) {
                    const uint4 v = qs[(s * 4 + i) * 32];
                    qf[i][s][0] = v.x; qf[i][s][1] = v.y; qf[i][s][2] = v.z; qf[i][s][3] = v.w;
                }
        }
        __syncthreads();
        if (tid == 0) { b_issue(p, BS_Q + BD, bi, sbase, pol); b_issue(p, BS_Q + 1 + BD, bi, sbase, pol); }
        float acc[2][8][4];
#pragma unroll
        for (int i = 0; i < 2; i++)
#pragma unroll
            for (int j = 0; j < 8; j++) { acc[i][j][0] = acc[i][j][1] = acc[i][j][2] = acc[i][j][3] = 0.f; }
        float mrun = -INFINITY, lrun = 0.f;
        const int head = tid >> 3, kq = tid & 7;
        float* alpha = reinterpret_cast<float*>(smem + M_ALPHA);
        for (int n = BS_CKV; n < BS_PART; n++) {
            b_wait(n, sbase);
            const uint32_t slot = sbase + (n % BRING) * SLOT;
            float sc[4][4][4];
#pragma unroll
            for (int i = 0; i < 4; i++)
#pragma unroll
                for (int j = 0; j < 4; j++) { sc[i][j][0] = sc[i][j][1] = sc[i][j][2] = sc[i][j][3] = 0.f; }
#pragma unroll
            for (int j = 0; j < 4; j++)
#pragma unroll
                for (int sp = 0; sp < 2; sp++) {
                    uint32_t bf[4];
                    ldsm4(bf, slot + warp * 4096 + (8 * j + (lane & 7)) * 128 + (((4 * sp + (lane >> 3)) ^ (lane & 7)) * 16));
#pragma unroll
                    for (int i = 0; i < 4; i++) {
                        mma16816(sc[i][j], qf[i][2 * sp], bf[0], bf[1]);
                        mma16816(sc[i][j], qf[i][2 * sp + 1], bf[2], bf[3]);
                    }
                }
#pragma unroll
            for (int i = 0; i < 4; i++)
#pragma unroll
                for (int j = 0; j < 4; j++)
                    *reinterpret_cast<float2*>(red + warp * 1024 + (8 * i + g) * 32 + ((8 * j) ^ (8 * (g & 3))) + 2 * t) =
                        make_float2(sc[i][j][0] + sc[i][j][2], sc[i][j][1] + sc[i][j][3]);
            __syncthreads();
            if (tid == 0 && n > BS_CKV) b_issue(p, n - 1 + BD, bi, sbase, pol);
            {
                float4 s = make_float4(0.f, 0.f, 0.f, 0.f);
#pragma unroll
                for (int w = 0; w < 8; w++) {
                    const float4 v = *reinterpret_cast<const float4*>(red + w * 1024 + head * 32 + ((4 * kq) ^ (8 * (head & 3))));
                    s.x += v.x; s.y += v.y; s.z += v.z; s.w += v.w;
                }
                const uint32_t r0 = pack_bf16(s.x, s.y), r1 = pack_bf16(s.z, s.w);
                const uint32_t s0 = pack_bf16(bf_lo(r0) * SCALE, bf_hi(r0) * SCALE);
                const uint32_t s1 = pack_bf16(bf_lo(r1) * SCALE, bf_hi(r1) * SCALE);
                const float f0 = bf_lo(s0), f1 = bf_hi(s0), f2 = bf_lo(s1), f3 = bf_hi(s1);
                float mx = fmaxf(fmaxf(f0, f1), fmaxf(f2, f3));
                mx = fmaxf(mx, __shfl_xor_sync(~0u, mx, 1));
                mx = fmaxf(mx, __shfl_xor_sync(~0u, mx, 2));
                mx = fmaxf(mx, __shfl_xor_sync(~0u, mx, 4));
                const float mnew = fmaxf(mrun, mx);
                const float al = expsub(mrun, mnew);
                const float p0 = expsub(f0, mnew), p1 = expsub(f1, mnew), p2 = expsub(f2, mnew), p3 = expsub(f3, mnew);
                lrun = lrun * al + ((p0 + p1) + (p2 + p3));
                mrun = mnew;
                *reinterpret_cast<uint2*>(smem + M_P + head * 80 + kq * 8) = make_uint2(pack_bf16(p0, p1), pack_bf16(p2, p3));
                if (kq == 0) alpha[head] = al;
            }
            __syncthreads();
            {
                uint32_t pf[2][2][4];
#pragma unroll
                for (int i = 0; i < 2; i++)
#pragma unroll
                    for (int ks = 0; ks < 2; ks++)
                        ldsm4(pf[i][ks], sbase + M_P + (16 * i + (lane & 15)) * 80 + (16 * ks + 8 * (lane >> 4)) * 2);
#pragma unroll
                for (int i = 0; i < 2; i++) {
                    const float a0 = alpha[16 * i + g], a1 = alpha[16 * i + 8 + g];
#pragma unroll
                    for (int j = 0; j < 8; j++) { acc[i][j][0] *= a0; acc[i][j][1] *= a0; acc[i][j][2] *= a1; acc[i][j][3] *= a1; }
                }
#pragma unroll
                for (int j = 0; j < 8; j++) {
                    uint32_t bf[4];
                    ldsm4t(bf, slot + warp * 4096 + lane * 128 + ((j ^ (lane & 7)) * 16));
#pragma unroll
                    for (int i = 0; i < 2; i++) {
                        mma16816(acc[i][j], pf[i][0], bf[0], bf[1]);
                        mma16816(acc[i][j], pf[i][1], bf[2], bf[3]);
                    }
                }
            }
        }
        __syncthreads();
        if (tid == 0) b_issue(p, BS_PART - 1 + BD, bi, sbase, pol);
        lrun += __shfl_xor_sync(~0u, lrun, 1);
        lrun += __shfl_xor_sync(~0u, lrun, 2);
        lrun += __shfl_xor_sync(~0u, lrun, 4);
        if (kq == 0) g_bml[head * NBCTA + bi] = make_float2(mrun, lrun);
#pragma unroll
        for (int i = 0; i < 2; i++)
#pragma unroll
            for (int j = 0; j < 8; j++) {
                g_bpart[((16 * i + g) * NBCTA + bi) * 256 + warp * 32 + j * 4 + t] = make_float2(acc[i][j][0], acc[i][j][1]);
                g_bpart[((16 * i + 8 + g) * NBCTA + bi) * 256 + warp * 32 + j * 4 + t] = make_float2(acc[i][j][2], acc[i][j][3]);
            }
    }
#pragma unroll 1
    for (int i = tid; i < NH * 36 && !(CLU); i += 256) g_outb[bi * NH * 36 + i] = make_uint4(0u, epoch, 0u, epoch);
    b_exchange(&ctl[C_BBAR + 1][0], BS_PART, &g_bpart[bi * NBCTA * 256], sbase, pol);
    {
        float* omega = reinterpret_cast<float*>(smem + M_OMEGA);
        if (warp == 0) {
            __syncwarp();
            const uint2 ml = ld_relaxed8(&g_bml[bi * NBCTA + lane]);
            const float ms = __uint_as_float(ml.x);
            float m = ms;
            m = fmaxf(m, __shfl_xor_sync(~0u, m, 1));
            m = fmaxf(m, __shfl_xor_sync(~0u, m, 2));
            m = fmaxf(m, __shfl_xor_sync(~0u, m, 4));
            const float w = expsub(ms, m);
            float l = w * __uint_as_float(ml.y);
            l += __shfl_xor_sync(~0u, l, 1);
            l += __shfl_xor_sync(~0u, l, 2);
            l += __shfl_xor_sync(~0u, l, 4);
            omega[lane] = w / l;
        }
        __syncthreads();
        b_wait(BS_PART, sbase);
        b_wait(BS_PART + 1, sbase);
#pragma unroll 1
        for (int b = 0; b < 4; b++) {
            const float2* ps = reinterpret_cast<const float2*>(smem + ((BS_PART + (b >> 1)) % BRING) * SLOT) + (b & 1) * 2048 + tid;
            float c0 = 0.f, c1 = 0.f;
#pragma unroll
            for (int s = 0; s < 8; s++) {
                const float w = omega[b * 8 + s];
                const float2 v = ps[s * 256];
                c0 = fmaf(w, v.x, c0);
                c1 = fmaf(w, v.y, c1);
            }
            const uint32_t hi = pack_bf16(c0, c1);
            *reinterpret_cast<uint32_t*>(smem + M_CH + b * CP + tid * 4) = hi;
            *reinterpret_cast<uint32_t*>(smem + M_CL + b * CP + tid * 4) = pack_bf16(c0 - bf_lo(hi), c1 - bf_hi(hi));
        }
        __syncthreads();
        if (tid == 0) { b_issue(p, BS_PART + BD, bi, sbase, pol); b_issue(p, BS_PART + 1 + BD, bi, sbase, pol); }
    }
    b_gemm(p, sbase, BS_WUV, BS_END, 512, sbase + M_CH, sbase + M_CL, CP, bi, pol);
    TS(12);
    if (CLU) {
        if (tid < 128) {
            const uint32_t xo = sbase + M_QB + ((tid >> 1) & 3) * QP + (tid >> 3) * 16 + (tid & 1) * 8;
            st_tagged2(&g_ctx[bi * 128 + tid], __uint_as_float(lds32(xo)), __uint_as_float(lds32(xo + 4)), epoch + 1);
        }
        return;
    }
    if (tid == 0) {
#pragma unroll 1
        for (int i = 0; i < 4; i++) {
            mbar_expect_tx(sbase + M_BAR + i * 8, 36864);
            tma3d(sbase + i * 36864, &p.tm_wo, 0, bi * 128 + i * 32, 0, sbase + M_BAR + i * 8, pol);
        }
    }
    TS(8);
    {
        float acc[9][4];
#pragma unroll
        for (int j = 0; j < 9; j++) { acc[j][0] = acc[j][1] = acc[j][2] = acc[j][3] = 0.f; }
#pragma unroll 1
        for (int i = 0; i < 4; i++) {
            const uint32_t xo = sbase + M_QB + (g & 3) * QP + i * 64 + t * 4;
            const uint32_t a0[4] = {lds32(xo), 0u, lds32(xo + 16), 0u}, a1[4] = {lds32(xo + 32), 0u, lds32(xo + 48), 0u};
            mbar_wait(sbase + M_BAR + i * 8, 0);
#pragma unroll
            for (int j = 0; j < 9; j++) {
                const int nt = warp * 9 + j;
                uint32_t w[4];
                ldsm4t(w, sbase + i * 36864 + (nt >> 3) * 4096 + lane * 128 + (((nt & 7) ^ (lane & 7)) * 16));
                mma16816(acc[j], a0, w[0], w[1]);
                mma16816(acc[j], a1, w[2], w[3]);
            }
        }
        if (g < 4) {
#pragma unroll
            for (int j = 0; j < 9; j++) {
                const int c2 = (warp * 9 + j) * 4 + t;
                st_tagged2(&g_outb[((c2 / 9) * NH + bi) * 36 + g * 9 + c2 % 9], acc[j][0], acc[j][1], epoch + 1);
            }
        }
    }
    TS(9);
    {
        const uint4* src = g_outb + (bi * NH + (tid >> 3)) * 36 + (tid & 7);
        float2* part = reinterpret_cast<float2*>(red);
        unsigned n = 0;
        while (true) {
            ulonglong2 v[5];
            bool ok = true;
#pragma unroll
            for (int i = 0; i < 5; i++)
                if (i < 4 || (tid & 7) < 4) v[i] = ld_tagged2(src + i * 8);
#pragma unroll
            for (int i = 0; i < 5; i++)
                if (i < 4 || (tid & 7) < 4) {
                    ok = ok && (unsigned)(v[i].x >> 32) == epoch + 1 && (unsigned)(v[i].y >> 32) == epoch + 1;
                    part[(tid >> 3) * 36 + (tid & 7) + i * 8] = make_float2(__uint_as_float((unsigned)v[i].x), __uint_as_float((unsigned)v[i].y));
                }
            if (ok) break;
            __nanosleep(400);
            if (++n > SPIN_LIMIT) __trap();
        }
        __syncthreads();
        if (tid < 36) {
            float s0 = 0.f, s1 = 0.f;
#pragma unroll 8
            for (int h = 0; h < NH; h++) { const float2 v = part[h * 36 + tid]; s0 += v.x; s1 += v.y; }
            *reinterpret_cast<uint32_t*>(p.out + (tid / 9) * 2 * DM + DM + bi * 18 + (tid % 9) * 2) = pack_bf16(s0, s1);
        }
    }
    TS(10);
}

template <bool CLU>
__global__ void __launch_bounds__(256, 1) fused_decode_kernel(const __grid_constant__ First f, const __grid_constant__ Params p) {
    extern __shared__ __align__(1024) char smem_raw[];
    const uint32_t sbase = (smem_u32(smem_raw) + 1023u) & ~1023u;
    char* smem = smem_raw + (sbase - smem_u32(smem_raw));
    const int tid = threadIdx.x, warp = tid >> 5, lane = tid & 31;
    const int blk = blockIdx.x;
    const bool isB = CLU ? blk < NBCTA : (blk & 3) == 0 && (blk >> 2) < NBCTA;
    const int bi = CLU ? blk : blk >> 2;
    const int nb = CLU ? blk - NBCTA : blk - min(NBCTA, (blk + 3) >> 2);
    const int nblk = CLU ? 8 * MINCL : gridDim.x, nnb = nblk - NBCTA;
    const int nstatic = nnb * (NW + XW);
    uint64_t pol, poln;
    asm volatile("createpolicy.fractional.L2::evict_first.b64 %0, 1.0;" : "=l"(pol));
    asm volatile("createpolicy.fractional.L2::evict_normal.b64 %0, 1.0;" : "=l"(poln));
    const uint32_t wbar = sbase + M_BAR + warp * 8, wslot = sbase + warp * SLOT;
    const bool hold = ((blk >> 2) >> KMIN << KMIN) * 4 * UPP < nstatic;
    const uint32_t jbar = sbase + M_BAR + (NSLOT + BRING) * 8, fbar = sbase + M_BAR + 4 * 8;
    const char* eptr = f.ptr[3 + (tid >> 10)];
    asm volatile("" : "+l"(eptr));
    if (warp < 4) {
        if (lane == 0) {
            if (warp == 0) {
                mbar_init(jbar, 1);
                asm volatile("fence.mbarrier_init.release.cluster;" ::: "memory");
                mbar_expect_tx(jbar, 36864 + 4 * 1152);
                if (CLU || blk < 128) tma3d(sbase + J0W, &p.tm_j0, blk * 32, 0, 0, jbar, poln);
            } else if (warp & 1) {
                if (warp & 2) {
#pragma unroll
                    for (int i = 0; i < NSLOT + BRING; i++) mbar_init(sbase + M_BAR + i * 8, 1);
                    mbar_expect_tx(fbar, NEARLY * TILE_BYTES);
                } else if (CLU && !isB) {
#pragma unroll
                    for (int i = 0; i < 2; i++) {
                        mbar_init(sbase + F_BAR + i * 8, 1);
                        mbar_expect_tx(sbase + F_BAR + i * 8, 1024);
                    }
                }
                asm volatile("fence.mbarrier_init.release.cluster;" ::: "memory");
            } else {
#pragma unroll
                for (int i = 0; i < 4; i++) asm volatile("st.shared.v4.u32 [%0], {%1,%1,%1,%1};" ::"r"(sbase + M_HELP + i * 16), "r"(0) : "memory");
            }
        }
    } else if (!isB) {
        const unsigned t = tid - 128;
        const char* const* q = f.ptr + (tid >> 10);
        asm volatile("{\n.reg .pred p;\nsetp.ne.u32 p, %1, 0;\n@p prefetch.global.L2 [%0];\n}"
                     ::"l"(q[0] + (nb * 8 + (t >> 4)) * 8192 + (t & 15) * 128), "r"((uint32_t)(nb < DM / 8)) : "memory");
        asm volatile("{\n.reg .pred p;\nsetp.ne.u32 p, %1, 0;\n@p prefetch.global.L2 [%0];\n}"
                     ::"l"(q[2] + t * 128), "r"((uint32_t)(nb == DM / 8 && t < 36)) : "memory");
    } else if (tid == 128) {
        asm volatile("prefetch.tensormap [%0];" ::"l"(&p.tm_j0) : "memory");
        asm volatile("prefetch.tensormap [%0];" ::"l"(&p.tm_wq) : "memory");
    }
    __syncthreads();
    if (tid == 128) {
        if (CLU || blk < 128) bulk_load(sbase + M_XA, f.ptr[2], 4608, jbar, poln);
        if (!isB && !hold)
            bulk_load(sbase, f.ptr[1] + (size_t)((nb * NEARLY >> 7) * (NH * UPP) + (nb * NEARLY & 127)) * TILE_BYTES, NEARLY * TILE_BYTES, fbar, pol);
    }
    const int u0 = ((warp / NEARLY) * nnb + nb) * NEARLY + warp % NEARLY;
    unsigned epoch = 0;
    if (lane == 0) epoch = ld_relaxed4(eptr);
    TS(0);
    if (CLU && !isB) asm volatile("barrier.cluster.arrive.relaxed.aligned;" ::: "memory");
    if ((warp >> 1) == 2 && blk < 128) st_relaxed64(&g_qll[((tid - 128) >> 4) * 2048 + blk * 16 + (tid & 15)], 0ull);
    if (isB || warp >= NW + XW) epoch = __shfl_sync(~0u, epoch, 0);
    if (isB && tid == 96) {
        if (hold) { unsigned n = 0; while (ld_acquire_cta_shared(sbase + M_HELP + 24) < 2) { if (++n > (SPIN_LIMIT << 4)) __trap(); } }
#pragma unroll 1
        for (int b = 0; b < 4; b++) bulk_load(sbase + M_XB + b * XP, p.xb + b * DM, 1152, sbase + M_BAR + NSLOT * 8, pol);
#pragma unroll 1
        for (int n = 0; n < BD; n++) b_issue(p, n, bi, sbase, pol);
    }
    if (warp >= 4 && blk < 128) {
        const int g = lane >> 2, t = lane & 3, j = tid - 128;
#pragma unroll 1
        for (int sl = blk, ph = 0;; sl += 128 - nblk, ph = 1) {
        mbar_wait(jbar, ph);
        TS(13);
        float acc[4][4];
#pragma unroll
        for (int i = 0; i < 16; i++) acc[i >> 2][i & 3] = 0.f;
        const uint32_t wa = sbase + J0W + ((warp - 4) * 144 + (lane & 15)) * 64;
        const uint32_t sw = (lane >> 1) & 3, xa = sbase + M_XA + (g & 3) * 1152 + (warp - 4) * 288 + t * 4;
#pragma unroll 3
        for (int s = 0; s < 9; s++) {
            const uint32_t a[4] = {lds32(xa + s * 32), 0u, lds32(xa + s * 32 + 16), 0u};
            uint32_t w0[4], w1[4];
            ldsm4t(w0, wa + s * 1024 + (((lane >> 4) ^ sw) * 16));
            ldsm4t(w1, wa + s * 1024 + (((2 + (lane >> 4)) ^ sw) * 16));
            mma16816(acc[0], a, w0[0], w0[1]);
            mma16816(acc[1], a, w0[2], w0[3]);
            mma16816(acc[2], a, w1[0], w1[1]);
            mma16816(acc[3], a, w1[2], w1[3]);
        }
        float2* j0 = reinterpret_cast<float2*>(smem + M_J0);
        if (g < 4) {
#pragma unroll
            for (int i = 0; i < 4; i++) j0[(warp - 4) * 64 + g * 16 + i * 4 + t] = make_float2(acc[i][0], acc[i][1]);
        }
        asm volatile("bar.sync 1, 128;" ::: "memory");
        const bool again = sl == blk && blk + 128 - nblk >= nblk;
        if (again && tid == 224) {
            mbar_expect_tx(jbar, 36864);
            tma3d(sbase + J0W, &p.tm_j0, (blk + 128 - nblk) * 32, 0, 0, jbar, pol);
        }
        if (warp < 6) {
            const float2 v0 = j0[j], v1 = j0[64 + j], v2 = j0[128 + j], v3 = j0[192 + j];
            st_relaxed64(&g_qll[(j >> 4) * 2048 + sl * 16 + (j & 15)],
                         (unsigned long long)pack_bf16((v0.x + v1.x) + (v2.x + v3.x), (v0.y + v1.y) + (v2.y + v3.y)) |
                             ((unsigned long long)(epoch + 1) << 32));
            __syncwarp();
            if (lane == 0) asm volatile("red.relaxed.cta.shared::cta.add.u32 [%0], 1;" ::"r"(sbase + M_HELP + 24) : "memory");
        } else if (warp == 7) {
            if (blk < C_LINES) g_ctl[(epoch & 1) ^ 1][blk][lane] = 0;
        }
        TS(1);
        if (!again) break;
        asm volatile("bar.sync 1, 128;" ::: "memory");
        }
    }
    if (isB) {
        b_chain<CLU>(p, smem, sbase, bi, epoch, pol);
        return;
    }
    if (warp < NW + XW) {
        a_worker<CLU>(p, u0, warp >= NW + ((nb & 3) < (CLU ? X3C : X3) ? 1 : 0), hold, nstatic, wslot, wbar, warp < NEARLY && !hold ? fbar : wbar,
                      sbase + M_HELP, epoch, pol);
        if (CLU && nb < NFIN) {
            if (warp == 3) out_issue_sum(p, sbase, nb >> 3, nb & 7, pol);
            else if (warp == 0) out_late(sbase, nb & 7);
        }
        return;
    } else if (warp == 7) {
#pragma unroll 1
        for (int i = nb; i < 4 * NH; i += nnb) g_oacc[i * 32 + lane] = make_float4(0.f, 0.f, 0.f, 0.f);
        if (nb < NREP * NH) g_vdone[nb][lane] = 0;
        __syncwarp();
        k_helper(sbase + M_HELP, epoch);
        if (nb == 0 && lane == 0) g_epoch = epoch + 1;
        __syncwarp();
        if (CLU && nb < NFIN) out_early(sbase, nb & 7, epoch + 1);
    } else if (CLU) {
    } else if (warp == 6 && nb < NFIN) {
        finisher(p, sbase, nb);
        TS(4);
    } else if (warp >= 6 - NPOLL && nb < NFIN) {
        v_poller(sbase, nb, warp - (6 - NPOLL));
    }
    if (CLU && nb < NFIN) out_project(sbase, nb & 7, warp - 4);
}

}

typedef CUresult (*EncodeFn)(CUtensorMap*, CUtensorMapDataType, cuuint32_t, void*, const cuuint64_t*, const cuuint64_t*,
                             const cuuint32_t*, const cuuint32_t*, CUtensorMapInterleave, CUtensorMapSwizzle,
                             CUtensorMapL2promotion, CUtensorMapFloatOOBfill);

extern "C" void kernel_launch(void* const* d_in, const int* in_sizes, int n_in, void* d_out, int out_size) {
    (void)in_sizes; (void)n_in; (void)out_size;
    static int nsm = 0, ncl = 0;
    static EncodeFn encode = nullptr;
    static const char* epoch_ptr = nullptr;
    cudaLaunchConfig_t cfg = {};
    cudaLaunchAttribute at[1];
    at[0].id = cudaLaunchAttributeClusterDimension;
    at[0].val.clusterDim.x = 8; at[0].val.clusterDim.y = 1; at[0].val.clusterDim.z = 1;
    cfg.blockDim = dim3(256); cfg.dynamicSmemBytes = SMEM_BYTES; cfg.stream = cudaStreamPerThread; cfg.attrs = at; cfg.numAttrs = 1;
    if (nsm == 0) {
        int dev = 0;
        cudaGetDevice(&dev);
        cudaDeviceGetAttribute(&nsm, cudaDevAttrMultiProcessorCount, dev);
        cudaFuncSetAttribute(fused_decode_kernel<false>, cudaFuncAttributeMaxDynamicSharedMemorySize, SMEM_BYTES);
        cudaFuncSetAttribute(fused_decode_kernel<true>, cudaFuncAttributeMaxDynamicSharedMemorySize, SMEM_BYTES);
        cfg.gridDim = dim3(128);
        if (cudaOccupancyMaxActiveClusters(&ncl, fused_decode_kernel<true>, &cfg) != cudaSuccess) { ncl = 0; (void)cudaGetLastError(); }
        if (ncl > MINCL) ncl = MINCL;
        cudaGetSymbolAddress((void**)&epoch_ptr, g_epoch);
        void* fn = nullptr;
        cudaDriverEntryPointQueryResult qr;
        cudaGetDriverEntryPoint("cuTensorMapEncodeTiled", &fn, cudaEnableDefault, &qr);
        encode = (EncodeFn)fn;
    }
    Params p;
    auto panels = [&](CUtensorMap* tm, void* ptr, int rows, int cols, int box_rows, int box_panels) {
        const cuuint64_t gd[3] = {64, (cuuint64_t)rows, (cuuint64_t)(cols / 64)}, gs[2] = {(cuuint64_t)cols * 2, 128};
        const cuuint32_t box[3] = {64, (cuuint32_t)box_rows, (cuuint32_t)box_panels}, es[3] = {1, 1, 1};
        encode(tm, CU_TENSOR_MAP_DATA_TYPE_BFLOAT16, 3, ptr, gd, gs, box, es, CU_TENSOR_MAP_INTERLEAVE_NONE,
               CU_TENSOR_MAP_SWIZZLE_128B, CU_TENSOR_MAP_L2_PROMOTION_L2_256B, CU_TENSOR_MAP_FLOAT_OOB_FILL_NONE);
    };
    panels(&p.tm_wq, d_in[7], DM, 4096, 128, 2);
    panels(&p.tm_wuk, d_in[8], 512, 4096, 128, 2);
    panels(&p.tm_wuv, d_in[9], 512, 4096, 128, 2);
    panels(&p.tm_wo, d_in[10], 4096, DM, 32, 9);
    panels(&p.tm_wf, d_in[10], 4096, DM, 128, 1);
    panels(&p.tm_ckv, d_in[6], 4 * SK, 512, 32, 8);
    {
        const cuuint64_t gd[3] = {4096, 192, 3}, gs[2] = {8192, 192 * 8192};
        const cuuint32_t box[3] = {32, 192, 3}, es[3] = {1, 1, 1};
        encode(&p.tm_j0, CU_TENSOR_MAP_DATA_TYPE_BFLOAT16, 3, d_in[3], gd, gs, box, es, CU_TENSOR_MAP_INTERLEAVE_NONE,
               CU_TENSOR_MAP_SWIZZLE_64B, CU_TENSOR_MAP_L2_PROMOTION_L2_128B, CU_TENSOR_MAP_FLOAT_OOB_FILL_NONE);
    }
    {
        const cuuint64_t gd[3] = {DM, 512, 8}, gs[2] = {8 * DM * 2, DM * 2};
        const cuuint32_t box[3] = {64, 16, 8}, es[3] = {1, 1, 1};
        encode(&p.tm_wl, CU_TENSOR_MAP_DATA_TYPE_BFLOAT16, 3, d_in[4], gd, gs, box, es, CU_TENSOR_MAP_INTERLEAVE_NONE,
               CU_TENSOR_MAP_SWIZZLE_128B, CU_TENSOR_MAP_L2_PROMOTION_L2_256B, CU_TENSOR_MAP_FLOAT_OOB_FILL_NONE);
    }
    p.kc = (const __nv_bfloat16*)d_in[1];
    p.vc = (const __nv_bfloat16*)d_in[2];
    p.wo = (const __nv_bfloat16*)d_in[4];
    p.xb = (const __nv_bfloat16*)d_in[5];
    p.out = (__nv_bfloat16*)d_out;
    const First f = {{(const char*)d_in[3], (const char*)d_in[1], (const char*)d_in[0], epoch_ptr}};
    if (ncl >= MINCL) {
        cfg.gridDim = dim3(8 * ncl);
        cudaLaunchKernelEx(&cfg, fused_decode_kernel<true>, f, p);
    } else {
        fused_decode_kernel<false><<<nsm, 256, SMEM_BYTES, cudaStreamPerThread>>>(f, p);
    }
}
```

```cpp
#include <cuda_runtime.h>
#include <cuda.h>
#include <cuda_bf16.h>
#include <stdint.h>

namespace {

constexpr int NH = 32, SK = 4096, DM = 576;
constexpr int KEYS = 128;
constexpr int UPP = SK / KEYS;
constexpr int NUK = 4 * NH * UPP;
constexpr int TILE_BYTES = KEYS * 256;
#define NWORK 2
constexpr int NW = NWORK;
constexpr int NBCTA = 32;
constexpr int MINCL = 15;
constexpr int NFIN = 72;
constexpr int SLOT = 32768;
constexpr int NSLOT = 6;
constexpr int BRING = 5;
constexpr int J0W = 5 * SLOT;
constexpr int MISC = NSLOT * SLOT + 4096;
constexpr int XP = 1168, CP = 1040, QP = 272;
constexpr int M_XA = MISC;
constexpr int M_XB = M_XA + 4 * XP;
constexpr int M_CH = M_XB + 4 * XP;
constexpr int M_CL = M_CH + 4 * CP;
constexpr int M_QB = M_CL + 4 * CP;
constexpr int M_QA = M_CH;
constexpr int M_J0 = M_QB + 4 * QP;
constexpr int M_P = M_J0 + 2048;
constexpr int M_ALPHA = M_P + 2560;
constexpr int M_OMEGA = M_ALPHA + 128;
constexpr int M_BAR = M_OMEGA + 128;
constexpr int M_HELP = M_BAR + 128;
constexpr int F_W = 3 * SLOT;
constexpr int F_X = NSLOT * SLOT, FXP = 1088;
constexpr int F_RECV = F_X + 8 * FXP;
constexpr int F_BAR = M_P;
constexpr int SMEM_BYTES = M_HELP + 128 + 1024;
static_assert(F_RECV + 2048 <= M_J0, "output phase layout");
static_assert(SMEM_BYTES <= 232448 && M_BAR % 8 == 0 && M_QA % 16 == 0 && M_P % 16 == 0, "smem layout");
#define XW 2
#define X3 1
#define X3C 2
#define NEARLY 2
#define BD 4
#define FPF 3
#define FSLEEP 800
#define VMINC 2
#define FJ 260
#define FP 384
#define NPOLL 2
#define PGAP 200
static_assert(NW + XW == 4 && 4 % NEARLY == 0 && BD <= BRING, "slots 4 and 5 hold the finisher weights");
constexpr int KMIN = 2, KMAX = 4, VMAX = 4;
constexpr float SCALE = 0.08838834764831845f;
constexpr float LOG2E = 1.4426950408889634f;
constexpr unsigned SPIN_LIMIT = 1u << 24;

#define NREP 2
constexpr int C_QUEUE = 0, C_KDONE = 1, C_BBAR = 3, C_LINES = 5;

struct First { const char* ptr[4]; };
struct Params {
    const __nv_bfloat16 *kc, *vc, *wo, *xb;
    __nv_bfloat16* out;
    CUtensorMap tm_j0;
    CUtensorMap tm_wq, tm_wuk, tm_ckv, tm_wuv, tm_wo;
    CUtensorMap tm_wl;
    CUtensorMap tm_wf;
};

__device__ unsigned g_epoch;
__device__ unsigned g_ctl[2][C_LINES][32];
__device__ uint2 g_qll[4 * 2048];
__device__ uint2 g_scores[128 * SK / 4];
__device__ float2 g_stats[128 * UPP];
__device__ float4 g_oacc[128 * 32];
__device__ unsigned g_vdone[NREP * NH][32];
__device__ uint4 g_qabs[4 * 8 * 4 * 4 * 32];
__device__ float2 g_bpart[NBCTA * NH * 256];
__device__ float2 g_bml[NBCTA * NH];
__device__ uint4 g_ctx[NH * 128];
__device__ uint4 g_outb[NBCTA * NH * 36];

#define TS(i)
#define TSV(i, v)
#define LAND(i)
#define CLK(x)
#define ACC(a, x, y)

__device__ __forceinline__ uint32_t smem_u32(const void* p) { return (uint32_t)__cvta_generic_to_shared(p); }
__device__ __forceinline__ void mbar_init(uint32_t bar, uint32_t cnt) {
    asm volatile("mbarrier.init.shared::cta.b64 [%0], %1;" ::"r"(bar), "r"(cnt) : "memory");
}
__device__ __forceinline__ void mbar_expect_tx(uint32_t bar, uint32_t bytes) {
    asm volatile("mbarrier.arrive.expect_tx.shared::cta.b64 _, [%0], %1;" ::"r"(bar), "r"(bytes) : "memory");
}
__device__ __forceinline__ bool mbar_try(uint32_t bar, uint32_t parity) {
    uint32_t ok;
    asm volatile("{\n.reg .pred p;\nmbarrier.try_wait.parity.shared::cta.b64 p, [%1], %2;\nselp.u32 %0, 1, 0, p;\n}\n"
                 : "=r"(ok) : "r"(bar), "r"(parity) : "memory");
    return ok;
}
__device__ __forceinline__ void mbar_wait(uint32_t bar, uint32_t parity) {
    unsigned n = 0;
    while (!mbar_try(bar, parity)) { if (++n > SPIN_LIMIT) __trap(); }
}
__device__ __forceinline__ void bulk_load(uint32_t dst, const void* src, uint32_t bytes, uint32_t bar, uint64_t pol) {
    asm volatile("cp.async.bulk.shared::cluster.global.mbarrier::complete_tx::bytes.L2::cache_hint [%0], [%1], %2, [%3], %4;"
                 ::"r"(dst), "l"(src), "r"(bytes), "r"(bar), "l"(pol) : "memory");
}
__device__ __forceinline__ void tma3d(uint32_t dst, const CUtensorMap* tm, int c0, int c1, int c2, uint32_t bar, uint64_t pol) {
    asm volatile("cp.async.bulk.tensor.3d.shared::cluster.global.mbarrier::complete_tx::bytes.L2::cache_hint [%0], [%1, {%3,%4,%5}], [%2], %6;"
                 ::"r"(dst), "l"(tm), "r"(bar), "r"(c0), "r"(c1), "r"(c2), "l"(pol) : "memory");
}
__device__ __forceinline__ void l2_prefetch(const void* src, uint32_t bytes) {
    asm volatile("cp.async.bulk.prefetch.L2.global [%0], %1;" ::"l"(src), "r"(bytes) : "memory");
}
__device__ __forceinline__ void ldsm4(uint32_t (&r)[4], uint32_t addr) {
    asm volatile("ldmatrix.sync.aligned.m8n8.x4.shared.b16 {%0,%1,%2,%3}, [%4];"
                 : "=r"(r[0]), "=r"(r[1]), "=r"(r[2]), "=r"(r[3]) : "r"(addr));
}
__device__ __forceinline__ void ldsm4t(uint32_t (&r)[4], uint32_t addr) {
    asm volatile("ldmatrix.sync.aligned.m8n8.x4.trans.shared.b16 {%0,%1,%2,%3}, [%4];"
                 : "=r"(r[0]), "=r"(r[1]), "=r"(r[2]), "=r"(r[3]) : "r"(addr));
}
__device__ __forceinline__ void mma16816(float (&d)[4], const uint32_t (&a)[4], uint32_t b0, uint32_t b1) {
    asm("mma.sync.aligned.m16n8k16.row.col.f32.bf16.bf16.f32 {%0,%1,%2,%3}, {%4,%5,%6,%7}, {%8,%9}, {%0,%1,%2,%3};"
        : "+f"(d[0]), "+f"(d[1]), "+f"(d[2]), "+f"(d[3])
        : "r"(a[0]), "r"(a[1]), "r"(a[2]), "r"(a[3]), "r"(b0), "r"(b1));
}
__device__ __forceinline__ void wgmma_tile(float (&d)[4], uint32_t da, uint32_t db, int accumulate) {
    asm volatile("{\n.reg .pred p;\n.reg .b32 x, y;\n.reg .b64 a, b;\nsetp.ne.u32 p, %6, 0;\nwgmma.fence.sync.aligned;\n"
                 "add.u32 x, %4, 0;\nadd.u32 y, %5, 0;\nmov.b64 a, {x, 0x40000040};\nmov.b64 b, {y, 1};\n"
                 "wgmma.mma_async.sync.aligned.m64n8k16.f32.bf16.bf16 {%0,%1,%2,%3}, a, b, p, 1, 1, 1, 0;\n"
                 "add.u32 x, %4, 128;\nadd.u32 y, %5, 8;\nmov.b64 a, {x, 0x40000040};\nmov.b64 b, {y, 1};\n"
                 "wgmma.mma_async.sync.aligned.m64n8k16.f32.bf16.bf16 {%0,%1,%2,%3}, a, b, 1, 1, 1, 1, 0;\n"
                 "add.u32 x, %4, 256;\nadd.u32 y, %5, 16;\nmov.b64 a, {x, 0x40000040};\nmov.b64 b, {y, 1};\n"
                 "wgmma.mma_async.sync.aligned.m64n8k16.f32.bf16.bf16 {%0,%1,%2,%3}, a, b, 1, 1, 1, 1, 0;\n"
                 "add.u32 x, %4, 384;\nadd.u32 y, %5, 24;\nmov.b64 a, {x, 0x40000040};\nmov.b64 b, {y, 1};\n"
                 "wgmma.mma_async.sync.aligned.m64n8k16.f32.bf16.bf16 {%0,%1,%2,%3}, a, b, 1, 1, 1, 1, 0;\n"
                 "add.u32 x, %4, 512;\nadd.u32 y, %5, 32;\nmov.b64 a, {x, 0x40000040};\nmov.b64 b, {y, 1};\n"
                 "wgmma.mma_async.sync.aligned.m64n8k16.f32.bf16.bf16 {%0,%1,%2,%3}, a, b, 1, 1, 1, 1, 0;\n"
                 "add.u32 x, %4, 640;\nadd.u32 y, %5, 40;\nmov.b64 a, {x, 0x40000040};\nmov.b64 b, {y, 1};\n"
                 "wgmma.mma_async.sync.aligned.m64n8k16.f32.bf16.bf16 {%0,%1,%2,%3}, a, b, 1, 1, 1, 1, 0;\n"
                 "add.u32 x, %4, 768;\nadd.u32 y, %5, 48;\nmov.b64 a, {x, 0x40000040};\nmov.b64 b, {y, 1};\n"
                 "wgmma.mma_async.sync.aligned.m64n8k16.f32.bf16.bf16 {%0,%1,%2,%3}, a, b, 1, 1, 1, 1, 0;\n"
                 "add.u32 x, %4, 896;\nadd.u32 y, %5, 56;\nmov.b64 a, {x, 0x40000040};\nmov.b64 b, {y, 1};\n"
                 "wgmma.mma_async.sync.aligned.m64n8k16.f32.bf16.bf16 {%0,%1,%2,%3}, a, b, 1, 1, 1, 1, 0;\n"
                 "wgmma.commit_group.sync.aligned;\n}"
                 : "+f"(d[0]), "+f"(d[1]), "+f"(d[2]), "+f"(d[3]) : "r"(da), "r"(db), "r"(accumulate) : "memory");
}
__device__ __forceinline__ uint32_t lds32(uint32_t a) {
    uint32_t v;
    asm volatile("ld.shared.u32 %0, [%1];" : "=r"(v) : "r"(a));
    return v;
}
__device__ __forceinline__ unsigned ld_acquire(const unsigned* p) {
    unsigned v;
    asm volatile("ld.acquire.gpu.global.u32 %0, [%1];" : "=r"(v) : "l"(p) : "memory");
    return v;
}
__device__ __forceinline__ uint2 ld_relaxed8(const void* p) {
    uint2 v;
    asm volatile("ld.relaxed.gpu.global.v2.u32 {%0,%1}, [%2];" : "=r"(v.x), "=r"(v.y) : "l"(p) : "memory");
    return v;
}
__device__ __forceinline__ unsigned ld_relaxed4(const void* p) {
    unsigned v;
    asm volatile("ld.relaxed.gpu.global.u32 %0, [%1];" : "=r"(v) : "l"(p) : "memory");
    return v;
}
__device__ __forceinline__ unsigned atom_inc(unsigned* p) {
    unsigned v;
    asm volatile("atom.relaxed.gpu.global.inc.u32 %0, [%1], 0x7fffffff;" : "=r"(v) : "l"(p) : "memory");
    return v;
}
__device__ __forceinline__ unsigned long long ld_relaxed64(const void* p) {
    unsigned long long v;
    asm volatile("ld.relaxed.gpu.global.u64 %0, [%1];" : "=l"(v) : "l"(p) : "memory");
    return v;
}
__device__ __forceinline__ void st_relaxed64(void* p, unsigned long long v) {
    asm volatile("st.relaxed.gpu.global.u64 [%0], %1;" ::"l"(p), "l"(v) : "memory");
}
__device__ __forceinline__ float4 ld_relaxed16(const void* p) {
    float4 v;
    asm volatile("ld.relaxed.gpu.global.v4.f32 {%0,%1,%2,%3}, [%4];" : "=f"(v.x), "=f"(v.y), "=f"(v.z), "=f"(v.w) : "l"(p) : "memory");
    return v;
}
__device__ __forceinline__ uint32_t mapa(uint32_t a, uint32_t rank) {
    uint32_t r;
    asm("mapa.shared::cluster.u32 %0, %1, %2;" : "=r"(r) : "r"(a), "r"(rank));
    return r;
}
__device__ __forceinline__ void mbar_spin(uint32_t bar) {
    asm volatile("{\n.reg .pred p, q;\n.reg .u32 n;\nmov.u32 n, 0;\n"
                 "SPIN:\nmbarrier.test_wait.parity.shared::cta.b64 p, [%0], 0;\nadd.u32 n, n, 1;\nsetp.gt.u32 q, n, 0x4000000;\n@q trap;\n"
                 "@!p bra.uni SPIN;\n}" ::"r"(bar) : "memory");
}
__device__ __forceinline__ void mbar_spin_cluster(uint32_t bar) {
    asm volatile("{\n.reg .pred p, q;\n.reg .u32 n;\nmov.u32 n, 0;\n"
                 "SPIN:\nmbarrier.test_wait.parity.relaxed.cluster.shared::cta.b64 p, [%0], 0;\nadd.u32 n, n, 1;\nsetp.gt.u32 q, n, 0x4000000;\n@q trap;\n"
                 "@!p bra.uni SPIN;\nfence.acquire.sync_restrict::shared::cluster.cluster;\n}" ::"r"(bar) : "memory");
}
__device__ __forceinline__ uint32_t now_ns() {
    unsigned long long t;
    asm volatile("mov.u64 %0, %globaltimer;" : "=l"(t));
    return (uint32_t)t;
}
__device__ __forceinline__ void fence_gpu() { asm volatile("fence.acq_rel.gpu;" ::: "memory"); }
__device__ __forceinline__ void red_add_u32(unsigned* p, unsigned v) {
    asm volatile("red.relaxed.gpu.global.add.u32 [%0], %1;" ::"l"(p), "r"(v) : "memory");
}
__device__ __forceinline__ void st_tagged2(void* p, float a, float b, unsigned tag) {
    const unsigned long long hi = (unsigned long long)tag << 32;
    asm volatile("st.relaxed.gpu.global.v2.b64 [%0], {%1,%2};" ::"l"(p), "l"(hi | __float_as_uint(a)), "l"(hi | __float_as_uint(b)) : "memory");
}
__device__ __forceinline__ ulonglong2 ld_tagged2(const void* p) {
    ulonglong2 v;
    asm volatile("ld.relaxed.gpu.global.v2.b64 {%0,%1}, [%2];" : "=l"(v.x), "=l"(v.y) : "l"(p) : "memory");
    return v;
}
__device__ __forceinline__ float4 atom_add_f4(void* p, float a, float b, float c, float d) {
    float4 r;
    asm volatile("atom.relaxed.gpu.global.add.v4.f32 {%0,%1,%2,%3}, [%4], {%5,%6,%7,%8};"
                 : "=f"(r.x), "=f"(r.y), "=f"(r.z), "=f"(r.w) : "l"(p), "f"(a), "f"(b), "f"(c), "f"(d) : "memory");
    return r;
}
__device__ __forceinline__ void red_release_cta_shared(uint32_t a, unsigned v) {
    asm volatile("red.release.cta.shared::cta.add.u32 [%0], %1;" ::"r"(a), "r"(v) : "memory");
}
__device__ __forceinline__ unsigned ld_acquire_cta_shared(uint32_t a) {
    unsigned v;
    asm volatile("ld.acquire.cta.shared::cta.u32 %0, [%1];" : "=r"(v) : "r"(a) : "memory");
    return v;
}
__device__ __forceinline__ void st_release_cta_shared(uint32_t a, unsigned v) {
    asm volatile("st.release.cta.shared::cta.u32 [%0], %1;" ::"r"(a), "r"(v) : "memory");
}
__device__ __forceinline__ void wait_count(const unsigned* p, unsigned target) {
    unsigned n = 0;
    while (ld_acquire(p) < target) { if (++n > SPIN_LIMIT) __trap(); }
}
__device__ __forceinline__ uint32_t pack_bf16(float lo, float hi) {
    uint32_t r;
    asm("cvt.rn.bf16x2.f32 %0, %1, %2;" : "=r"(r) : "f"(hi), "f"(lo));
    return r;
}
__device__ __forceinline__ float bf_lo(uint32_t v) { return __uint_as_float(v << 16); }
__device__ __forceinline__ float bf_hi(uint32_t v) { return __uint_as_float(v & 0xffff0000u); }
__device__ __forceinline__ float ex2(float x) { float y; asm("ex2.approx.ftz.f32 %0, %1;" : "=f"(y) : "f"(x)); return y; }
__device__ __forceinline__ float expsub(float a, float b) { return ex2((a - b) * LOG2E); }
__device__ __forceinline__ float warp_max(float v) {
#pragma unroll
    for (int m = 16; m; m >>= 1) v = fmaxf(v, __shfl_xor_sync(~0u, v, m));
    return v;
}
__device__ __forceinline__ float warp_sum(float v) {
#pragma unroll
    for (int m = 16; m; m >>= 1) v += __shfl_xor_sync(~0u, v, m);
    return v;
}
template <bool CLU>
__device__ __forceinline__ unsigned unit_block(int u) {
    const unsigned x = ((unsigned)u & (NUK - 1)) / UPP;
    const int lg = u < NUK ? min(KMAX, max(KMIN, 29 - __clz(x | 1))) : min(VMAX, max(CLU ? VMINC : 0, 29 - __clz((127 - x) | 1)));
    const unsigned r = x & ((4u << lg) - 1);
    return ((x - r + (r & ((1u << lg) - 1)) * 4 + (r >> lg)) * UPP) | ((unsigned)u & (UPP - 1));
}
__device__ __forceinline__ const char* block_src(const void* base, unsigned blk) {
    const unsigned po = blk / UPP;
    return reinterpret_cast<const char*>(base) + (size_t)(((po & 3) * NH + (po >> 2)) * UPP + blk % UPP) * TILE_BYTES;
}

template <bool CLU>
__device__ __forceinline__ void a_worker(const Params& p, int un, bool once, bool hold, int nstatic, uint32_t slot, uint32_t bar, uint32_t wb,
                                         uint32_t help, unsigned epoch, uint64_t pol) {
    constexpr int NU = 2 * NUK;
    const int lane = threadIdx.x & 31, g = lane >> 2, t = lane & 3;
    const int li = lane & 7;
    uint32_t kaddr[4], vaddr[8];
    {
        const int e = (lane >> 3) & 1, kk = lane >> 4;
#pragma unroll
        for (int s = 0; s < 4; s++) kaddr[s] = slot + (16 * li + e) * 256 + ((2 * s + kk + li) & 7) * 16;
        const int vrow = 4 * (li >> 1) + (li & 1) + 2 * kk;
#pragma unroll
        for (int c = 0; c < 8; c++) vaddr[c] = slot + vrow * 256 + e * 128 + ((c + li) & 7) * 16;
#pragma unroll
        for (int c = 0; c < 8; c++) asm volatile("" : "+r"(vaddr[c]));
    }
    const uint32_t vmask = (g >> 1) != t ? 0u : ((g & 1) ? 0xffff0000u : 0xffffu);
    int kseen = -1;
    unsigned long long H0 = 0, H1 = 0;
    auto header = [&](int v, unsigned vb) {
        if (v >= NU) return;
        const void *a0, *a1;
        if (v < NUK) {
            const unsigned po = vb / UPP;
            a0 = g_qll + (po & 3) * 2048 + (po >> 2) * 64 + lane;
            a1 = reinterpret_cast<const uint2*>(a0) + 32;
        } else {
            const int half = vb / (NUK / 2);
            if (half > kseen) {
                unsigned n = 0;
                while (ld_acquire_cta_shared(help + 12 + 4 * half) == 0) { if (++n > (SPIN_LIMIT << 4)) __trap(); }
                kseen = half;
            }
            a0 = &g_scores[vb * (KEYS / 4) + lane];
            a1 = &g_stats[(vb / UPP) * UPP + lane];
        }
        H0 = ld_relaxed64(a0);
        H1 = ld_relaxed64(a1);
    };
    epoch = __shfl_sync(~0u, epoch, 0);
    if (hold) { unsigned n = 0; while (ld_acquire_cta_shared(help + 24) < 2) { if (++n > (SPIN_LIMIT << 4)) __trap(); } }
    unsigned (*ctl)[32] = g_ctl[epoch & 1];
    const unsigned tag = epoch + 1;
    unsigned nxt = once ? NU : 0;
    int u = -1;
    unsigned bu = 0, bn = unit_block<CLU>(un);
    bool have = false;
    uint32_t phase = 0;
    unsigned kpend = 0;
    const unsigned zero = gridDim.x >> 24;
    uint32_t Q[16];
    float4 oret = make_float4(0.f, 0.f, 0.f, 0.f);
    while (true) {
        const char* nsrc = block_src(un < NUK ? p.kc : p.vc, bn);
        float4* odst = &g_oacc[(bu / UPP) * 32 + lane];
        unsigned* vdst = &g_vdone[(lane & (NREP - 1)) * NH + bu / (4 * UPP)][0];
        float d[8][4];
        CLK(c1);
        asm volatile("" : "+l"(odst));
        if (u >= NUK) {
#pragma unroll
            for (int j = 0; j < 8; j++) { d[j][0] = d[j][1] = d[j][2] = d[j][3] = 0.f; }
            mbar_wait(wb, phase);
            LAND(NUK + bu);
            uint32_t a[2][8][4];
#pragma unroll
            for (int c = 0; c < 8; c++) ldsm4t(a[0][c], vaddr[c]);
#pragma unroll
            for (int j = 0; j < 8; j++) {
                if (j < 7) {
#pragma unroll
                    for (int c = 0; c < 8; c++) ldsm4t(a[(j + 1) & 1][c], vaddr[c] + (j + 1) * 4096);
                }
#pragma unroll
                for (int c = 0; c < 8; c++) mma16816(d[c], a[j & 1][c], Q[2 * j], Q[2 * j + 1]);
            }
            float o[4];
#pragma unroll
            for (int r = 0; r < 2; r++) {
                o[2 * r] = d[0][2 * r] + d[7][2 * r + 1];
                o[2 * r + 1] = d[0][2 * r + 1] + d[1][2 * r];
#pragma unroll
                for (int k = 1; k < 4; k++) {
                    const int src = (lane & 28) | ((t - k) & 3);
                    o[2 * r] += __shfl_sync(~0u, d[2 * k][2 * r] + d[2 * k - 1][2 * r + 1], src);
                    o[2 * r + 1] += __shfl_sync(~0u, d[2 * k][2 * r + 1] + d[2 * k + 1][2 * r], src);
                }
            }
            oret = atom_add_f4(odst, o[0], o[1], o[2], o[3]);
        } else if (u >= 0) {
#pragma unroll
            for (int j = 0; j < 8; j++) { d[j][0] = d[j][1] = d[j][2] = d[j][3] = 0.f; }
            mbar_wait(wb, phase);
            LAND(bu);
            uint32_t a[2][8][4];
#pragma unroll
            for (int j = 0; j < 8; j++) ldsm4(a[0][j], kaddr[0] + (4 * (j & 3) + 2 * (j >> 2)) * 256);
#pragma unroll
            for (int s = 0; s < 8; s++) {
                if (s < 7) {
#pragma unroll
                    for (int j = 0; j < 8; j++)
                        ldsm4(a[(s + 1) & 1][j], kaddr[(s + 1) & 3] + (4 * (j & 3) + 2 * (j >> 2)) * 256 + ((s + 1) >> 2) * 128);
                }
#pragma unroll
                for (int j = 0; j < 8; j++)
                    mma16816(d[j], a[s & 1][j], Q[(s & 4) * 2 + ((2 * s - 2 * j) & 7)], Q[(s & 4) * 2 + ((2 * s + 1 - 2 * j) & 7)]);
            }
        }
        const bool pre = wb != bar;
        if (u >= 0) { phase = pre ? 0 : phase ^ 1; wb = bar; }
        CLK(c2b);
        if (un < NU && lane == 0) {
            if (!once) nxt = atom_inc(&ctl[C_QUEUE][0]);
            if (u >= 0 || !pre) {
                mbar_expect_tx(bar, TILE_BYTES);
                bulk_load(slot, nsrc, TILE_BYTES, bar, pol);
            }
        }
        const uint32_t tiss = now_ns();
        CLK(c3);
        if ((unsigned)u < (unsigned)NUK) {
            const int j0 = (t - (g >> 1)) & 3;
            float v[4];
#pragma unroll
            for (int q = 0; q < 4; q++) {
                const int jq = (q >> 1) * 4, e = (q & 1) * 2;
                const float x0 = (g & 1) ? d[jq + 0][e + 1] : d[jq + 0][e];
                const float x1 = (g & 1) ? d[jq + 1][e + 1] : d[jq + 1][e];
                const float x2 = (g & 1) ? d[jq + 2][e + 1] : d[jq + 2][e];
                const float x3 = (g & 1) ? d[jq + 3][e + 1] : d[jq + 3][e];
                const float y0 = (j0 & 1) ? x1 : x0, y1 = (j0 & 1) ? x3 : x2;
                v[q] = (j0 & 2) ? y1 : y0;
            }
            const uint32_t r0 = pack_bf16(v[0], v[1]), r1 = pack_bf16(v[2], v[3]);
            const uint32_t s0 = pack_bf16(bf_lo(r0) * SCALE, bf_hi(r0) * SCALE);
            const uint32_t s1 = pack_bf16(bf_lo(r1) * SCALE, bf_hi(r1) * SCALE);
            g_scores[bu * (KEYS / 4) + 4 * g + j0] = make_uint2(s0, s1);
            const float f0 = bf_lo(s0), f1 = bf_hi(s0), f2 = bf_lo(s1), f3 = bf_hi(s1);
            const float m = warp_max(fmaxf(fmaxf(f0, f1), fmaxf(f2, f3)));
            const float l = warp_sum((expsub(f0, m) + expsub(f1, m)) + (expsub(f2, m) + expsub(f3, m)));
            if (lane == 0) g_stats[bu] = make_float2(m, l);
            kpend++;
            if (un / (NUK / 2) != u / (NUK / 2)) {
                __syncwarp();
                if (lane == 0) {
                    red_release_cta_shared(help + 4 * (u / (NUK / 2)), kpend);
                    if (un >= NUK) red_release_cta_shared(help + 8, 1u);
                }
                kpend = 0;
            }
        }
        CLK(c4);
        int unn = NU;
        if (un < NU) {
            unsigned n = 0;
            while (true) {
                if (!have) header(un, bn);
                if (un >= NUK || __all_sync(~0u, (uint32_t)(H0 >> 32) == tag && (uint32_t)(H1 >> 32) == tag)) break;
                if (++n > SPIN_LIMIT) __trap();
                have = false;
            }
            if (un >= NUK) {
                const uint32_t s0 = (uint32_t)H0, s1 = (uint32_t)(H0 >> 32);
                const float mu = __uint_as_float((uint32_t)H1);
                const float m = warp_max(mu);
                const float l = warp_sum(__uint_as_float((uint32_t)(H1 >> 32)) * expsub(mu, m));
                const float inv = 1.0f / l;
                const uint32_t w0 = pack_bf16(expsub(bf_lo(s0), m) * inv, expsub(bf_hi(s0), m) * inv);
                const uint32_t w1 = pack_bf16(expsub(bf_lo(s1), m) * inv, expsub(bf_hi(s1), m) * inv);
#pragma unroll
                for (int j = 0; j < 8; j++) {
                    Q[2 * j] = __shfl_sync(~0u, w0, 4 * j + t) & vmask;
                    Q[2 * j + 1] = __shfl_sync(~0u, w1, 4 * j + t) & vmask;
                }
            } else {
#pragma unroll
                for (int j = 0; j < 8; j++) {
                    const int src = (((j + g) & 7) << 2) + t;
                    Q[j] = __shfl_sync(~0u, (uint32_t)H0, src);
                    Q[8 + j] = __shfl_sync(~0u, (uint32_t)H1, src);
                }
            }
            unn = nstatic + (int)__shfl_sync(~0u, nxt, 0);
            if (CLU && !once && unn >= NU && lane == 0)
                asm volatile("st.relaxed.cta.shared::cta.u32 [%0], %1;" ::"r"(help + 28), "r"((tiss + (FJ - (unn - NU)) * 10) | 1u) : "memory");
        }
        if (u >= NUK && lane < (CLU ? 1 : NREP))
            red_add_u32(vdst,
                        1u + ((__float_as_uint(oret.x) | __float_as_uint(oret.y) | __float_as_uint(oret.z) | __float_as_uint(oret.w)) & zero));
        if (un >= NU) break;
        bu = bn;
        have = !(un < NUK && unn >= NUK && !(un >= NUK / 2 && unn < NUK + NUK / 2));
        bn = unit_block<CLU>(unn);
        if (have) header(unn, bn);
        u = un;
        un = unn;
    }
}

__device__ __forceinline__ void k_helper(uint32_t help, unsigned epoch) {
    if ((threadIdx.x & 31) != 0) return;
    unsigned (*ctl)[32] = g_ctl[epoch & 1];
    unsigned sent0 = 0, sent1 = 0, n = 0;
    int seen = 0;
    bool fin = false;
    while (!fin || seen < 2) {
        if (!fin) {
            fin = ld_acquire_cta_shared(help + 8) == NW + XW;
            const unsigned c0 = ld_acquire_cta_shared(help), c1 = ld_acquire_cta_shared(help + 4);
            if (c0 != sent0 || c1 != sent1) {
                fence_gpu();
                if (c0 != sent0) red_add_u32(&ctl[C_KDONE][0], c0 - sent0);
                if (c1 != sent1) red_add_u32(&ctl[C_KDONE + 1][0], c1 - sent1);
                sent0 = c0; sent1 = c1;
            }
        }
        if (seen < 2 && ld_acquire(&ctl[C_KDONE + seen][0]) >= NUK / 2) {
            st_release_cta_shared(help + 12 + 4 * seen, 1u);
            seen++;
        } else {
            __nanosleep(300);
        }
        if (++n > SPIN_LIMIT) __trap();
    }
}

__device__ __forceinline__ void v_poller(uint32_t sbase, int f, int w) {
    const int lane = threadIdx.x & 31;
    const unsigned (*cp)[32] = &g_vdone[((f * NPOLL + w) % NREP) * NH];
    unsigned n = 0;
    while (ld_acquire_cta_shared(sbase + M_HELP + 12) == 0) { __nanosleep(1000); if (++n > SPIN_LIMIT) __trap(); }
    int h = 0;
    bool fast = false;
    while (h < NH) {
        const unsigned r = __ballot_sync(~0u, ld_acquire(&cp[min(h + (lane & 3), NH - 1)][0]) >= 4 * UPP) & 15u;
        if (r & 1) {
            h = min(NH, h + __ffs(~r) - 1);
            __syncwarp();
            if (lane == 0) asm volatile("red.release.cta.shared::cta.max.u32 [%0], %1;" ::"r"(sbase + M_HELP + 20), "r"(h) : "memory");
        }
        if (h < NH - 4) {
            __nanosleep(h ? 300 : 1000);
        } else if (!fast) {
            fast = true;
            const long long t0 = clock64();
            while (clock64() - t0 < w * PGAP) {}
        }
        if (++n > SPIN_LIMIT) __trap();
    }
}
__device__ __forceinline__ void finisher(const Params& p, uint32_t sbase, int f) {
    const int lane = threadIdx.x & 31;
    {
        const char* wg = reinterpret_cast<const char*>(p.wo);
        const uint32_t dst = sbase + 4 * SLOT + (16 * (lane & 7) + (lane >> 3)) * 16;
#pragma unroll 1
        for (int h = -FPF - 4; h < NH; h++) {
            if (lane == 0 && (unsigned)(h + FPF) < (unsigned)NH) l2_prefetch(wg + (size_t)(h + FPF) * 147456 + f * 2048, 2048);
            if (h >= 0) {
#pragma unroll
                for (int r = 0; r < 4; r++)
                    asm volatile("cp.async.cg.shared.global [%0], [%1], 16;" ::"r"(dst + h * 2048 + ((r & 1) * 4 + (r >> 1) * 8) * 16),
                                 "l"(wg + (size_t)(h * 128 + r * 32 + lane) * (DM * 2) + f * 16) : "memory");
            }
            __nanosleep(FSLEEP);
        }
        asm volatile("cp.async.wait_all;" ::: "memory");
        __syncwarp();
    }
    TS(11);
    const float4* vec = g_oacc + ((lane >> 2) & 3) * 32 + (lane >> 4) * 16 + (lane & 3);
    float acc[2][2][4];
#pragma unroll
    for (int i = 0; i < 16; i++) acc[i >> 3][(i >> 2) & 1][i & 3] = 0.f;
    uint32_t* outp = reinterpret_cast<uint32_t*>(p.out + (lane >> 2) * (2 * DM) + f * 8 + (lane & 3) * 2);
    uint32_t wa = sbase + 4 * SLOT + lane * 16;
    auto project = [&](const float4 (&x)[4], const uint32_t (&w)[4][4]) {
#pragma unroll
        for (int s = 0; s < 4; s++) {
            const uint32_t a[4] = {pack_bf16(x[s].x, x[s].y), 0u, pack_bf16(x[s].z, x[s].w), 0u};
            mma16816(acc[0][s & 1], a, w[s >> 1][(s & 1) * 2], w[s >> 1][(s & 1) * 2 + 1]);
            mma16816(acc[1][s & 1], a, w[2 + (s >> 1)][(s & 1) * 2], w[2 + (s >> 1)][(s & 1) * 2 + 1]);
        }
    };
    int h = 0;
    unsigned n = 0;
    while (h < NH) {
        uint32_t w[4][4];
#pragma unroll
        for (int q = 0; q < 4; q++) ldsm4t(w[q], wa + q * 512);
        int ready;
        while ((ready = ld_acquire_cta_shared(sbase + M_HELP + 20)) <= h) {
            if (h < NH - 3) __nanosleep(100);
            if (++n > (SPIN_LIMIT << 4)) __trap();
        }
        float4 x[4], y[4];
#pragma unroll
        for (int s = 0; s < 4; s++) x[s] = ld_relaxed16(vec + s * 4);
        const bool two = ready > h + 1;
        if (two) {
#pragma unroll
            for (int s = 0; s < 4; s++) y[s] = ld_relaxed16(vec + 128 + s * 4);
        }
        project(x, w);
        if (two) {
#pragma unroll
            for (int q = 0; q < 4; q++) ldsm4t(w[q], wa + 2048 + q * 512);
            project(y, w);
        }
        const int nr = two ? 2 : 1;
        h += nr;
        vec += nr * 128;
        wa += nr * 2048;
        const float o0 = acc[0][0][0] + acc[0][1][0] + __shfl_down_sync(~0u, acc[1][0][0] + acc[1][1][0], 16);
        const float o1 = acc[0][0][1] + acc[0][1][1] + __shfl_down_sync(~0u, acc[1][0][1] + acc[1][1][1], 16);
        asm volatile("{\n.reg .pred p;\nsetp.ne.u32 p, %2, 0;\n@p st.global.u32 [%0], %1;\n}" ::"l"(outp), "r"(pack_bf16(o0, o1)),
                     "r"((uint32_t)(lane < 16 && h == NH)) : "memory");
    }
}

__device__ __forceinline__ void out_fetch(uint32_t sbase, int step, int h) {
    const int lane = threadIdx.x & 31, g = lane >> 2;
    float4 x[4];
#pragma unroll
    for (int b = 0; b < 4; b++) x[b] = ld_relaxed16(&g_oacc[(h * 4 + ((b + g) & 3)) * 32 + lane]);
#pragma unroll
    for (int b = 0; b < 4; b++) {
        const uint32_t a = sbase + F_X + step * FXP + g * 128 + ((b + g) & 3) * 16 + (lane & 3) * 4;
        asm volatile("st.shared.u32 [%0], %1;\nst.shared.u32 [%0 + 64], %2;" ::"r"(a), "r"(pack_bf16(x[b].x, x[b].y)), "r"(pack_bf16(x[b].z, x[b].w)) : "memory");
    }
    asm volatile("fence.proxy.async.shared::cta;" ::: "memory");
}
__device__ __forceinline__ void out_early(uint32_t sbase, int rank, unsigned tag) {
    const int lane = threadIdx.x & 31;
    if (lane < 10) {
        mbar_init(sbase + F_BAR + 16 + lane * 8, lane < 7 ? 1 : lane == 7 ? 2 : 4);
        if (lane < 8) mbar_expect_tx(sbase + F_BAR + 16 + lane * 8, 16384);
    }
    asm volatile("fence.mbarrier_init.release.cluster;" ::: "memory");
    unsigned n = 0;
#pragma unroll 1
    for (int i = 0; i < 3; i++) {
        while (ld_acquire(&g_vdone[8 * i + rank][0]) < 4 * UPP) { __nanosleep(500); if (++n > SPIN_LIMIT) __trap(); }
        out_fetch(sbase, 4 + i, 8 * i + rank);
#pragma unroll 1
        for (int j = 0; j < 16 && i == 0;) {
            const ulonglong2 v = ld_tagged2(&g_ctx[((j >> 2) * 8 + rank) * 128 + (j & 3) * 32 + lane]);
            if (__all_sync(~0u, (unsigned)(v.x >> 32) == tag && (unsigned)(v.y >> 32) == tag)) {
                asm volatile("st.shared.v2.u32 [%0], {%1,%2};" ::"r"(sbase + F_X + (j >> 2) * FXP + ((j & 3) * 32 + lane) * 8), "r"((uint32_t)v.x), "r"((uint32_t)v.y) : "memory");
                j++;
            } else {
                __nanosleep(500);
                if (++n > SPIN_LIMIT) __trap();
            }
        }
    }
    __syncwarp();
    if (lane == 0) st_release_cta_shared(sbase + M_HELP + 32, 1u);
}
__device__ __forceinline__ void out_late(uint32_t sbase, int rank) {
    unsigned n = 0;
    while (ld_acquire_cta_shared(sbase + M_HELP + 32) == 0) { if (++n > (SPIN_LIMIT << 4)) __trap(); }
    while (ld_acquire(&g_vdone[24 + rank][0]) < 4 * UPP) { if (++n > SPIN_LIMIT) __trap(); }
    TS(12);
    out_fetch(sbase, 7, 24 + rank);
    __syncwarp();
    if ((threadIdx.x & 31) == 0) asm volatile("mbarrier.arrive.shared::cta.b64 _, [%0];" ::"r"(sbase + F_BAR + 72) : "memory");
    TS(13);
}
__device__ __forceinline__ void out_project(uint32_t sbase, int rank, int w) {
    const int lane = threadIdx.x & 31, g = lane >> 2, t = lane & 3;
    unsigned n = 0;
    while (ld_acquire_cta_shared(sbase + M_HELP + 32) == 0) { __nanosleep(500); if (++n > SPIN_LIMIT) __trap(); }
    asm volatile("barrier.cluster.wait.acquire.aligned;" ::: "memory");
    const uint32_t rdst = mapa(sbase + F_RECV + 1024 + rank * 128 + (g & 3) * 32 + t * 16, 2 * w + (g >> 2));
    const uint32_t rbar = mapa(sbase + F_BAR + 8, 2 * w + (g >> 2));
    while (ld_acquire_cta_shared(sbase + M_HELP + 28) == 0) { __nanosleep(200); if (++n > SPIN_LIMIT) __trap(); }
    const uint32_t da = (1u << 16) | (((sbase + F_W) & 0x3ffff) >> 4), db = (4u << 16) | (((sbase + F_X) & 0x3ffff) >> 4);
    float d[4] = {0.f, 0.f, 0.f, 0.f};
#pragma unroll
    for (int i = 0; i < 8; i++) {
        mbar_spin(sbase + F_BAR + 16 + i * 8);
        wgmma_tile(d, da + (i % 6) * 1024, db + i * (FXP / 16), i & 3);
        if (i < 2 || (i & 3) == 3) asm volatile("wgmma.wait_group.sync.aligned 0;" : "+f"(d[0]), "+f"(d[1]), "+f"(d[2]), "+f"(d[3])::"memory");
        if (i < 2) {
            asm volatile("{\n.reg .pred p;\nsetp.eq.u32 p, %1, 0;\n@p mbarrier.arrive.shared::cta.b64 _, [%0];\n}"
                         ::"r"(sbase + F_BAR + 80 + i * 8), "r"(lane) : "memory");
        } else if ((i & 3) == 3) {
            if (t < 2)
                asm volatile("st.async.weak.shared::cluster.mbarrier::complete_tx::bytes.v4.f32 [%0], {%1,%2,%3,%4}, [%5];"
                             ::"r"(rdst - (i < 4 ? 1024 : 0)), "f"(d[0]), "f"(d[1]), "f"(d[2]), "f"(d[3]), "r"(rbar - (i < 4 ? 8 : 0)) : "memory");
            __syncwarp();
        }
    }
}
__device__ __forceinline__ void out_issue_sum(const Params& p, uint32_t sbase, int c, int rank, uint64_t pol) {
    const int lane = threadIdx.x & 31;
    if (lane == 0) {
        unsigned n = 0;
        while (ld_acquire_cta_shared(sbase + M_HELP + 32) == 0) { __nanosleep(500); if (++n > SPIN_LIMIT) __trap(); }
        asm volatile("prefetch.tensormap [%0];" ::"l"(&p.tm_wf) : "memory");
        asm volatile("prefetch.tensormap [%0];" ::"l"(&p.tm_wl) : "memory");
        uint32_t t0;
        while ((t0 = ld_acquire_cta_shared(sbase + M_HELP + 28)) == 0) { __nanosleep(100); if (++n > SPIN_LIMIT) __trap(); }
#pragma unroll 1
        for (int i = 0; i < 8; i++) {
            const int h = (i & 3) * 8 + rank;
            if (i >= 6) mbar_wait(sbase + F_BAR + 32 + i * 8, 0);
            for (int k = 0; k < 4096 && (int)(now_ns() - t0) < 0; k++) {}
            if (i == 0) TS(16);
            tma3d(sbase + F_W + (i < 6 ? i : i - 6) * 16384, i < 4 ? &p.tm_wf : &p.tm_wl, i < 4 ? 0 : c * 64, i < 4 ? h * 128 : h * 16,
                  i < 4 ? c : 0, sbase + F_BAR + 16 + i * 8, pol);
            t0 += FP;
        }
        TS(17);
    }
    __syncwarp();
    __nv_bfloat16* dst = p.out + (((lane >> 1) & 2) + (lane & 1)) * (2 * DM) + DM + c * 64 + (rank >> 1) * 16 + (lane & 2) * 4 +
                         (rank & 1) * 4 + (lane >> 3);
    uint32_t src = sbase + F_RECV + lane * 4;
#pragma unroll 1
    for (int r = 0; r < 2; r++) {
        asm volatile("" : "+l"(dst), "+r"(src));
        mbar_spin_cluster(sbase + F_BAR + r * 8);
        float x[8];
#pragma unroll
        for (int i = 0; i < 8; i++) asm volatile("ld.shared.f32 %0, [%1];" : "=f"(x[i]) : "r"(src + i * 128) : "memory");
        const float v = (((x[0] + x[1]) + (x[2] + x[3])) + (x[4] + x[5])) + (x[6] + x[7]);
        asm volatile("{\n.reg .b16 h;\ncvt.rn.bf16.f32 h, %1;\nst.global.b16 [%0], h;\n}" ::"l"(dst), "f"(v) : "memory");
        TS(14 + r);
        dst -= DM;
        src += 1024;
    }
}

constexpr int BS_WUK = 5, BS_Q = 9, BS_CKV = 11, BS_PART = 27, BS_WUV = 29, BS_END = 33;

__device__ __noinline__ void b_issue(const Params& p, int n, int bi, uint32_t sbase, uint64_t pol) {
    if (n >= BS_END || (n >= BS_Q && n < BS_CKV) || (n >= BS_PART && n < BS_WUV)) return;
    const uint32_t bar = sbase + M_BAR + (NSLOT + n % BRING) * 8;
    const CUtensorMap* tm;
    int row, panel = 2 * bi;
    if (n < BS_WUK) { tm = &p.tm_wq; row = n * 128; }
    else if (n < BS_Q) { tm = &p.tm_wuk; row = (n - BS_WUK) * 128; }
    else if (n < BS_PART) {
        tm = &p.tm_ckv; panel = 0;
        row = (bi >> 3) * SK + ((n - BS_CKV) * 8 + (bi & 7)) * 32;
    }
    else { tm = &p.tm_wuv; row = (n - BS_WUV) * 128; }
    mbar_expect_tx(bar, n == 0 ? 32768 + 4 * 1152 : 32768);
    tma3d(sbase + (n % BRING) * SLOT, tm, 0, row, panel, bar, pol);
}
__device__ __forceinline__ void b_issue_xchg(int n, const void* src, uint32_t sbase, uint64_t pol) {
    asm volatile("fence.proxy.async;" ::: "memory");
#pragma unroll
    for (int i = 0; i < 2; i++) {
        const uint32_t bar = sbase + M_BAR + (NSLOT + (n + i) % BRING) * 8;
        mbar_expect_tx(bar, 32768);
        bulk_load(sbase + ((n + i) % BRING) * SLOT, reinterpret_cast<const char*>(src) + i * 32768, 32768, bar, pol);
    }
}
__device__ __forceinline__ void b_wait(int n, uint32_t sbase) {
    mbar_wait(sbase + M_BAR + (NSLOT + n % BRING) * 8, (n / BRING) & 1);
}

__device__ __noinline__ void b_gemm(const Params& p, uint32_t sbase, int n0, int n1, int ktot, uint32_t xh, uint32_t xl, int pitch,
                                    int bi, uint64_t pol) {
    const int tid = threadIdx.x, warp = tid >> 5, lane = tid & 31, g = lane >> 2, t = lane & 3;
    const uint32_t woff = (warp >> 2) * 16384 + (lane & 15) * 128 + ((((warp & 3) * 2 + (lane >> 4)) ^ (lane & 7)) * 16);
    const uint32_t xoff = (g & 3) * pitch + t * 4;
    float acc[2][4];
#pragma unroll
    for (int i = 0; i < 8; i++) acc[i >> 2][i & 3] = 0.f;
#pragma unroll 1
    for (int n = n0; n < n1; n++) {
        b_wait(n, sbase);
        const uint32_t slot = sbase + (n % BRING) * SLOT + woff;
        const int k0 = (n - n0) * 128;
        const int ns = min(8, (ktot - k0) >> 4);
#pragma unroll 2
        for (int s = 0; s < ns; s++) {
            uint32_t a[4], w[4];
            const uint32_t xo = xoff + (k0 + 16 * s) * 2;
            a[0] = lds32(xh + xo); a[2] = lds32(xh + xo + 16);
            a[1] = xl ? lds32(xl + xo) : 0u; a[3] = xl ? lds32(xl + xo + 16) : 0u;
            ldsm4t(w, slot + s * 2048);
            mma16816(acc[0], a, w[0], w[1]);
            mma16816(acc[1], a, w[2], w[3]);
        }
        __syncthreads();
        if (tid == 0) b_issue(p, n + BD, bi, sbase, pol);
    }
    if (g < 4) {
#pragma unroll
        for (int j = 0; j < 2; j++)
            asm volatile("st.shared.u32 [%0], %1;" ::"r"(sbase + M_QB + g * QP + (warp * 16 + j * 8 + t * 2) * 2),
                         "r"(pack_bf16(acc[j][0] + acc[j][2], acc[j][1] + acc[j][3])) : "memory");
    }
    __syncthreads();
}

__device__ __forceinline__ void b_exchange(unsigned* c, int n, const void* src, uint32_t sbase, uint64_t pol) {
    TS(n == BS_Q ? 24 : 28);
    __syncthreads();
    if (threadIdx.x == 0) {
        TS(n == BS_Q ? 25 : 29);
        fence_gpu();
        TS(n == BS_Q ? 26 : 30);
        red_add_u32(c, 1u);
        wait_count(c, NBCTA);
        TS(n == BS_Q ? 27 : 31);
        b_issue_xchg(n, src, sbase, pol);
    }
}

template <bool CLU>
__device__ __noinline__ void b_chain(const Params& p, char* smem, uint32_t sbase, int bi, unsigned epoch, uint64_t pol) {
    const int tid = threadIdx.x, warp = tid >> 5, lane = tid & 31, g = lane >> 2, t = lane & 3;
    unsigned (*ctl)[32] = g_ctl[epoch & 1];
    float* red = reinterpret_cast<float*>(smem + 5 * SLOT);
    b_gemm(p, sbase, 0, BS_WUK, DM, sbase + M_XB, 0, XP, bi, pol);
    TS(6);
    {
        uint32_t Q[16];
#pragma unroll
        for (int c = 0; c < 16; c++) Q[c] = lds32(sbase + M_QB + (g & 3) * QP + c * 16 + t * 4);
        float* qa = reinterpret_cast<float*>(smem + M_QA);
#pragma unroll 1
        for (int n = BS_WUK; n < BS_Q; n++) {
            b_wait(n, sbase);
            const uint32_t base = sbase + (n % BRING) * SLOT + (warp * 16 + (lane & 15)) * 128;
            float d[2][4];
#pragma unroll
            for (int i = 0; i < 8; i++) d[i >> 2][i & 3] = 0.f;
#pragma unroll
            for (int s = 0; s < 8; s++) {
                uint32_t a[4];
                ldsm4(a, base + (s >> 2) * 16384 + (((2 * (s & 3) + (lane >> 4)) ^ (lane & 7)) * 16));
                mma16816(d[s & 1], a, Q[2 * s], Q[2 * s + 1]);
            }
            const int c = (n - BS_WUK) * 128 + warp * 16 + g + 8 * (t >> 1);
            qa[(2 * (t & 1)) * 512 + c] = (t & 2) ? d[0][2] + d[1][2] : d[0][0] + d[1][0];
            qa[(2 * (t & 1) + 1) * 512 + c] = (t & 2) ? d[0][3] + d[1][3] : d[0][1] + d[1][1];
            __syncthreads();
            if (tid == 0) b_issue(p, n + BD, bi, sbase, pol);
        }
#pragma unroll 1
        for (int r = 0; r < 2; r++) {
            const int id = tid + r * 256;
            const int b = id >> 7, c0 = ((id >> 2) & 31) * 16 + (id & 3) * 2;
            const float2 u0 = *reinterpret_cast<const float2*>(qa + b * 512 + c0);
            const float2 u1 = *reinterpret_cast<const float2*>(qa + b * 512 + c0 + 8);
            const uint32_t h0 = pack_bf16(u0.x, u0.y), h1 = pack_bf16(u1.x, u1.y);
            const uint32_t l0 = pack_bf16(u0.x - bf_lo(h0), u0.y - bf_hi(h0)), l1 = pack_bf16(u1.x - bf_lo(h1), u1.y - bf_hi(h1));
            g_qabs[((id >> 2) * 4 + (bi >> 3)) * 32 + (bi & 7) * 4 + (id & 3)] = make_uint4(h0, l0, h1, l1);
        }
    }
    b_exchange(&ctl[C_BBAR][0], BS_Q, &g_qabs[(bi >> 3) * 4096], sbase, pol);
    {
        uint32_t qf[4][4][4];
        b_wait(BS_Q + (warp >> 2), sbase);
        TS(7);
        {
            const uint4* qs = reinterpret_cast<const uint4*>(smem + ((BS_Q + (warp >> 2)) % BRING) * SLOT) + (warp & 3) * 512 + lane;
#pragma unroll
            for (int s = 0; s < 4; s++)
#pragma unroll
                for (int i = 0; i < 4; i++) {
                    const uint4 v = qs[(s * 4 + i) * 32];
                    qf[i][s][0] = v.x; qf[i][s][1] = v.y; qf[i][s][2] = v.z; qf[i][s][3] = v.w;
                }
        }
        __syncthreads();
        if (tid == 0) { b_issue(p, BS_Q + BD, bi, sbase, pol); b_issue(p, BS_Q + 1 + BD, bi, sbase, pol); }
        float acc[2][8][4];
#pragma unroll
        for (int i = 0; i < 2; i++)
#pragma unroll
            for (int j = 0; j < 8; j++) { acc[i][j][0] = acc[i][j][1] = acc[i][j][2] = acc[i][j][3] = 0.f; }
        float mrun = -INFINITY, lrun = 0.f;
        const int head = tid >> 3, kq = tid & 7;
        float* alpha = reinterpret_cast<float*>(smem + M_ALPHA);
        for (int n = BS_CKV; n < BS_PART; n++) {
            b_wait(n, sbase);
            const uint32_t slot = sbase + (n % BRING) * SLOT;
            float sc[4][4][4];
#pragma unroll
            for (int i = 0; i < 4; i++)
#pragma unroll
                for (int j = 0; j < 4; j++) { sc[i][j][0] = sc[i][j][1] = sc[i][j][2] = sc[i][j][3] = 0.f; }
#pragma unroll
            for (int j = 0; j < 4; j++)
#pragma unroll
                for (int sp = 0; sp < 2; sp++) {
                    uint32_t bf[4];
                    ldsm4(bf, slot + warp * 4096 + (8 * j + (lane & 7)) * 128 + (((4 * sp + (lane >> 3)) ^ (lane & 7)) * 16));
#pragma unroll
                    for (int i = 0; i < 4; i++) {
                        mma16816(sc[i][j], qf[i][2 * sp], bf[0], bf[1]);
                        mma16816(sc[i][j], qf[i][2 * sp + 1], bf[2], bf[3]);
                    }
                }
#pragma unroll
            for (int i = 0; i < 4; i++)
#pragma unroll
                for (int j = 0; j < 4; j++)
                    *reinterpret_cast<float2*>(red + warp * 1024 + (8 * i + g) * 32 + ((8 * j) ^ (8 * (g & 3))) + 2 * t) =
                        make_float2(sc[i][j][0] + sc[i][j][2], sc[i][j][1] + sc[i][j][3]);
            __syncthreads();
            if (tid == 0 && n > BS_CKV) b_issue(p, n - 1 + BD, bi, sbase, pol);
            {
                float4 s = make_float4(0.f, 0.f, 0.f, 0.f);
#pragma unroll
                for (int w = 0; w < 8; w++) {
                    const float4 v = *reinterpret_cast<const float4*>(red + w * 1024 + head * 32 + ((4 * kq) ^ (8 * (head & 3))));
                    s.x += v.x; s.y += v.y; s.z += v.z; s.w += v.w;
                }
                const uint32_t r0 = pack_bf16(s.x, s.y), r1 = pack_bf16(s.z, s.w);
                const uint32_t s0 = pack_bf16(bf_lo(r0) * SCALE, bf_hi(r0) * SCALE);
                const uint32_t s1 = pack_bf16(bf_lo(r1) * SCALE, bf_hi(r1) * SCALE);
                const float f0 = bf_lo(s0), f1 = bf_hi(s0), f2 = bf_lo(s1), f3 = bf_hi(s1);
                float mx = fmaxf(fmaxf(f0, f1), fmaxf(f2, f3));
                mx = fmaxf(mx, __shfl_xor_sync(~0u, mx, 1));
                mx = fmaxf(mx, __shfl_xor_sync(~0u, mx, 2));
                mx = fmaxf(mx, __shfl_xor_sync(~0u, mx, 4));
                const float mnew = fmaxf(mrun, mx);
                const float al = expsub(mrun, mnew);
                const float p0 = expsub(f0, mnew), p1 = expsub(f1, mnew), p2 = expsub(f2, mnew), p3 = expsub(f3, mnew);
                lrun = lrun * al + ((p0 + p1) + (p2 + p3));
                mrun = mnew;
                *reinterpret_cast<uint2*>(smem + M_P + head * 80 + kq * 8) = make_uint2(pack_bf16(p0, p1), pack_bf16(p2, p3));
                if (kq == 0) alpha[head] = al;
            }
            __syncthreads();
            {
                uint32_t pf[2][2][4];
#pragma unroll
                for (int i = 0; i < 2; i++)
#pragma unroll
                    for (int ks = 0; ks < 2; ks++)
                        ldsm4(pf[i][ks], sbase + M_P + (16 * i + (lane & 15)) * 80 + (16 * ks + 8 * (lane >> 4)) * 2);
#pragma unroll
                for (int i = 0; i < 2; i++) {
                    const float a0 = alpha[16 * i + g], a1 = alpha[16 * i + 8 + g];
#pragma unroll
                    for (int j = 0; j < 8; j++) { acc[i][j][0] *= a0; acc[i][j][1] *= a0; acc[i][j][2] *= a1; acc[i][j][3] *= a1; }
                }
#pragma unroll
                for (int j = 0; j < 8; j++) {
                    uint32_t bf[4];
                    ldsm4t(bf, slot + warp * 4096 + lane * 128 + ((j ^ (lane & 7)) * 16));
#pragma unroll
                    for (int i = 0; i < 2; i++) {
                        mma16816(acc[i][j], pf[i][0], bf[0], bf[1]);
                        mma16816(acc[i][j], pf[i][1], bf[2], bf[3]);
                    }
                }
            }
        }
        __syncthreads();
        if (tid == 0) b_issue(p, BS_PART - 1 + BD, bi, sbase, pol);
        lrun += __shfl_xor_sync(~0u, lrun, 1);
        lrun += __shfl_xor_sync(~0u, lrun, 2);
        lrun += __shfl_xor_sync(~0u, lrun, 4);
        if (kq == 0) g_bml[head * NBCTA + bi] = make_float2(mrun, lrun);
#pragma unroll
        for (int i = 0; i < 2; i++)
#pragma unroll
            for (int j = 0; j < 8; j++) {
                g_bpart[((16 * i + g) * NBCTA + bi) * 256 + warp * 32 + j * 4 + t] = make_float2(acc[i][j][0], acc[i][j][1]);
                g_bpart[((16 * i + 8 + g) * NBCTA + bi) * 256 + warp * 32 + j * 4 + t] = make_float2(acc[i][j][2], acc[i][j][3]);
            }
    }
#pragma unroll 1
    for (int i = tid; i < NH * 36 && !(CLU); i += 256) g_outb[bi * NH * 36 + i] = make_uint4(0u, epoch, 0u, epoch);
    b_exchange(&ctl[C_BBAR + 1][0], BS_PART, &g_bpart[bi * NBCTA * 256], sbase, pol);
    {
        float* omega = reinterpret_cast<float*>(smem + M_OMEGA);
        if (warp == 0) {
            __syncwarp();
            const uint2 ml = ld_relaxed8(&g_bml[bi * NBCTA + lane]);
            const float ms = __uint_as_float(ml.x);
            float m = ms;
            m = fmaxf(m, __shfl_xor_sync(~0u, m, 1));
            m = fmaxf(m, __shfl_xor_sync(~0u, m, 2));
            m = fmaxf(m, __shfl_xor_sync(~0u, m, 4));
            const float w = expsub(ms, m);
            float l = w * __uint_as_float(ml.y);
            l += __shfl_xor_sync(~0u, l, 1);
            l += __shfl_xor_sync(~0u, l, 2);
            l += __shfl_xor_sync(~0u, l, 4);
            omega[lane] = w / l;
        }
        __syncthreads();
        b_wait(BS_PART, sbase);
        b_wait(BS_PART + 1, sbase);
#pragma unroll 1
        for (int b = 0; b < 4; b++) {
            const float2* ps = reinterpret_cast<const float2*>(smem + ((BS_PART + (b >> 1)) % BRING) * SLOT) + (b & 1) * 2048 + tid;
            float c0 = 0.f, c1 = 0.f;
#pragma unroll
            for (int s = 0; s < 8; s++) {
                const float w = omega[b * 8 + s];
                const float2 v = ps[s * 256];
                c0 = fmaf(w, v.x, c0);
                c1 = fmaf(w, v.y, c1);
            }
            const uint32_t hi = pack_bf16(c0, c1);
            *reinterpret_cast<uint32_t*>(smem + M_CH + b * CP + tid * 4) = hi;
            *reinterpret_cast<uint32_t*>(smem + M_CL + b * CP + tid * 4) = pack_bf16(c0 - bf_lo(hi), c1 - bf_hi(hi));
        }
        __syncthreads();
        if (tid == 0) { b_issue(p, BS_PART + BD, bi, sbase, pol); b_issue(p, BS_PART + 1 + BD, bi, sbase, pol); }
    }
    b_gemm(p, sbase, BS_WUV, BS_END, 512, sbase + M_CH, sbase + M_CL, CP, bi, pol);
    TS(12);
    if (CLU) {
        if (tid < 128) {
            const uint32_t xo = sbase + M_QB + ((tid >> 1) & 3) * QP + (tid >> 3) * 16 + (tid & 1) * 8;
            st_tagged2(&g_ctx[bi * 128 + tid], __uint_as_float(lds32(xo)), __uint_as_float(lds32(xo + 4)), epoch + 1);
        }
        return;
    }
    if (tid == 0) {
#pragma unroll 1
        for (int i = 0; i < 4; i++) {
            mbar_expect_tx(sbase + M_BAR + i * 8, 36864);
            tma3d(sbase + i * 36864, &p.tm_wo, 0, bi * 128 + i * 32, 0, sbase + M_BAR + i * 8, pol);
        }
    }
    TS(8);
    {
        float acc[9][4];
#pragma unroll
        for (int j = 0; j < 9; j++) { acc[j][0] = acc[j][1] = acc[j][2] = acc[j][3] = 0.f; }
#pragma unroll 1
        for (int i = 0; i < 4; i++) {
            const uint32_t xo = sbase + M_QB + (g & 3) * QP + i * 64 + t * 4;
            const uint32_t a0[4] = {lds32(xo), 0u, lds32(xo + 16), 0u}, a1[4] = {lds32(xo + 32), 0u, lds32(xo + 48), 0u};
            mbar_wait(sbase + M_BAR + i * 8, 0);
#pragma unroll
            for (int j = 0; j < 9; j++) {
                const int nt = warp * 9 + j;
                uint32_t w[4];
                ldsm4t(w, sbase + i * 36864 + (nt >> 3) * 4096 + lane * 128 + (((nt & 7) ^ (lane & 7)) * 16));
                mma16816(acc[j], a0, w[0], w[1]);
                mma16816(acc[j], a1, w[2], w[3]);
            }
        }
        if (g < 4) {
#pragma unroll
            for (int j = 0; j < 9; j++) {
                const int c2 = (warp * 9 + j) * 4 + t;
                st_tagged2(&g_outb[((c2 / 9) * NH + bi) * 36 + g * 9 + c2 % 9], acc[j][0], acc[j][1], epoch + 1);
            }
        }
    }
    TS(9);
    {
        const uint4* src = g_outb + (bi * NH + (tid >> 3)) * 36 + (tid & 7);
        float2* part = reinterpret_cast<float2*>(red);
        unsigned n = 0;
        while (true) {
            ulonglong2 v[5];
            bool ok = true;
#pragma unroll
            for (int i = 0; i < 5; i++)
                if (i < 4 || (tid & 7) < 4) v[i] = ld_tagged2(src + i * 8);
#pragma unroll
            for (int i = 0; i < 5; i++)
                if (i < 4 || (tid & 7) < 4) {
                    ok = ok && (unsigned)(v[i].x >> 32) == epoch + 1 && (unsigned)(v[i].y >> 32) == epoch + 1;
                    part[(tid >> 3) * 36 + (tid & 7) + i * 8] = make_float2(__uint_as_float((unsigned)v[i].x), __uint_as_float((unsigned)v[i].y));
                }
            if (ok) break;
            __nanosleep(400);
            if (++n > SPIN_LIMIT) __trap();
        }
        __syncthreads();
        if (tid < 36) {
            float s0 = 0.f, s1 = 0.f;
#pragma unroll 8
            for (int h = 0; h < NH; h++) { const float2 v = part[h * 36 + tid]; s0 += v.x; s1 += v.y; }
            *reinterpret_cast<uint32_t*>(p.out + (tid / 9) * 2 * DM + DM + bi * 18 + (tid % 9) * 2) = pack_bf16(s0, s1);
        }
    }
    TS(10);
}

template <bool CLU>
__global__ void __launch_bounds__(256, 1) fused_decode_kernel(const __grid_constant__ First f, const __grid_constant__ Params p) {
    extern __shared__ __align__(1024) char smem_raw[];
    const uint32_t sbase = (smem_u32(smem_raw) + 1023u) & ~1023u;
    char* smem = smem_raw + (sbase - smem_u32(smem_raw));
    const int tid = threadIdx.x, warp = tid >> 5, lane = tid & 31;
    const int blk = blockIdx.x;
    const bool isB = CLU ? blk < NBCTA : (blk & 3) == 0 && (blk >> 2) < NBCTA;
    const int bi = CLU ? blk : blk >> 2;
    const int nb = CLU ? blk - NBCTA : blk - min(NBCTA, (blk + 3) >> 2);
    const int nblk = CLU ? 8 * MINCL : gridDim.x, nnb = nblk - NBCTA;
    const int nstatic = nnb * (NW + XW);
    uint64_t pol, poln;
    asm volatile("createpolicy.fractional.L2::evict_first.b64 %0, 1.0;" : "=l"(pol));
    asm volatile("createpolicy.fractional.L2::evict_normal.b64 %0, 1.0;" : "=l"(poln));
    const uint32_t wbar = sbase + M_BAR + warp * 8, wslot = sbase + warp * SLOT;
    const bool hold = ((blk >> 2) >> KMIN << KMIN) * 4 * UPP < nstatic;
    const uint32_t jbar = sbase + M_BAR + (NSLOT + BRING) * 8, fbar = sbase + M_BAR + 4 * 8;
    const char* eptr = f.ptr[3 + (tid >> 10)];
    asm volatile("" : "+l"(eptr));
    if (warp < 4) {
        if (lane == 0) {
            if (warp == 0) {
                mbar_init(jbar, 1);
                asm volatile("fence.mbarrier_init.release.cluster;" ::: "memory");
                mbar_expect_tx(jbar, 36864 + 4 * 1152);
                if (CLU || blk < 128) tma3d(sbase + J0W, &p.tm_j0, blk * 32, 0, 0, jbar, poln);
            } else if (warp & 1) {
                if (warp & 2) {
#pragma unroll
                    for (int i = 0; i < NSLOT + BRING; i++) mbar_init(sbase + M_BAR + i * 8, 1);
                    mbar_expect_tx(fbar, NEARLY * TILE_BYTES);
                } else if (CLU && !isB) {
#pragma unroll
                    for (int i = 0; i < 2; i++) {
                        mbar_init(sbase + F_BAR + i * 8, 1);
                        mbar_expect_tx(sbase + F_BAR + i * 8, 1024);
                    }
                }
                asm volatile("fence.mbarrier_init.release.cluster;" ::: "memory");
            } else {
#pragma unroll
                for (int i = 0; i < 4; i++) asm volatile("st.shared.v4.u32 [%0], {%1,%1,%1,%1};" ::"r"(sbase + M_HELP + i * 16), "r"(0) : "memory");
            }
        }
    } else if (!isB) {
        const unsigned t = tid - 128;
        const char* const* q = f.ptr + (tid >> 10);
        asm volatile("{\n.reg .pred p;\nsetp.ne.u32 p, %1, 0;\n@p prefetch.global.L2 [%0];\n}"
                     ::"l"(q[0] + (nb * 8 + (t >> 4)) * 8192 + (t & 15) * 128), "r"((uint32_t)(nb < DM / 8)) : "memory");
        asm volatile("{\n.reg .pred p;\nsetp.ne.u32 p, %1, 0;\n@p prefetch.global.L2 [%0];\n}"
                     ::"l"(q[2] + t * 128), "r"((uint32_t)(nb == DM / 8 && t < 36)) : "memory");
    } else if (tid == 128) {
        asm volatile("prefetch.tensormap [%0];" ::"l"(&p.tm_j0) : "memory");
        asm volatile("prefetch.tensormap [%0];" ::"l"(&p.tm_wq) : "memory");
    }
    __syncthreads();
    if (tid == 128) {
        if (CLU || blk < 128) bulk_load(sbase + M_XA, f.ptr[2], 4608, jbar, poln);
        if (!isB && !hold)
            bulk_load(sbase, f.ptr[1] + (size_t)((nb * NEARLY >> 7) * (NH * UPP) + (nb * NEARLY & 127)) * TILE_BYTES, NEARLY * TILE_BYTES, fbar, pol);
    }
    const int u0 = ((warp / NEARLY) * nnb + nb) * NEARLY + warp % NEARLY;
    unsigned epoch = 0;
    if (lane == 0) epoch = ld_relaxed4(eptr);
    TS(0);
    if (CLU && !isB) asm volatile("barrier.cluster.arrive.relaxed.aligned;" ::: "memory");
    if ((warp >> 1) == 2 && blk < 128) st_relaxed64(&g_qll[((tid - 128) >> 4) * 2048 + blk * 16 + (tid & 15)], 0ull);
    if (isB || warp >= NW + XW) epoch = __shfl_sync(~0u, epoch, 0);
    if (isB && tid == 96) {
        if (hold) { unsigned n = 0; while (ld_acquire_cta_shared(sbase + M_HELP + 24) < 2) { if (++n > (SPIN_LIMIT << 4)) __trap(); } }
#pragma unroll 1
        for (int b = 0; b < 4; b++) bulk_load(sbase + M_XB + b * XP, p.xb + b * DM, 1152, sbase + M_BAR + NSLOT * 8, pol);
#pragma unroll 1
        for (int n = 0; n < BD; n++) b_issue(p, n, bi, sbase, pol);
    }
    if (warp >= 4 && blk < 128) {
        const int g = lane >> 2, t = lane & 3, j = tid - 128;
#pragma unroll 1
        for (int sl = blk, ph = 0;; sl += 128 - nblk, ph = 1) {
        mbar_wait(jbar, ph);
        TS(13);
        float acc[4][4];
#pragma unroll
        for (int i = 0; i < 16; i++) acc[i >> 2][i & 3] = 0.f;
        const uint32_t wa = sbase + J0W + ((warp - 4) * 144 + (lane & 15)) * 64;
        const uint32_t sw = (lane >> 1) & 3, xa = sbase + M_XA + (g & 3) * 1152 + (warp - 4) * 288 + t * 4;
#pragma unroll 3
        for (int s = 0; s < 9; s++) {
            const uint32_t a[4] = {lds32(xa + s * 32), 0u, lds32(xa + s * 32 + 16), 0u};
            uint32_t w0[4], w1[4];
            ldsm4t(w0, wa + s * 1024 + (((lane >> 4) ^ sw) * 16));
            ldsm4t(w1, wa + s * 1024 + (((2 + (lane >> 4)) ^ sw) * 16));
            mma16816(acc[0], a, w0[0], w0[1]);
            mma16816(acc[1], a, w0[2], w0[3]);
            mma16816(acc[2], a, w1[0], w1[1]);
            mma16816(acc[3], a, w1[2], w1[3]);
        }
        float2* j0 = reinterpret_cast<float2*>(smem + M_J0);
        if (g < 4) {
#pragma unroll
            for (int i = 0; i < 4; i++) j0[(warp - 4) * 64 + g * 16 + i * 4 + t] = make_float2(acc[i][0], acc[i][1]);
        }
        asm volatile("bar.sync 1, 128;" ::: "memory");
        const bool again = sl == blk && blk + 128 - nblk >= nblk;
        if (again && tid == 224) {
            mbar_expect_tx(jbar, 36864);
            tma3d(sbase + J0W, &p.tm_j0, (blk + 128 - nblk) * 32, 0, 0, jbar, pol);
        }
        if (warp < 6) {
            const float2 v0 = j0[j], v1 = j0[64 + j], v2 = j0[128 + j], v3 = j0[192 + j];
            st_relaxed64(&g_qll[(j >> 4) * 2048 + sl * 16 + (j & 15)],
                         (unsigned long long)pack_bf16((v0.x + v1.x) + (v2.x + v3.x), (v0.y + v1.y) + (v2.y + v3.y)) |
                             ((unsigned long long)(epoch + 1) << 32));
            __syncwarp();
            if (lane == 0) asm volatile("red.relaxed.cta.shared::cta.add.u32 [%0], 1;" ::"r"(sbase + M_HELP + 24) : "memory");
        } else if (warp == 7) {
            if (blk < C_LINES) g_ctl[(epoch & 1) ^ 1][blk][lane] = 0;
        }
        TS(1);
        if (!again) break;
        asm volatile("bar.sync 1, 128;" ::: "memory");
        }
    }
    if (isB) {
        b_chain<CLU>(p, smem, sbase, bi, epoch, pol);
        return;
    }
    if (warp < NW + XW) {
        a_worker<CLU>(p, u0, warp >= NW + ((nb & 3) < (CLU ? X3C : X3) ? 1 : 0), hold, nstatic, wslot, wbar, warp < NEARLY && !hold ? fbar : wbar,
                      sbase + M_HELP, epoch, pol);
        if (CLU && nb < NFIN) {
            if (warp == 3) out_issue_sum(p, sbase, nb >> 3, nb & 7, pol);
            else if (warp == 0) out_late(sbase, nb & 7);
        }
        return;
    } else if (warp == 7) {
#pragma unroll 1
        for (int i = nb; i < 4 * NH; i += nnb) g_oacc[i * 32 + lane] = make_float4(0.f, 0.f, 0.f, 0.f);
        if (nb < NREP * NH) g_vdone[nb][lane] = 0;
        __syncwarp();
        k_helper(sbase + M_HELP, epoch);
        if (nb == 0 && lane == 0) g_epoch = epoch + 1;
        __syncwarp();
        if (CLU && nb < NFIN) out_early(sbase, nb & 7, epoch + 1);
    } else if (CLU) {
    } else if (warp == 6 && nb < NFIN) {
        finisher(p, sbase, nb);
        TS(4);
    } else if (warp >= 6 - NPOLL && nb < NFIN) {
        v_poller(sbase, nb, warp - (6 - NPOLL));
    }
    if (CLU && nb < NFIN) out_project(sbase, nb & 7, warp - 4);
}

}

typedef CUresult (*EncodeFn)(CUtensorMap*, CUtensorMapDataType, cuuint32_t, void*, const cuuint64_t*, const cuuint64_t*,
                             const cuuint32_t*, const cuuint32_t*, CUtensorMapInterleave, CUtensorMapSwizzle,
                             CUtensorMapL2promotion, CUtensorMapFloatOOBfill);

extern "C" void kernel_launch(void* const* d_in, const int* in_sizes, int n_in, void* d_out, int out_size) {
    (void)in_sizes; (void)n_in; (void)out_size;
    static int nsm = 0, ncl = 0;
    static EncodeFn encode = nullptr;
    static const char* epoch_ptr = nullptr;
    cudaLaunchConfig_t cfg = {};
    cudaLaunchAttribute at[1];
    at[0].id = cudaLaunchAttributeClusterDimension;
    at[0].val.clusterDim.x = 8; at[0].val.clusterDim.y = 1; at[0].val.clusterDim.z = 1;
    cfg.blockDim = dim3(256); cfg.dynamicSmemBytes = SMEM_BYTES; cfg.stream = cudaStreamPerThread; cfg.attrs = at; cfg.numAttrs = 1;
    if (nsm == 0) {
        int dev = 0;
        cudaGetDevice(&dev);
        cudaDeviceGetAttribute(&nsm, cudaDevAttrMultiProcessorCount, dev);
        cudaFuncSetAttribute(fused_decode_kernel<false>, cudaFuncAttributeMaxDynamicSharedMemorySize, SMEM_BYTES);
        cudaFuncSetAttribute(fused_decode_kernel<true>, cudaFuncAttributeMaxDynamicSharedMemorySize, SMEM_BYTES);
        cfg.gridDim = dim3(128);
        if (cudaOccupancyMaxActiveClusters(&ncl, fused_decode_kernel<true>, &cfg) != cudaSuccess) { ncl = 0; (void)cudaGetLastError(); }
        if (ncl > MINCL) ncl = MINCL;
        cudaGetSymbolAddress((void**)&epoch_ptr, g_epoch);
        void* fn = nullptr;
        cudaDriverEntryPointQueryResult qr;
        cudaGetDriverEntryPoint("cuTensorMapEncodeTiled", &fn, cudaEnableDefault, &qr);
        encode = (EncodeFn)fn;
    }
    Params p;
    auto panels = [&](CUtensorMap* tm, void* ptr, int rows, int cols, int box_rows, int box_panels) {
        const cuuint64_t gd[3] = {64, (cuuint64_t)rows, (cuuint64_t)(cols / 64)}, gs[2] = {(cuuint64_t)cols * 2, 128};
        const cuuint32_t box[3] = {64, (cuuint32_t)box_rows, (cuuint32_t)box_panels}, es[3] = {1, 1, 1};
        encode(tm, CU_TENSOR_MAP_DATA_TYPE_BFLOAT16, 3, ptr, gd, gs, box, es, CU_TENSOR_MAP_INTERLEAVE_NONE,
               CU_TENSOR_MAP_SWIZZLE_128B, CU_TENSOR_MAP_L2_PROMOTION_L2_256B, CU_TENSOR_MAP_FLOAT_OOB_FILL_NONE);
    };
    panels(&p.tm_wq, d_in[7], DM, 4096, 128, 2);
    panels(&p.tm_wuk, d_in[8], 512, 4096, 128, 2);
    panels(&p.tm_wuv, d_in[9], 512, 4096, 128, 2);
    panels(&p.tm_wo, d_in[10], 4096, DM, 32, 9);
    panels(&p.tm_wf, d_in[10], 4096, DM, 128, 1);
    panels(&p.tm_ckv, d_in[6], 4 * SK, 512, 32, 8);
    {
        const cuuint64_t gd[3] = {4096, 192, 3}, gs[2] = {8192, 192 * 8192};
        const cuuint32_t box[3] = {32, 192, 3}, es[3] = {1, 1, 1};
        encode(&p.tm_j0, CU_TENSOR_MAP_DATA_TYPE_BFLOAT16, 3, d_in[3], gd, gs, box, es, CU_TENSOR_MAP_INTERLEAVE_NONE,
               CU_TENSOR_MAP_SWIZZLE_64B, CU_TENSOR_MAP_L2_PROMOTION_L2_128B, CU_TENSOR_MAP_FLOAT_OOB_FILL_NONE);
    }
    {
        const cuuint64_t gd[3] = {DM, 512, 8}, gs[2] = {8 * DM * 2, DM * 2};
        const cuuint32_t box[3] = {64, 16, 8}, es[3] = {1, 1, 1};
        encode(&p.tm_wl, CU_TENSOR_MAP_DATA_TYPE_BFLOAT16, 3, d_in[4], gd, gs, box, es, CU_TENSOR_MAP_INTERLEAVE_NONE,
               CU_TENSOR_MAP_SWIZZLE_128B, CU_TENSOR_MAP_L2_PROMOTION_L2_256B, CU_TENSOR_MAP_FLOAT_OOB_FILL_NONE);
    }
    p.kc = (const __nv_bfloat16*)d_in[1];
    p.vc = (const __nv_bfloat16*)d_in[2];
    p.wo = (const __nv_bfloat16*)d_in[4];
    p.xb = (const __nv_bfloat16*)d_in[5];
    p.out = (__nv_bfloat16*)d_out;
    const First f = {{(const char*)d_in[3], (const char*)d_in[1], (const char*)d_in[0], epoch_ptr}};
    if (ncl >= MINCL) {
        cfg.gridDim = dim3(8 * ncl);
        cudaLaunchKernelEx(&cfg, fused_decode_kernel<true>, f, p);
    } else {
        fused_decode_kernel<false><<<nsm, 256, SMEM_BYTES, cudaStreamPerThread>>>(f, p);
    }
}
```

```cpp
#include <cuda_runtime.h>
#include <cuda.h>
#include <cuda_bf16.h>
#include <stdint.h>

namespace {

constexpr int NH = 32, SK = 4096, DM = 576;
constexpr int KEYS = 128;
constexpr int UPP = SK / KEYS;
constexpr int NUK = 4 * NH * UPP;
constexpr int TILE_BYTES = KEYS * 256;
#define NWORK 2
constexpr int NW = NWORK;
constexpr int NBCTA = 32;
constexpr int MINCL = 15;
constexpr int NFIN = 72;
constexpr int SLOT = 32768;
constexpr int NSLOT = 6;
constexpr int BRING = 5;
constexpr int J0W = 5 * SLOT;
constexpr int MISC = NSLOT * SLOT + 4096;
constexpr int XP = 1168, CP = 1040, QP = 272;
constexpr int M_XA = MISC;
constexpr int M_XB = M_XA + 4 * XP;
constexpr int M_CH = M_XB + 4 * XP;
constexpr int M_CL = M_CH + 4 * CP;
constexpr int M_QB = M_CL + 4 * CP;
constexpr int M_QA = M_CH;
constexpr int M_J0 = M_QB + 4 * QP;
constexpr int M_P = M_J0 + 2048;
constexpr int M_ALPHA = M_P + 2560;
constexpr int M_OMEGA = M_ALPHA + 128;
constexpr int M_BAR = M_OMEGA + 128;
constexpr int M_HELP = M_BAR + 128;
constexpr int F_W = 3 * SLOT;
constexpr int F_X = NSLOT * SLOT, FXP = 1088;
constexpr int F_RECV = F_X + 8 * FXP;
constexpr int F_BAR = M_P;
constexpr int SMEM_BYTES = M_HELP + 128 + 1024;
static_assert(F_RECV + 2048 <= M_J0, "output phase layout");
static_assert(SMEM_BYTES <= 232448 && M_BAR % 8 == 0 && M_QA % 16 == 0 && M_P % 16 == 0, "smem layout");
#define XW 2
#define X3 1
#define X3C 2
#define NEARLY 2
#define BD 4
#define FPF 3
#define FSLEEP 800
#define VMINC 2
#define FJ 256
#define FP 384
#define NPOLL 2
#define PGAP 200
static_assert(NW + XW == 4 && 4 % NEARLY == 0 && BD <= BRING, "slots 4 and 5 hold the finisher weights");
constexpr int KMIN = 2, KMAX = 4, VMAX = 4;
constexpr float SCALE = 0.08838834764831845f;
constexpr float LOG2E = 1.4426950408889634f;
constexpr unsigned SPIN_LIMIT = 1u << 24;

#define NREP 2
constexpr int C_QUEUE = 0, C_KDONE = 1, C_BBAR = 3, C_LINES = 5;

struct First { const char* ptr[4]; };
struct Params {
    const __nv_bfloat16 *kc, *vc, *wo, *xb;
    __nv_bfloat16* out;
    CUtensorMap tm_j0;
    CUtensorMap tm_wq, tm_wuk, tm_ckv, tm_wuv, tm_wo;
    CUtensorMap tm_wl;
    CUtensorMap tm_wf;
};

__device__ unsigned g_epoch;
__device__ unsigned g_ctl[2][C_LINES][32];
__device__ uint2 g_qll[4 * 2048];
__device__ uint2 g_scores[128 * SK / 4];
__device__ float2 g_stats[128 * UPP];
__device__ float4 g_oacc[128 * 32];
__device__ unsigned g_vdone[NREP * NH][32];
__device__ uint4 g_qabs[4 * 8 * 4 * 4 * 32];
__device__ float2 g_bpart[NBCTA * NH * 256];
__device__ float2 g_bml[NBCTA * NH];
__device__ uint4 g_ctx[NH * 128];
__device__ uint4 g_outb[NBCTA * NH * 36];

__device__ __forceinline__ int cluster_role(int b) {
    const int i = b - NFIN, q = ((i >> 1) * 43 >> 7) * 2, r = i - 3 * q;
    int x = i - q;
    asm("{\n.reg .pred p;\nsetp.ge.s32 p, %1, 4;\nselp.s32 %0, %2, %0, p;\nsetp.lt.s32 p, %3, 0;\nselp.s32 %0, %4, %0, p;\n}"
        : "+r"(x) : "r"(r), "r"(NBCTA + NFIN - 4 + q + r), "r"(i), "r"(b + NBCTA));
    return x;
}

#define TS(i)
#define TSV(i, v)
#define LAND(i)
#define CLK(x)
#define ACC(a, x, y)

__device__ __forceinline__ uint32_t smem_u32(const void* p) { return (uint32_t)__cvta_generic_to_shared(p); }
__device__ __forceinline__ void mbar_init(uint32_t bar, uint32_t cnt) {
    asm volatile("mbarrier.init.shared::cta.b64 [%0], %1;" ::"r"(bar), "r"(cnt) : "memory");
}
__device__ __forceinline__ void mbar_expect_tx(uint32_t bar, uint32_t bytes) {
    asm volatile("mbarrier.arrive.expect_tx.shared::cta.b64 _, [%0], %1;" ::"r"(bar), "r"(bytes) : "memory");
}
__device__ __forceinline__ bool mbar_try(uint32_t bar, uint32_t parity) {
    uint32_t ok;
    asm volatile("{\n.reg .pred p;\nmbarrier.try_wait.parity.shared::cta.b64 p, [%1], %2;\nselp.u32 %0, 1, 0, p;\n}\n"
                 : "=r"(ok) : "r"(bar), "r"(parity) : "memory");
    return ok;
}
__device__ __forceinline__ void mbar_wait(uint32_t bar, uint32_t parity) {
    unsigned n = 0;
    while (!mbar_try(bar, parity)) { if (++n > SPIN_LIMIT) __trap(); }
}
__device__ __forceinline__ void bulk_load(uint32_t dst, const void* src, uint32_t bytes, uint32_t bar, uint64_t pol) {
    asm volatile("cp.async.bulk.shared::cluster.global.mbarrier::complete_tx::bytes.L2::cache_hint [%0], [%1], %2, [%3], %4;"
                 ::"r"(dst), "l"(src), "r"(bytes), "r"(bar), "l"(pol) : "memory");
}
__device__ __forceinline__ void tma3d(uint32_t dst, const CUtensorMap* tm, int c0, int c1, int c2, uint32_t bar, uint64_t pol) {
    asm volatile("cp.async.bulk.tensor.3d.shared::cluster.global.mbarrier::complete_tx::bytes.L2::cache_hint [%0], [%1, {%3,%4,%5}], [%2], %6;"
                 ::"r"(dst), "l"(tm), "r"(bar), "r"(c0), "r"(c1), "r"(c2), "l"(pol) : "memory");
}
__device__ __forceinline__ void l2_prefetch(const void* src, uint32_t bytes) {
    asm volatile("cp.async.bulk.prefetch.L2.global [%0], %1;" ::"l"(src), "r"(bytes) : "memory");
}
__device__ __forceinline__ void ldsm4(uint32_t (&r)[4], uint32_t addr) {
    asm volatile("ldmatrix.sync.aligned.m8n8.x4.shared.b16 {%0,%1,%2,%3}, [%4];"
                 : "=r"(r[0]), "=r"(r[1]), "=r"(r[2]), "=r"(r[3]) : "r"(addr));
}
__device__ __forceinline__ void ldsm4t(uint32_t (&r)[4], uint32_t addr) {
    asm volatile("ldmatrix.sync.aligned.m8n8.x4.trans.shared.b16 {%0,%1,%2,%3}, [%4];"
                 : "=r"(r[0]), "=r"(r[1]), "=r"(r[2]), "=r"(r[3]) : "r"(addr));
}
__device__ __forceinline__ void mma16816(float (&d)[4], const uint32_t (&a)[4], uint32_t b0, uint32_t b1) {
    asm("mma.sync.aligned.m16n8k16.row.col.f32.bf16.bf16.f32 {%0,%1,%2,%3}, {%4,%5,%6,%7}, {%8,%9}, {%0,%1,%2,%3};"
        : "+f"(d[0]), "+f"(d[1]), "+f"(d[2]), "+f"(d[3])
        : "r"(a[0]), "r"(a[1]), "r"(a[2]), "r"(a[3]), "r"(b0), "r"(b1));
}
__device__ __forceinline__ void wgmma_tile(float (&d)[4], uint32_t da, uint32_t db, int accumulate) {
    asm volatile("{\n.reg .pred p;\n.reg .b32 x, y;\n.reg .b64 a, b;\nsetp.ne.u32 p, %6, 0;\nwgmma.fence.sync.aligned;\n"
                 "add.u32 x, %4, 0;\nadd.u32 y, %5, 0;\nmov.b64 a, {x, 0x40000040};\nmov.b64 b, {y, 1};\n"
                 "wgmma.mma_async.sync.aligned.m64n8k16.f32.bf16.bf16 {%0,%1,%2,%3}, a, b, p, 1, 1, 1, 0;\n"
                 "add.u32 x, %4, 128;\nadd.u32 y, %5, 8;\nmov.b64 a, {x, 0x40000040};\nmov.b64 b, {y, 1};\n"
                 "wgmma.mma_async.sync.aligned.m64n8k16.f32.bf16.bf16 {%0,%1,%2,%3}, a, b, 1, 1, 1, 1, 0;\n"
                 "add.u32 x, %4, 256;\nadd.u32 y, %5, 16;\nmov.b64 a, {x, 0x40000040};\nmov.b64 b, {y, 1};\n"
                 "wgmma.mma_async.sync.aligned.m64n8k16.f32.bf16.bf16 {%0,%1,%2,%3}, a, b, 1, 1, 1, 1, 0;\n"
                 "add.u32 x, %4, 384;\nadd.u32 y, %5, 24;\nmov.b64 a, {x, 0x40000040};\nmov.b64 b, {y, 1};\n"
                 "wgmma.mma_async.sync.aligned.m64n8k16.f32.bf16.bf16 {%0,%1,%2,%3}, a, b, 1, 1, 1, 1, 0;\n"
                 "add.u32 x, %4, 512;\nadd.u32 y, %5, 32;\nmov.b64 a, {x, 0x40000040};\nmov.b64 b, {y, 1};\n"
                 "wgmma.mma_async.sync.aligned.m64n8k16.f32.bf16.bf16 {%0,%1,%2,%3}, a, b, 1, 1, 1, 1, 0;\n"
                 "add.u32 x, %4, 640;\nadd.u32 y, %5, 40;\nmov.b64 a, {x, 0x40000040};\nmov.b64 b, {y, 1};\n"
                 "wgmma.mma_async.sync.aligned.m64n8k16.f32.bf16.bf16 {%0,%1,%2,%3}, a, b, 1, 1, 1, 1, 0;\n"
                 "add.u32 x, %4, 768;\nadd.u32 y, %5, 48;\nmov.b64 a, {x, 0x40000040};\nmov.b64 b, {y, 1};\n"
                 "wgmma.mma_async.sync.aligned.m64n8k16.f32.bf16.bf16 {%0,%1,%2,%3}, a, b, 1, 1, 1, 1, 0;\n"
                 "add.u32 x, %4, 896;\nadd.u32 y, %5, 56;\nmov.b64 a, {x, 0x40000040};\nmov.b64 b, {y, 1};\n"
                 "wgmma.mma_async.sync.aligned.m64n8k16.f32.bf16.bf16 {%0,%1,%2,%3}, a, b, 1, 1, 1, 1, 0;\n"
                 "wgmma.commit_group.sync.aligned;\n}"
                 : "+f"(d[0]), "+f"(d[1]), "+f"(d[2]), "+f"(d[3]) : "r"(da), "r"(db), "r"(accumulate) : "memory");
}
__device__ __forceinline__ uint32_t lds32(uint32_t a) {
    uint32_t v;
    asm volatile("ld.shared.u32 %0, [%1];" : "=r"(v) : "r"(a));
    return v;
}
__device__ __forceinline__ unsigned ld_acquire(const unsigned* p) {
    unsigned v;
    asm volatile("ld.acquire.gpu.global.u32 %0, [%1];" : "=r"(v) : "l"(p) : "memory");
    return v;
}
__device__ __forceinline__ uint2 ld_relaxed8(const void* p) {
    uint2 v;
    asm volatile("ld.relaxed.gpu.global.v2.u32 {%0,%1}, [%2];" : "=r"(v.x), "=r"(v.y) : "l"(p) : "memory");
    return v;
}
__device__ __forceinline__ unsigned ld_relaxed4(const void* p) {
    unsigned v;
    asm volatile("ld.relaxed.gpu.global.u32 %0, [%1];" : "=r"(v) : "l"(p) : "memory");
    return v;
}
__device__ __forceinline__ unsigned atom_inc(unsigned* p) {
    unsigned v;
    asm volatile("atom.relaxed.gpu.global.inc.u32 %0, [%1], 0x7fffffff;" : "=r"(v) : "l"(p) : "memory");
    return v;
}
__device__ __forceinline__ unsigned long long ld_relaxed64(const void* p) {
    unsigned long long v;
    asm volatile("ld.relaxed.gpu.global.u64 %0, [%1];" : "=l"(v) : "l"(p) : "memory");
    return v;
}
__device__ __forceinline__ void st_relaxed64(void* p, unsigned long long v) {
    asm volatile("st.relaxed.gpu.global.u64 [%0], %1;" ::"l"(p), "l"(v) : "memory");
}
__device__ __forceinline__ float4 ld_relaxed16(const void* p) {
    float4 v;
    asm volatile("ld.relaxed.gpu.global.v4.f32 {%0,%1,%2,%3}, [%4];" : "=f"(v.x), "=f"(v.y), "=f"(v.z), "=f"(v.w) : "l"(p) : "memory");
    return v;
}
__device__ __forceinline__ uint32_t mapa(uint32_t a, uint32_t rank) {
    uint32_t r;
    asm("mapa.shared::cluster.u32 %0, %1, %2;" : "=r"(r) : "r"(a), "r"(rank));
    return r;
}
__device__ __forceinline__ void mbar_spin(uint32_t bar) {
    asm volatile("{\n.reg .pred p, q;\n.reg .u32 n;\nmov.u32 n, 0;\n"
                 "SPIN:\nmbarrier.test_wait.parity.shared::cta.b64 p, [%0], 0;\nadd.u32 n, n, 1;\nsetp.gt.u32 q, n, 0x4000000;\n@q trap;\n"
                 "@!p bra.uni SPIN;\n}" ::"r"(bar) : "memory");
}
__device__ __forceinline__ void mbar_spin_cluster(uint32_t bar) {
    asm volatile("{\n.reg .pred p, q;\n.reg .u32 n;\nmov.u32 n, 0;\n"
                 "SPIN:\nmbarrier.test_wait.parity.relaxed.cluster.shared::cta.b64 p, [%0], 0;\nadd.u32 n, n, 1;\nsetp.gt.u32 q, n, 0x4000000;\n@q trap;\n"
                 "@!p bra.uni SPIN;\nfence.acquire.sync_restrict::shared::cluster.cluster;\n}" ::"r"(bar) : "memory");
}
__device__ __forceinline__ uint32_t now_ns() {
    unsigned long long t;
    asm volatile("mov.u64 %0, %globaltimer;" : "=l"(t));
    return (uint32_t)t;
}
__device__ __forceinline__ void fence_gpu() { asm volatile("fence.acq_rel.gpu;" ::: "memory"); }
__device__ __forceinline__ void red_add_u32(unsigned* p, unsigned v) {
    asm volatile("red.relaxed.gpu.global.add.u32 [%0], %1;" ::"l"(p), "r"(v) : "memory");
}
__device__ __forceinline__ void st_tagged2(void* p, float a, float b, unsigned tag) {
    const unsigned long long hi = (unsigned long long)tag << 32;
    asm volatile("st.relaxed.gpu.global.v2.b64 [%0], {%1,%2};" ::"l"(p), "l"(hi | __float_as_uint(a)), "l"(hi | __float_as_uint(b)) : "memory");
}
__device__ __forceinline__ ulonglong2 ld_tagged2(const void* p) {
    ulonglong2 v;
    asm volatile("ld.relaxed.gpu.global.v2.b64 {%0,%1}, [%2];" : "=l"(v.x), "=l"(v.y) : "l"(p) : "memory");
    return v;
}
__device__ __forceinline__ float4 atom_add_f4(void* p, float a, float b, float c, float d) {
    float4 r;
    asm volatile("atom.relaxed.gpu.global.add.v4.f32 {%0,%1,%2,%3}, [%4], {%5,%6,%7,%8};"
                 : "=f"(r.x), "=f"(r.y), "=f"(r.z), "=f"(r.w) : "l"(p), "f"(a), "f"(b), "f"(c), "f"(d) : "memory");
    return r;
}
__device__ __forceinline__ void red_release_cta_shared(uint32_t a, unsigned v) {
    asm volatile("red.release.cta.shared::cta.add.u32 [%0], %1;" ::"r"(a), "r"(v) : "memory");
}
__device__ __forceinline__ unsigned ld_acquire_cta_shared(uint32_t a) {
    unsigned v;
    asm volatile("ld.acquire.cta.shared::cta.u32 %0, [%1];" : "=r"(v) : "r"(a) : "memory");
    return v;
}
__device__ __forceinline__ void st_release_cta_shared(uint32_t a, unsigned v) {
    asm volatile("st.release.cta.shared::cta.u32 [%0], %1;" ::"r"(a), "r"(v) : "memory");
}
__device__ __forceinline__ void wait_count(const unsigned* p, unsigned target) {
    unsigned n = 0;
    while (ld_acquire(p) < target) { if (++n > SPIN_LIMIT) __trap(); }
}
__device__ __forceinline__ uint32_t pack_bf16(float lo, float hi) {
    uint32_t r;
    asm("cvt.rn.bf16x2.f32 %0, %1, %2;" : "=r"(r) : "f"(hi), "f"(lo));
    return r;
}
__device__ __forceinline__ float bf_lo(uint32_t v) { return __uint_as_float(v << 16); }
__device__ __forceinline__ float bf_hi(uint32_t v) { return __uint_as_float(v & 0xffff0000u); }
__device__ __forceinline__ float ex2(float x) { float y; asm("ex2.approx.ftz.f32 %0, %1;" : "=f"(y) : "f"(x)); return y; }
__device__ __forceinline__ float expsub(float a, float b) { return ex2((a - b) * LOG2E); }
__device__ __forceinline__ float warp_max(float v) {
#pragma unroll
    for (int m = 16; m; m >>= 1) v = fmaxf(v, __shfl_xor_sync(~0u, v, m));
    return v;
}
__device__ __forceinline__ float warp_sum(float v) {
#pragma unroll
    for (int m = 16; m; m >>= 1) v += __shfl_xor_sync(~0u, v, m);
    return v;
}
template <bool CLU>
__device__ __forceinline__ unsigned unit_block(int u) {
    const unsigned x = ((unsigned)u & (NUK - 1)) / UPP;
    const int lg = u < NUK ? min(KMAX, max(KMIN, 29 - __clz(x | 1))) : min(VMAX, max(CLU ? VMINC : 0, 29 - __clz((127 - x) | 1)));
    const unsigned r = x & ((4u << lg) - 1);
    return ((x - r + (r & ((1u << lg) - 1)) * 4 + (r >> lg)) * UPP) | ((unsigned)u & (UPP - 1));
}
__device__ __forceinline__ const char* block_src(const void* base, unsigned blk) {
    const unsigned po = blk / UPP;
    return reinterpret_cast<const char*>(base) + (size_t)(((po & 3) * NH + (po >> 2)) * UPP + blk % UPP) * TILE_BYTES;
}

template <bool CLU>
__device__ __forceinline__ void a_worker(const Params& p, int un, bool once, bool hold, int nstatic, uint32_t slot, uint32_t bar, uint32_t wb,
                                         uint32_t help, unsigned epoch, uint64_t pol) {
    constexpr int NU = 2 * NUK;
    const int lane = threadIdx.x & 31, g = lane >> 2, t = lane & 3;
    const int li = lane & 7;
    uint32_t kaddr[4], vaddr[8];
    {
        const int e = (lane >> 3) & 1, kk = lane >> 4;
#pragma unroll
        for (int s = 0; s < 4; s++) kaddr[s] = slot + (16 * li + e) * 256 + ((2 * s + kk + li) & 7) * 16;
        const int vrow = 4 * (li >> 1) + (li & 1) + 2 * kk;
#pragma unroll
        for (int c = 0; c < 8; c++) vaddr[c] = slot + vrow * 256 + e * 128 + ((c + li) & 7) * 16;
#pragma unroll
        for (int c = 0; c < 8; c++) asm volatile("" : "+r"(vaddr[c]));
    }
    const uint32_t vmask = (g >> 1) != t ? 0u : ((g & 1) ? 0xffff0000u : 0xffffu);
    int kseen = -1;
    unsigned long long H0 = 0, H1 = 0;
    auto header = [&](int v, unsigned vb) {
        if (v >= NU) return;
        const void *a0, *a1;
        if (v < NUK) {
            const unsigned po = vb / UPP;
            a0 = g_qll + (po & 3) * 2048 + (po >> 2) * 64 + lane;
            a1 = reinterpret_cast<const uint2*>(a0) + 32;
        } else {
            const int half = vb / (NUK / 2);
            if (half > kseen) {
                unsigned n = 0;
                while (ld_acquire_cta_shared(help + 12 + 4 * half) == 0) { if (++n > (SPIN_LIMIT << 4)) __trap(); }
                kseen = half;
            }
            a0 = &g_scores[vb * (KEYS / 4) + lane];
            a1 = &g_stats[(vb / UPP) * UPP + lane];
        }
        H0 = ld_relaxed64(a0);
        H1 = ld_relaxed64(a1);
    };
    epoch = __shfl_sync(~0u, epoch, 0);
    if (hold) { unsigned n = 0; while (ld_acquire_cta_shared(help + 24) < 2) { if (++n > (SPIN_LIMIT << 4)) __trap(); } }
    unsigned (*ctl)[32] = g_ctl[epoch & 1];
    const unsigned tag = epoch + 1;
    unsigned nxt = once ? NU : 0;
    int u = -1;
    unsigned bu = 0, bn = unit_block<CLU>(un);
    bool have = false;
    uint32_t phase = 0;
    unsigned kpend = 0;
    const unsigned zero = gridDim.x >> 24;
    uint32_t Q[16];
    float4 oret = make_float4(0.f, 0.f, 0.f, 0.f);
    while (true) {
        const char* nsrc = block_src(un < NUK ? p.kc : p.vc, bn);
        float4* odst = &g_oacc[(bu / UPP) * 32 + lane];
        unsigned* vdst = &g_vdone[(lane & (NREP - 1)) * NH + bu / (4 * UPP)][0];
        float d[8][4];
        CLK(c1);
        asm volatile("" : "+l"(odst));
        if (u >= NUK) {
#pragma unroll
            for (int j = 0; j < 8; j++) { d[j][0] = d[j][1] = d[j][2] = d[j][3] = 0.f; }
            mbar_wait(wb, phase);
            LAND(NUK + bu);
            uint32_t a[2][8][4];
#pragma unroll
            for (int c = 0; c < 8; c++) ldsm4t(a[0][c], vaddr[c]);
#pragma unroll
            for (int j = 0; j < 8; j++) {
                if (j < 7) {
#pragma unroll
                    for (int c = 0; c < 8; c++) ldsm4t(a[(j + 1) & 1][c], vaddr[c] + (j + 1) * 4096);
                }
#pragma unroll
                for (int c = 0; c < 8; c++) mma16816(d[c], a[j & 1][c], Q[2 * j], Q[2 * j + 1]);
            }
            float o[4];
#pragma unroll
            for (int r = 0; r < 2; r++) {
                o[2 * r] = d[0][2 * r] + d[7][2 * r + 1];
                o[2 * r + 1] = d[0][2 * r + 1] + d[1][2 * r];
#pragma unroll
                for (int k = 1; k < 4; k++) {
                    const int src = (lane & 28) | ((t - k) & 3);
                    o[2 * r] += __shfl_sync(~0u, d[2 * k][2 * r] + d[2 * k - 1][2 * r + 1], src);
                    o[2 * r + 1] += __shfl_sync(~0u, d[2 * k][2 * r + 1] + d[2 * k + 1][2 * r], src);
                }
            }
            oret = atom_add_f4(odst, o[0], o[1], o[2], o[3]);
        } else if (u >= 0) {
#pragma unroll
            for (int j = 0; j < 8; j++) { d[j][0] = d[j][1] = d[j][2] = d[j][3] = 0.f; }
            mbar_wait(wb, phase);
            LAND(bu);
            uint32_t a[2][8][4];
#pragma unroll
            for (int j = 0; j < 8; j++) ldsm4(a[0][j], kaddr[0] + (4 * (j & 3) + 2 * (j >> 2)) * 256);
#pragma unroll
            for (int s = 0; s < 8; s++) {
                if (s < 7) {
#pragma unroll
                    for (int j = 0; j < 8; j++)
                        ldsm4(a[(s + 1) & 1][j], kaddr[(s + 1) & 3] + (4 * (j & 3) + 2 * (j >> 2)) * 256 + ((s + 1) >> 2) * 128);
                }
#pragma unroll
                for (int j = 0; j < 8; j++)
                    mma16816(d[j], a[s & 1][j], Q[(s & 4) * 2 + ((2 * s - 2 * j) & 7)], Q[(s & 4) * 2 + ((2 * s + 1 - 2 * j) & 7)]);
            }
        }
        const bool pre = wb != bar;
        if (u >= 0) { phase = pre ? 0 : phase ^ 1; wb = bar; }
        CLK(c2b);
        if (un < NU && lane == 0) {
            if (!once) nxt = atom_inc(&ctl[C_QUEUE][0]);
            if (u >= 0 || !pre) {
                mbar_expect_tx(bar, TILE_BYTES);
                bulk_load(slot, nsrc, TILE_BYTES, bar, pol);
            }
        }
        const uint32_t tiss = now_ns();
        CLK(c3);
        if ((unsigned)u < (unsigned)NUK) {
            const int j0 = (t - (g >> 1)) & 3;
            float v[4];
#pragma unroll
            for (int q = 0; q < 4; q++) {
                const int jq = (q >> 1) * 4, e = (q & 1) * 2;
                const float x0 = (g & 1) ? d[jq + 0][e + 1] : d[jq + 0][e];
                const float x1 = (g & 1) ? d[jq + 1][e + 1] : d[jq + 1][e];
                const float x2 = (g & 1) ? d[jq + 2][e + 1] : d[jq + 2][e];
                const float x3 = (g & 1) ? d[jq + 3][e + 1] : d[jq + 3][e];
                const float y0 = (j0 & 1) ? x1 : x0, y1 = (j0 & 1) ? x3 : x2;
                v[q] = (j0 & 2) ? y1 : y0;
            }
            const uint32_t r0 = pack_bf16(v[0], v[1]), r1 = pack_bf16(v[2], v[3]);
            const uint32_t s0 = pack_bf16(bf_lo(r0) * SCALE, bf_hi(r0) * SCALE);
            const uint32_t s1 = pack_bf16(bf_lo(r1) * SCALE, bf_hi(r1) * SCALE);
            g_scores[bu * (KEYS / 4) + 4 * g + j0] = make_uint2(s0, s1);
            const float f0 = bf_lo(s0), f1 = bf_hi(s0), f2 = bf_lo(s1), f3 = bf_hi(s1);
            const float m = warp_max(fmaxf(fmaxf(f0, f1), fmaxf(f2, f3)));
            const float l = warp_sum((expsub(f0, m) + expsub(f1, m)) + (expsub(f2, m) + expsub(f3, m)));
            if (lane == 0) g_stats[bu] = make_float2(m, l);
            kpend++;
            if (un / (NUK / 2) != u / (NUK / 2)) {
                __syncwarp();
                if (lane == 0) {
                    red_release_cta_shared(help + 4 * (u / (NUK / 2)), kpend);
                    if (un >= NUK) red_release_cta_shared(help + 8, 1u);
                }
                kpend = 0;
            }
        }
        CLK(c4);
        int unn = NU;
        if (un < NU) {
            unsigned n = 0;
            while (true) {
                if (!have) header(un, bn);
                if (un >= NUK || __all_sync(~0u, (uint32_t)(H0 >> 32) == tag && (uint32_t)(H1 >> 32) == tag)) break;
                if (++n > SPIN_LIMIT) __trap();
                have = false;
            }
            if (un >= NUK) {
                const uint32_t s0 = (uint32_t)H0, s1 = (uint32_t)(H0 >> 32);
                const float mu = __uint_as_float((uint32_t)H1);
                const float m = warp_max(mu);
                const float l = warp_sum(__uint_as_float((uint32_t)(H1 >> 32)) * expsub(mu, m));
                const float inv = 1.0f / l;
                const uint32_t w0 = pack_bf16(expsub(bf_lo(s0), m) * inv, expsub(bf_hi(s0), m) * inv);
                const uint32_t w1 = pack_bf16(expsub(bf_lo(s1), m) * inv, expsub(bf_hi(s1), m) * inv);
#pragma unroll
                for (int j = 0; j < 8; j++) {
                    Q[2 * j] = __shfl_sync(~0u, w0, 4 * j + t) & vmask;
                    Q[2 * j + 1] = __shfl_sync(~0u, w1, 4 * j + t) & vmask;
                }
            } else {
#pragma unroll
                for (int j = 0; j < 8; j++) {
                    const int src = (((j + g) & 7) << 2) + t;
                    Q[j] = __shfl_sync(~0u, (uint32_t)H0, src);
                    Q[8 + j] = __shfl_sync(~0u, (uint32_t)H1, src);
                }
            }
            unn = nstatic + (int)__shfl_sync(~0u, nxt, 0);
            if (CLU && !once && unn >= NU && lane == 0)
                asm volatile("st.relaxed.cta.shared::cta.u32 [%0], %1;" ::"r"(help + 28), "r"((tiss + (FJ - (unn - NU)) * 10) | 1u) : "memory");
        }
        if (u >= NUK && lane < (CLU ? 1 : NREP))
            red_add_u32(vdst,
                        1u + ((__float_as_uint(oret.x) | __float_as_uint(oret.y) | __float_as_uint(oret.z) | __float_as_uint(oret.w)) & zero));
        if (un >= NU) break;
        bu = bn;
        have = !(un < NUK && unn >= NUK && !(un >= NUK / 2 && unn < NUK + NUK / 2));
        bn = unit_block<CLU>(unn);
        if (have) header(unn, bn);
        u = un;
        un = unn;
    }
}

__device__ __forceinline__ void k_helper(uint32_t help, unsigned epoch) {
    if ((threadIdx.x & 31) != 0) return;
    unsigned (*ctl)[32] = g_ctl[epoch & 1];
    unsigned sent0 = 0, sent1 = 0, n = 0;
    int seen = 0;
    bool fin = false;
    while (!fin || seen < 2) {
        if (!fin) {
            fin = ld_acquire_cta_shared(help + 8) == NW + XW;
            const unsigned c0 = ld_acquire_cta_shared(help), c1 = ld_acquire_cta_shared(help + 4);
            if (c0 != sent0 || c1 != sent1) {
                fence_gpu();
                if (c0 != sent0) red_add_u32(&ctl[C_KDONE][0], c0 - sent0);
                if (c1 != sent1) red_add_u32(&ctl[C_KDONE + 1][0], c1 - sent1);
                sent0 = c0; sent1 = c1;
            }
        }
        if (seen < 2 && ld_acquire(&ctl[C_KDONE + seen][0]) >= NUK / 2) {
            st_release_cta_shared(help + 12 + 4 * seen, 1u);
            seen++;
        } else {
            __nanosleep(300);
        }
        if (++n > SPIN_LIMIT) __trap();
    }
}

__device__ __forceinline__ void v_poller(uint32_t sbase, int f, int w) {
    const int lane = threadIdx.x & 31;
    const unsigned (*cp)[32] = &g_vdone[((f * NPOLL + w) % NREP) * NH];
    unsigned n = 0;
    while (ld_acquire_cta_shared(sbase + M_HELP + 12) == 0) { __nanosleep(1000); if (++n > SPIN_LIMIT) __trap(); }
    int h = 0;
    bool fast = false;
    while (h < NH) {
        const unsigned r = __ballot_sync(~0u, ld_acquire(&cp[min(h + (lane & 3), NH - 1)][0]) >= 4 * UPP) & 15u;
        if (r & 1) {
            h = min(NH, h + __ffs(~r) - 1);
            __syncwarp();
            if (lane == 0) asm volatile("red.release.cta.shared::cta.max.u32 [%0], %1;" ::"r"(sbase + M_HELP + 20), "r"(h) : "memory");
        }
        if (h < NH - 4) {
            __nanosleep(h ? 300 : 1000);
        } else if (!fast) {
            fast = true;
            const long long t0 = clock64();
            while (clock64() - t0 < w * PGAP) {}
        }
        if (++n > SPIN_LIMIT) __trap();
    }
}
__device__ __forceinline__ void finisher(const Params& p, uint32_t sbase, int f) {
    const int lane = threadIdx.x & 31;
    {
        const char* wg = reinterpret_cast<const char*>(p.wo);
        const uint32_t dst = sbase + 4 * SLOT + (16 * (lane & 7) + (lane >> 3)) * 16;
#pragma unroll 1
        for (int h = -FPF - 4; h < NH; h++) {
            if (lane == 0 && (unsigned)(h + FPF) < (unsigned)NH) l2_prefetch(wg + (size_t)(h + FPF) * 147456 + f * 2048, 2048);
            if (h >= 0) {
#pragma unroll
                for (int r = 0; r < 4; r++)
                    asm volatile("cp.async.cg.shared.global [%0], [%1], 16;" ::"r"(dst + h * 2048 + ((r & 1) * 4 + (r >> 1) * 8) * 16),
                                 "l"(wg + (size_t)(h * 128 + r * 32 + lane) * (DM * 2) + f * 16) : "memory");
            }
            __nanosleep(FSLEEP);
        }
        asm volatile("cp.async.wait_all;" ::: "memory");
        __syncwarp();
    }
    TS(11);
    const float4* vec = g_oacc + ((lane >> 2) & 3) * 32 + (lane >> 4) * 16 + (lane & 3);
    float acc[2][2][4];
#pragma unroll
    for (int i = 0; i < 16; i++) acc[i >> 3][(i >> 2) & 1][i & 3] = 0.f;
    uint32_t* outp = reinterpret_cast<uint32_t*>(p.out + (lane >> 2) * (2 * DM) + f * 8 + (lane & 3) * 2);
    uint32_t wa = sbase + 4 * SLOT + lane * 16;
    auto project = [&](const float4 (&x)[4], const uint32_t (&w)[4][4]) {
#pragma unroll
        for (int s = 0; s < 4; s++) {
            const uint32_t a[4] = {pack_bf16(x[s].x, x[s].y), 0u, pack_bf16(x[s].z, x[s].w), 0u};
            mma16816(acc[0][s & 1], a, w[s >> 1][(s & 1) * 2], w[s >> 1][(s & 1) * 2 + 1]);
            mma16816(acc[1][s & 1], a, w[2 + (s >> 1)][(s & 1) * 2], w[2 + (s >> 1)][(s & 1) * 2 + 1]);
        }
    };
    int h = 0;
    unsigned n = 0;
    while (h < NH) {
        uint32_t w[4][4];
#pragma unroll
        for (int q = 0; q < 4; q++) ldsm4t(w[q], wa + q * 512);
        int ready;
        while ((ready = ld_acquire_cta_shared(sbase + M_HELP + 20)) <= h) {
            if (h < NH - 3) __nanosleep(100);
            if (++n > (SPIN_LIMIT << 4)) __trap();
        }
        float4 x[4], y[4];
#pragma unroll
        for (int s = 0; s < 4; s++) x[s] = ld_relaxed16(vec + s * 4);
        const bool two = ready > h + 1;
        if (two) {
#pragma unroll
            for (int s = 0; s < 4; s++) y[s] = ld_relaxed16(vec + 128 + s * 4);
        }
        project(x, w);
        if (two) {
#pragma unroll
            for (int q = 0; q < 4; q++) ldsm4t(w[q], wa + 2048 + q * 512);
            project(y, w);
        }
        const int nr = two ? 2 : 1;
        h += nr;
        vec += nr * 128;
        wa += nr * 2048;
        const float o0 = acc[0][0][0] + acc[0][1][0] + __shfl_down_sync(~0u, acc[1][0][0] + acc[1][1][0], 16);
        const float o1 = acc[0][0][1] + acc[0][1][1] + __shfl_down_sync(~0u, acc[1][0][1] + acc[1][1][1], 16);
        asm volatile("{\n.reg .pred p;\nsetp.ne.u32 p, %2, 0;\n@p st.global.u32 [%0], %1;\n}" ::"l"(outp), "r"(pack_bf16(o0, o1)),
                     "r"((uint32_t)(lane < 16 && h == NH)) : "memory");
    }
}

__device__ __forceinline__ void out_fetch(uint32_t sbase, int step, int h) {
    const int lane = threadIdx.x & 31, g = lane >> 2;
    float4 x[4];
#pragma unroll
    for (int b = 0; b < 4; b++) x[b] = ld_relaxed16(&g_oacc[(h * 4 + ((b + g) & 3)) * 32 + lane]);
#pragma unroll
    for (int b = 0; b < 4; b++) {
        const uint32_t a = sbase + F_X + step * FXP + g * 128 + ((b + g) & 3) * 16 + (lane & 3) * 4;
        asm volatile("st.shared.u32 [%0], %1;\nst.shared.u32 [%0 + 64], %2;" ::"r"(a), "r"(pack_bf16(x[b].x, x[b].y)), "r"(pack_bf16(x[b].z, x[b].w)) : "memory");
    }
    asm volatile("fence.proxy.async.shared::cta;" ::: "memory");
}
__device__ __forceinline__ void out_early(uint32_t sbase, int rank, unsigned tag) {
    const int lane = threadIdx.x & 31;
    if (lane < 10) {
        mbar_init(sbase + F_BAR + 16 + lane * 8, lane < 7 ? 1 : lane == 7 ? 2 : 4);
        if (lane < 8) mbar_expect_tx(sbase + F_BAR + 16 + lane * 8, 16384);
    }
    asm volatile("fence.mbarrier_init.release.cluster;" ::: "memory");
    unsigned n = 0;
#pragma unroll 1
    for (int i = 0; i < 3; i++) {
        while (ld_acquire(&g_vdone[8 * i + rank][0]) < 4 * UPP) { __nanosleep(500); if (++n > SPIN_LIMIT) __trap(); }
        out_fetch(sbase, 4 + i, 8 * i + rank);
#pragma unroll 1
        for (int j = 0; j < 16 && i == 0;) {
            const ulonglong2 v = ld_tagged2(&g_ctx[((j >> 2) * 8 + rank) * 128 + (j & 3) * 32 + lane]);
            if (__all_sync(~0u, (unsigned)(v.x >> 32) == tag && (unsigned)(v.y >> 32) == tag)) {
                asm volatile("st.shared.v2.u32 [%0], {%1,%2};" ::"r"(sbase + F_X + (j >> 2) * FXP + ((j & 3) * 32 + lane) * 8), "r"((uint32_t)v.x), "r"((uint32_t)v.y) : "memory");
                j++;
            } else {
                __nanosleep(500);
                if (++n > SPIN_LIMIT) __trap();
            }
        }
    }
    __syncwarp();
    if (lane == 0) st_release_cta_shared(sbase + M_HELP + 32, 1u);
}
__device__ __forceinline__ void out_late(uint32_t sbase, int rank) {
    unsigned n = 0;
    while (ld_acquire_cta_shared(sbase + M_HELP + 32) == 0) { if (++n > (SPIN_LIMIT << 4)) __trap(); }
    while (ld_acquire(&g_vdone[24 + rank][0]) < 4 * UPP) { if (++n > SPIN_LIMIT) __trap(); }
    TS(12);
    out_fetch(sbase, 7, 24 + rank);
    __syncwarp();
    if ((threadIdx.x & 31) == 0) asm volatile("mbarrier.arrive.shared::cta.b64 _, [%0];" ::"r"(sbase + F_BAR + 72) : "memory");
    TS(13);
}
__device__ __forceinline__ void out_project(uint32_t sbase, int rank, int w) {
    const int lane = threadIdx.x & 31, g = lane >> 2, t = lane & 3;
    unsigned n = 0;
    while (ld_acquire_cta_shared(sbase + M_HELP + 32) == 0) { __nanosleep(500); if (++n > SPIN_LIMIT) __trap(); }
    asm volatile("barrier.cluster.wait.acquire.aligned;" ::: "memory");
    const uint32_t rdst = mapa(sbase + F_RECV + 1024 + rank * 128 + (g & 3) * 32 + t * 16, 2 * w + (g >> 2));
    const uint32_t rbar = mapa(sbase + F_BAR + 8, 2 * w + (g >> 2));
    while (ld_acquire_cta_shared(sbase + M_HELP + 28) == 0) { __nanosleep(200); if (++n > SPIN_LIMIT) __trap(); }
    const uint32_t da = (1u << 16) | (((sbase + F_W) & 0x3ffff) >> 4), db = (4u << 16) | (((sbase + F_X) & 0x3ffff) >> 4);
    float d[4] = {0.f, 0.f, 0.f, 0.f};
#pragma unroll
    for (int i = 0; i < 8; i++) {
        mbar_spin(sbase + F_BAR + 16 + i * 8);
        wgmma_tile(d, da + (i % 6) * 1024, db + i * (FXP / 16), i & 3);
        if (i < 2 || (i & 3) == 3) asm volatile("wgmma.wait_group.sync.aligned 0;" : "+f"(d[0]), "+f"(d[1]), "+f"(d[2]), "+f"(d[3])::"memory");
        if (i < 2) {
            asm volatile("{\n.reg .pred p;\nsetp.eq.u32 p, %1, 0;\n@p mbarrier.arrive.shared::cta.b64 _, [%0];\n}"
                         ::"r"(sbase + F_BAR + 80 + i * 8), "r"(lane) : "memory");
        } else if ((i & 3) == 3) {
            if (t < 2)
                asm volatile("st.async.weak.shared::cluster.mbarrier::complete_tx::bytes.v4.f32 [%0], {%1,%2,%3,%4}, [%5];"
                             ::"r"(rdst - (i < 4 ? 1024 : 0)), "f"(d[0]), "f"(d[1]), "f"(d[2]), "f"(d[3]), "r"(rbar - (i < 4 ? 8 : 0)) : "memory");
            __syncwarp();
        }
    }
}
__device__ __forceinline__ void out_issue_sum(const Params& p, uint32_t sbase, int c, int rank, uint64_t pol) {
    const int lane = threadIdx.x & 31;
    if (lane == 0) {
        unsigned n = 0;
        while (ld_acquire_cta_shared(sbase + M_HELP + 32) == 0) { __nanosleep(500); if (++n > SPIN_LIMIT) __trap(); }
        asm volatile("prefetch.tensormap [%0];" ::"l"(&p.tm_wf) : "memory");
        asm volatile("prefetch.tensormap [%0];" ::"l"(&p.tm_wl) : "memory");
        uint32_t t0;
        while ((t0 = ld_acquire_cta_shared(sbase + M_HELP + 28)) == 0) { __nanosleep(100); if (++n > SPIN_LIMIT) __trap(); }
#pragma unroll 1
        for (int i = 0; i < 8; i++) {
            const int h = (i & 3) * 8 + rank;
            if (i >= 6) mbar_wait(sbase + F_BAR + 32 + i * 8, 0);
            for (int k = 0; k < 4096 && (int)(now_ns() - t0) < 0; k++) {}
            if (i == 0) TS(16);
            tma3d(sbase + F_W + (i < 6 ? i : i - 6) * 16384, i < 4 ? &p.tm_wf : &p.tm_wl, i < 4 ? 0 : c * 64, i < 4 ? h * 128 : h * 16,
                  i < 4 ? c : 0, sbase + F_BAR + 16 + i * 8, pol);
            t0 += FP;
        }
        TS(17);
    }
    __syncwarp();
    __nv_bfloat16* dst = p.out + (((lane >> 1) & 2) + (lane & 1)) * (2 * DM) + DM + c * 64 + (rank >> 1) * 16 + (lane & 2) * 4 +
                         (rank & 1) * 4 + (lane >> 3);
    uint32_t src = sbase + F_RECV + lane * 4;
#pragma unroll 1
    for (int r = 0; r < 2; r++) {
        asm volatile("" : "+l"(dst), "+r"(src));
        mbar_spin_cluster(sbase + F_BAR + r * 8);
        float x[8];
#pragma unroll
        for (int i = 0; i < 8; i++) asm volatile("ld.shared.f32 %0, [%1];" : "=f"(x[i]) : "r"(src + i * 128) : "memory");
        const float v = (((x[0] + x[1]) + (x[2] + x[3])) + (x[4] + x[5])) + (x[6] + x[7]);
        asm volatile("{\n.reg .b16 h;\ncvt.rn.bf16.f32 h, %1;\nst.global.b16 [%0], h;\n}" ::"l"(dst), "f"(v) : "memory");
        TS(14 + r);
        dst -= DM;
        src += 1024;
    }
}

constexpr int BS_WUK = 5, BS_Q = 9, BS_CKV = 11, BS_PART = 27, BS_WUV = 29, BS_END = 33;

__device__ __noinline__ void b_issue(const Params& p, int n, int bi, uint32_t sbase, uint64_t pol) {
    if (n >= BS_END || (n >= BS_Q && n < BS_CKV) || (n >= BS_PART && n < BS_WUV)) return;
    const uint32_t bar = sbase + M_BAR + (NSLOT + n % BRING) * 8;
    const CUtensorMap* tm;
    int row, panel = 2 * bi;
    if (n < BS_WUK) { tm = &p.tm_wq; row = n * 128; }
    else if (n < BS_Q) { tm = &p.tm_wuk; row = (n - BS_WUK) * 128; }
    else if (n < BS_PART) {
        tm = &p.tm_ckv; panel = 0;
        row = (bi >> 3) * SK + ((n - BS_CKV) * 8 + (bi & 7)) * 32;
    }
    else { tm = &p.tm_wuv; row = (n - BS_WUV) * 128; }
    mbar_expect_tx(bar, n == 0 ? 32768 + 4 * 1152 : 32768);
    tma3d(sbase + (n % BRING) * SLOT, tm, 0, row, panel, bar, pol);
}
__device__ __forceinline__ void b_issue_xchg(int n, const void* src, uint32_t sbase, uint64_t pol) {
    asm volatile("fence.proxy.async;" ::: "memory");
#pragma unroll
    for (int i = 0; i < 2; i++) {
        const uint32_t bar = sbase + M_BAR + (NSLOT + (n + i) % BRING) * 8;
        mbar_expect_tx(bar, 32768);
        bulk_load(sbase + ((n + i) % BRING) * SLOT, reinterpret_cast<const char*>(src) + i * 32768, 32768, bar, pol);
    }
}
__device__ __forceinline__ void b_wait(int n, uint32_t sbase) {
    mbar_wait(sbase + M_BAR + (NSLOT + n % BRING) * 8, (n / BRING) & 1);
}

__device__ __noinline__ void b_gemm(const Params& p, uint32_t sbase, int n0, int n1, int ktot, uint32_t xh, uint32_t xl, int pitch,
                                    int bi, uint64_t pol) {
    const int tid = threadIdx.x, warp = tid >> 5, lane = tid & 31, g = lane >> 2, t = lane & 3;
    const uint32_t woff = (warp >> 2) * 16384 + (lane & 15) * 128 + ((((warp & 3) * 2 + (lane >> 4)) ^ (lane & 7)) * 16);
    const uint32_t xoff = (g & 3) * pitch + t * 4;
    float acc[2][4];
#pragma unroll
    for (int i = 0; i < 8; i++) acc[i >> 2][i & 3] = 0.f;
#pragma unroll 1
    for (int n = n0; n < n1; n++) {
        b_wait(n, sbase);
        const uint32_t slot = sbase + (n % BRING) * SLOT + woff;
        const int k0 = (n - n0) * 128;
        const int ns = min(8, (ktot - k0) >> 4);
#pragma unroll 2
        for (int s = 0; s < ns; s++) {
            uint32_t a[4], w[4];
            const uint32_t xo = xoff + (k0 + 16 * s) * 2;
            a[0] = lds32(xh + xo); a[2] = lds32(xh + xo + 16);
            a[1] = xl ? lds32(xl + xo) : 0u; a[3] = xl ? lds32(xl + xo + 16) : 0u;
            ldsm4t(w, slot + s * 2048);
            mma16816(acc[0], a, w[0], w[1]);
            mma16816(acc[1], a, w[2], w[3]);
        }
        __syncthreads();
        if (tid == 0) b_issue(p, n + BD, bi, sbase, pol);
    }
    if (g < 4) {
#pragma unroll
        for (int j = 0; j < 2; j++)
            asm volatile("st.shared.u32 [%0], %1;" ::"r"(sbase + M_QB + g * QP + (warp * 16 + j * 8 + t * 2) * 2),
                         "r"(pack_bf16(acc[j][0] + acc[j][2], acc[j][1] + acc[j][3])) : "memory");
    }
    __syncthreads();
}

__device__ __forceinline__ void b_exchange(unsigned* c, int n, const void* src, uint32_t sbase, uint64_t pol) {
    TS(n == BS_Q ? 24 : 28);
    __syncthreads();
    if (threadIdx.x == 0) {
        TS(n == BS_Q ? 25 : 29);
        fence_gpu();
        TS(n == BS_Q ? 26 : 30);
        red_add_u32(c, 1u);
        wait_count(c, NBCTA);
        TS(n == BS_Q ? 27 : 31);
        b_issue_xchg(n, src, sbase, pol);
    }
}

template <bool CLU>
__device__ __noinline__ void b_chain(const Params& p, char* smem, uint32_t sbase, int bi, unsigned epoch, uint64_t pol) {
    const int tid = threadIdx.x, warp = tid >> 5, lane = tid & 31, g = lane >> 2, t = lane & 3;
    unsigned (*ctl)[32] = g_ctl[epoch & 1];
    float* red = reinterpret_cast<float*>(smem + 5 * SLOT);
    b_gemm(p, sbase, 0, BS_WUK, DM, sbase + M_XB, 0, XP, bi, pol);
    TS(6);
    {
        uint32_t Q[16];
#pragma unroll
        for (int c = 0; c < 16; c++) Q[c] = lds32(sbase + M_QB + (g & 3) * QP + c * 16 + t * 4);
        float* qa = reinterpret_cast<float*>(smem + M_QA);
#pragma unroll 1
        for (int n = BS_WUK; n < BS_Q; n++) {
            b_wait(n, sbase);
            const uint32_t base = sbase + (n % BRING) * SLOT + (warp * 16 + (lane & 15)) * 128;
            float d[2][4];
#pragma unroll
            for (int i = 0; i < 8; i++) d[i >> 2][i & 3] = 0.f;
#pragma unroll
            for (int s = 0; s < 8; s++) {
                uint32_t a[4];
                ldsm4(a, base + (s >> 2) * 16384 + (((2 * (s & 3) + (lane >> 4)) ^ (lane & 7)) * 16));
                mma16816(d[s & 1], a, Q[2 * s], Q[2 * s + 1]);
            }
            const int c = (n - BS_WUK) * 128 + warp * 16 + g + 8 * (t >> 1);
            qa[(2 * (t & 1)) * 512 + c] = (t & 2) ? d[0][2] + d[1][2] : d[0][0] + d[1][0];
            qa[(2 * (t & 1) + 1) * 512 + c] = (t & 2) ? d[0][3] + d[1][3] : d[0][1] + d[1][1];
            __syncthreads();
            if (tid == 0) b_issue(p, n + BD, bi, sbase, pol);
        }
#pragma unroll 1
        for (int r = 0; r < 2; r++) {
            const int id = tid + r * 256;
            const int b = id >> 7, c0 = ((id >> 2) & 31) * 16 + (id & 3) * 2;
            const float2 u0 = *reinterpret_cast<const float2*>(qa + b * 512 + c0);
            const float2 u1 = *reinterpret_cast<const float2*>(qa + b * 512 + c0 + 8);
            const uint32_t h0 = pack_bf16(u0.x, u0.y), h1 = pack_bf16(u1.x, u1.y);
            const uint32_t l0 = pack_bf16(u0.x - bf_lo(h0), u0.y - bf_hi(h0)), l1 = pack_bf16(u1.x - bf_lo(h1), u1.y - bf_hi(h1));
            g_qabs[((id >> 2) * 4 + (bi >> 3)) * 32 + (bi & 7) * 4 + (id & 3)] = make_uint4(h0, l0, h1, l1);
        }
    }
    b_exchange(&ctl[C_BBAR][0], BS_Q, &g_qabs[(bi >> 3) * 4096], sbase, pol);
    {
        uint32_t qf[4][4][4];
        b_wait(BS_Q + (warp >> 2), sbase);
        TS(7);
        {
            const uint4* qs = reinterpret_cast<const uint4*>(smem + ((BS_Q + (warp >> 2)) % BRING) * SLOT) + (warp & 3) * 512 + lane;
#pragma unroll
            for (int s = 0; s < 4; s++)
#pragma unroll
                for (int i = 0; i < 4; i++) {
                    const uint4 v = qs[(s * 4 + i) * 32];
                    qf[i][s][0] = v.x; qf[i][s][1] = v.y; qf[i][s][2] = v.z; qf[i][s][3] = v.w;
                }
        }
        __syncthreads();
        if (tid == 0) { b_issue(p, BS_Q + BD, bi, sbase, pol); b_issue(p, BS_Q + 1 + BD, bi, sbase, pol); }
        float acc[2][8][4];
#pragma unroll
        for (int i = 0; i < 2; i++)
#pragma unroll
            for (int j = 0; j < 8; j++) { acc[i][j][0] = acc[i][j][1] = acc[i][j][2] = acc[i][j][3] = 0.f; }
        float mrun = -INFINITY, lrun = 0.f;
        const int head = tid >> 3, kq = tid & 7;
        float* alpha = reinterpret_cast<float*>(smem + M_ALPHA);
        for (int n = BS_CKV; n < BS_PART; n++) {
            b_wait(n, sbase);
            const uint32_t slot = sbase + (n % BRING) * SLOT;
            float sc[4][4][4];
#pragma unroll
            for (int i = 0; i < 4; i++)
#pragma unroll
                for (int j = 0; j < 4; j++) { sc[i][j][0] = sc[i][j][1] = sc[i][j][2] = sc[i][j][3] = 0.f; }
#pragma unroll
            for (int j = 0; j < 4; j++)
#pragma unroll
                for (int sp = 0; sp < 2; sp++) {
                    uint32_t bf[4];
                    ldsm4(bf, slot + warp * 4096 + (8 * j + (lane & 7)) * 128 + (((4 * sp + (lane >> 3)) ^ (lane & 7)) * 16));
#pragma unroll
                    for (int i = 0; i < 4; i++) {
                        mma16816(sc[i][j], qf[i][2 * sp], bf[0], bf[1]);
                        mma16816(sc[i][j], qf[i][2 * sp + 1], bf[2], bf[3]);
                    }
                }
#pragma unroll
            for (int i = 0; i < 4; i++)
#pragma unroll
                for (int j = 0; j < 4; j++)
                    *reinterpret_cast<float2*>(red + warp * 1024 + (8 * i + g) * 32 + ((8 * j) ^ (8 * (g & 3))) + 2 * t) =
                        make_float2(sc[i][j][0] + sc[i][j][2], sc[i][j][1] + sc[i][j][3]);
            __syncthreads();
            if (tid == 0 && n > BS_CKV) b_issue(p, n - 1 + BD, bi, sbase, pol);
            {
                float4 s = make_float4(0.f, 0.f, 0.f, 0.f);
#pragma unroll
                for (int w = 0; w < 8; w++) {
                    const float4 v = *reinterpret_cast<const float4*>(red + w * 1024 + head * 32 + ((4 * kq) ^ (8 * (head & 3))));
                    s.x += v.x; s.y += v.y; s.z += v.z; s.w += v.w;
                }
                const uint32_t r0 = pack_bf16(s.x, s.y), r1 = pack_bf16(s.z, s.w);
                const uint32_t s0 = pack_bf16(bf_lo(r0) * SCALE, bf_hi(r0) * SCALE);
                const uint32_t s1 = pack_bf16(bf_lo(r1) * SCALE, bf_hi(r1) * SCALE);
                const float f0 = bf_lo(s0), f1 = bf_hi(s0), f2 = bf_lo(s1), f3 = bf_hi(s1);
                float mx = fmaxf(fmaxf(f0, f1), fmaxf(f2, f3));
                mx = fmaxf(mx, __shfl_xor_sync(~0u, mx, 1));
                mx = fmaxf(mx, __shfl_xor_sync(~0u, mx, 2));
                mx = fmaxf(mx, __shfl_xor_sync(~0u, mx, 4));
                const float mnew = fmaxf(mrun, mx);
                const float al = expsub(mrun, mnew);
                const float p0 = expsub(f0, mnew), p1 = expsub(f1, mnew), p2 = expsub(f2, mnew), p3 = expsub(f3, mnew);
                lrun = lrun * al + ((p0 + p1) + (p2 + p3));
                mrun = mnew;
                *reinterpret_cast<uint2*>(smem + M_P + head * 80 + kq * 8) = make_uint2(pack_bf16(p0, p1), pack_bf16(p2, p3));
                if (kq == 0) alpha[head] = al;
            }
            __syncthreads();
            {
                uint32_t pf[2][2][4];
#pragma unroll
                for (int i = 0; i < 2; i++)
#pragma unroll
                    for (int ks = 0; ks < 2; ks++)
                        ldsm4(pf[i][ks], sbase + M_P + (16 * i + (lane & 15)) * 80 + (16 * ks + 8 * (lane >> 4)) * 2);
#pragma unroll
                for (int i = 0; i < 2; i++) {
                    const float a0 = alpha[16 * i + g], a1 = alpha[16 * i + 8 + g];
#pragma unroll
                    for (int j = 0; j < 8; j++) { acc[i][j][0] *= a0; acc[i][j][1] *= a0; acc[i][j][2] *= a1; acc[i][j][3] *= a1; }
                }
#pragma unroll
                for (int j = 0; j < 8; j++) {
                    uint32_t bf[4];
                    ldsm4t(bf, slot + warp * 4096 + lane * 128 + ((j ^ (lane & 7)) * 16));
#pragma unroll
                    for (int i = 0; i < 2; i++) {
                        mma16816(acc[i][j], pf[i][0], bf[0], bf[1]);
                        mma16816(acc[i][j], pf[i][1], bf[2], bf[3]);
                    }
                }
            }
        }
        __syncthreads();
        if (tid == 0) b_issue(p, BS_PART - 1 + BD, bi, sbase, pol);
        lrun += __shfl_xor_sync(~0u, lrun, 1);
        lrun += __shfl_xor_sync(~0u, lrun, 2);
        lrun += __shfl_xor_sync(~0u, lrun, 4);
        if (kq == 0) g_bml[head * NBCTA + bi] = make_float2(mrun, lrun);
#pragma unroll
        for (int i = 0; i < 2; i++)
#pragma unroll
            for (int j = 0; j < 8; j++) {
                g_bpart[((16 * i + g) * NBCTA + bi) * 256 + warp * 32 + j * 4 + t] = make_float2(acc[i][j][0], acc[i][j][1]);
                g_bpart[((16 * i + 8 + g) * NBCTA + bi) * 256 + warp * 32 + j * 4 + t] = make_float2(acc[i][j][2], acc[i][j][3]);
            }
    }
#pragma unroll 1
    for (int i = tid; i < NH * 36 && !(CLU); i += 256) g_outb[bi * NH * 36 + i] = make_uint4(0u, epoch, 0u, epoch);
    b_exchange(&ctl[C_BBAR + 1][0], BS_PART, &g_bpart[bi * NBCTA * 256], sbase, pol);
    {
        float* omega = reinterpret_cast<float*>(smem + M_OMEGA);
        if (warp == 0) {
            __syncwarp();
            const uint2 ml = ld_relaxed8(&g_bml[bi * NBCTA + lane]);
            const float ms = __uint_as_float(ml.x);
            float m = ms;
            m = fmaxf(m, __shfl_xor_sync(~0u, m, 1));
            m = fmaxf(m, __shfl_xor_sync(~0u, m, 2));
            m = fmaxf(m, __shfl_xor_sync(~0u, m, 4));
            const float w = expsub(ms, m);
            float l = w * __uint_as_float(ml.y);
            l += __shfl_xor_sync(~0u, l, 1);
            l += __shfl_xor_sync(~0u, l, 2);
            l += __shfl_xor_sync(~0u, l, 4);
            omega[lane] = w / l;
        }
        __syncthreads();
        b_wait(BS_PART, sbase);
        b_wait(BS_PART + 1, sbase);
#pragma unroll 1
        for (int b = 0; b < 4; b++) {
            const float2* ps = reinterpret_cast<const float2*>(smem + ((BS_PART + (b >> 1)) % BRING) * SLOT) + (b & 1) * 2048 + tid;
            float c0 = 0.f, c1 = 0.f;
#pragma unroll
            for (int s = 0; s < 8; s++) {
                const float w = omega[b * 8 + s];
                const float2 v = ps[s * 256];
                c0 = fmaf(w, v.x, c0);
                c1 = fmaf(w, v.y, c1);
            }
            const uint32_t hi = pack_bf16(c0, c1);
            *reinterpret_cast<uint32_t*>(smem + M_CH + b * CP + tid * 4) = hi;
            *reinterpret_cast<uint32_t*>(smem + M_CL + b * CP + tid * 4) = pack_bf16(c0 - bf_lo(hi), c1 - bf_hi(hi));
        }
        __syncthreads();
        if (tid == 0) { b_issue(p, BS_PART + BD, bi, sbase, pol); b_issue(p, BS_PART + 1 + BD, bi, sbase, pol); }
    }
    b_gemm(p, sbase, BS_WUV, BS_END, 512, sbase + M_CH, sbase + M_CL, CP, bi, pol);
    TS(12);
    if (CLU) {
        if (tid < 128) {
            const uint32_t xo = sbase + M_QB + ((tid >> 1) & 3) * QP + (tid >> 3) * 16 + (tid & 1) * 8;
            st_tagged2(&g_ctx[bi * 128 + tid], __uint_as_float(lds32(xo)), __uint_as_float(lds32(xo + 4)), epoch + 1);
        }
        return;
    }
    if (tid == 0) {
#pragma unroll 1
        for (int i = 0; i < 4; i++) {
            mbar_expect_tx(sbase + M_BAR + i * 8, 36864);
            tma3d(sbase + i * 36864, &p.tm_wo, 0, bi * 128 + i * 32, 0, sbase + M_BAR + i * 8, pol);
        }
    }
    TS(8);
    {
        float acc[9][4];
#pragma unroll
        for (int j = 0; j < 9; j++) { acc[j][0] = acc[j][1] = acc[j][2] = acc[j][3] = 0.f; }
#pragma unroll 1
        for (int i = 0; i < 4; i++) {
            const uint32_t xo = sbase + M_QB + (g & 3) * QP + i * 64 + t * 4;
            const uint32_t a0[4] = {lds32(xo), 0u, lds32(xo + 16), 0u}, a1[4] = {lds32(xo + 32), 0u, lds32(xo + 48), 0u};
            mbar_wait(sbase + M_BAR + i * 8, 0);
#pragma unroll
            for (int j = 0; j < 9; j++) {
                const int nt = warp * 9 + j;
                uint32_t w[4];
                ldsm4t(w, sbase + i * 36864 + (nt >> 3) * 4096 + lane * 128 + (((nt & 7) ^ (lane & 7)) * 16));
                mma16816(acc[j], a0, w[0], w[1]);
                mma16816(acc[j], a1, w[2], w[3]);
            }
        }
        if (g < 4) {
#pragma unroll
            for (int j = 0; j < 9; j++) {
                const int c2 = (warp * 9 + j) * 4 + t;
                st_tagged2(&g_outb[((c2 / 9) * NH + bi) * 36 + g * 9 + c2 % 9], acc[j][0], acc[j][1], epoch + 1);
            }
        }
    }
    TS(9);
    {
        const uint4* src = g_outb + (bi * NH + (tid >> 3)) * 36 + (tid & 7);
        float2* part = reinterpret_cast<float2*>(red);
        unsigned n = 0;
        while (true) {
            ulonglong2 v[5];
            bool ok = true;
#pragma unroll
            for (int i = 0; i < 5; i++)
                if (i < 4 || (tid & 7) < 4) v[i] = ld_tagged2(src + i * 8);
#pragma unroll
            for (int i = 0; i < 5; i++)
                if (i < 4 || (tid & 7) < 4) {
                    ok = ok && (unsigned)(v[i].x >> 32) == epoch + 1 && (unsigned)(v[i].y >> 32) == epoch + 1;
                    part[(tid >> 3) * 36 + (tid & 7) + i * 8] = make_float2(__uint_as_float((unsigned)v[i].x), __uint_as_float((unsigned)v[i].y));
                }
            if (ok) break;
            __nanosleep(400);
            if (++n > SPIN_LIMIT) __trap();
        }
        __syncthreads();
        if (tid < 36) {
            float s0 = 0.f, s1 = 0.f;
#pragma unroll 8
            for (int h = 0; h < NH; h++) { const float2 v = part[h * 36 + tid]; s0 += v.x; s1 += v.y; }
            *reinterpret_cast<uint32_t*>(p.out + (tid / 9) * 2 * DM + DM + bi * 18 + (tid % 9) * 2) = pack_bf16(s0, s1);
        }
    }
    TS(10);
}

template <bool CLU>
__global__ void __launch_bounds__(256, 1) fused_decode_kernel(const __grid_constant__ First f, const __grid_constant__ Params p) {
    extern __shared__ __align__(1024) char smem_raw[];
    const uint32_t sbase = (smem_u32(smem_raw) + 1023u) & ~1023u;
    char* smem = smem_raw + (sbase - smem_u32(smem_raw));
    const int tid = threadIdx.x, warp = tid >> 5, lane = tid & 31;
    asm volatile("{\n.reg .pred p;\nsetp.ne.u32 p, %1, 0;\n@p prefetch.global.L2 [%0];\n}"
                 ::"l"(f.ptr[tid >> 10] + (blockIdx.x * 8 + warp) * 8192 + lane * 128), "r"((uint32_t)(blockIdx.x < DM / 8 && lane < 16)) : "memory");
    const char* eptr = f.ptr[3 + (tid >> 10)];
    const int blk = CLU ? cluster_role(blockIdx.x) : blockIdx.x;
    const bool isB = CLU ? blk < NBCTA : (blk & 3) == 0 && (blk >> 2) < NBCTA;
    const int bi = CLU ? blk : blk >> 2;
    const int nb = CLU ? blk - NBCTA : blk - min(NBCTA, (blk + 3) >> 2);
    const int nblk = CLU ? 8 * MINCL : gridDim.x, nnb = nblk - NBCTA;
    const int nstatic = nnb * (NW + XW);
    uint64_t pol, poln;
    asm volatile("createpolicy.fractional.L2::evict_first.b64 %0, 1.0;" : "=l"(pol));
    asm volatile("createpolicy.fractional.L2::evict_normal.b64 %0, 1.0;" : "=l"(poln));
    const uint32_t wbar = sbase + M_BAR + warp * 8, wslot = sbase + warp * SLOT;
    const bool hold = ((blk >> 2) >> KMIN << KMIN) * 4 * UPP < nstatic;
    const uint32_t jbar = sbase + M_BAR + (NSLOT + BRING) * 8, fbar = sbase + M_BAR + 4 * 8;
    if (warp < 4) {
        if (lane == 0) {
            if (warp == 0) {
                mbar_init(jbar, 1);
                asm volatile("fence.mbarrier_init.release.cluster;" ::: "memory");
                mbar_expect_tx(jbar, 36864 + 4 * 1152);
                if (CLU || blk < 128) tma3d(sbase + J0W, &p.tm_j0, blk * 32, 0, 0, jbar, poln);
            } else if (warp & 1) {
                if (warp & 2) {
#pragma unroll
                    for (int i = 0; i < NSLOT + BRING; i++) mbar_init(sbase + M_BAR + i * 8, 1);
                    mbar_expect_tx(fbar, NEARLY * TILE_BYTES);
                } else if (CLU && !isB) {
#pragma unroll
                    for (int i = 0; i < 2; i++) {
                        mbar_init(sbase + F_BAR + i * 8, 1);
                        mbar_expect_tx(sbase + F_BAR + i * 8, 1024);
                    }
                }
                asm volatile("fence.mbarrier_init.release.cluster;" ::: "memory");
            } else {
#pragma unroll
                for (int i = 0; i < 4; i++) asm volatile("st.shared.v4.u32 [%0], {%1,%1,%1,%1};" ::"r"(sbase + M_HELP + i * 16), "r"(0) : "memory");
            }
        }
    } else if (blockIdx.x >= DM / 8) {
        if (tid == 128) {
            asm volatile("prefetch.tensormap [%0];" ::"l"(&p.tm_j0) : "memory");
            asm volatile("prefetch.tensormap [%0];" ::"l"(&p.tm_wq) : "memory");
        } else if (blockIdx.x == DM / 8 + 4 && tid >= 220) {
            asm volatile("prefetch.global.L2 [%0];" ::"l"(f.ptr[2 + (tid >> 10)] + (tid - 220) * 128) : "memory");
        }
    }
    __syncthreads();
    if (tid == 128) {
        if (CLU || blk < 128) bulk_load(sbase + M_XA, f.ptr[2], 4608, jbar, poln);
        if (!isB && !hold)
            bulk_load(sbase, f.ptr[1] + (size_t)((nb * NEARLY >> 7) * (NH * UPP) + (nb * NEARLY & 127)) * TILE_BYTES, NEARLY * TILE_BYTES, fbar, pol);
    }
    const int u0 = ((warp / NEARLY) * nnb + nb) * NEARLY + warp % NEARLY;
    unsigned epoch = 0;
    if (lane == 0) epoch = ld_relaxed4(eptr);
    TS(0);
    if (CLU && (unsigned)nb < NFIN) asm volatile("barrier.cluster.arrive.relaxed.aligned;" ::: "memory");
    if ((warp >> 1) == 2 && blk < 128) st_relaxed64(&g_qll[((tid - 128) >> 4) * 2048 + blk * 16 + (tid & 15)], 0ull);
    if (isB || warp >= NW + XW) epoch = __shfl_sync(~0u, epoch, 0);
    if (isB && tid == 96) {
        if (hold) { unsigned n = 0; while (ld_acquire_cta_shared(sbase + M_HELP + 24) < 2) { if (++n > (SPIN_LIMIT << 4)) __trap(); } }
#pragma unroll 1
        for (int b = 0; b < 4; b++) bulk_load(sbase + M_XB + b * XP, p.xb + b * DM, 1152, sbase + M_BAR + NSLOT * 8, pol);
#pragma unroll 1
        for (int n = 0; n < BD; n++) b_issue(p, n, bi, sbase, pol);
    }
    if (warp >= 4 && blk < 128) {
        const int g = lane >> 2, t = lane & 3, j = tid - 128;
#pragma unroll 1
        for (int sl = blk, ph = 0;; sl += 128 - nblk, ph = 1) {
        mbar_wait(jbar, ph);
        TS(13);
        float acc[4][4];
#pragma unroll
        for (int i = 0; i < 16; i++) acc[i >> 2][i & 3] = 0.f;
        const uint32_t wa = sbase + J0W + ((warp - 4) * 144 + (lane & 15)) * 64;
        const uint32_t sw = (lane >> 1) & 3, xa = sbase + M_XA + (g & 3) * 1152 + (warp - 4) * 288 + t * 4;
#pragma unroll 3
        for (int s = 0; s < 9; s++) {
            const uint32_t a[4] = {lds32(xa + s * 32), 0u, lds32(xa + s * 32 + 16), 0u};
            uint32_t w0[4], w1[4];
            ldsm4t(w0, wa + s * 1024 + (((lane >> 4) ^ sw) * 16));
            ldsm4t(w1, wa + s * 1024 + (((2 + (lane >> 4)) ^ sw) * 16));
            mma16816(acc[0], a, w0[0], w0[1]);
            mma16816(acc[1], a, w0[2], w0[3]);
            mma16816(acc[2], a, w1[0], w1[1]);
            mma16816(acc[3], a, w1[2], w1[3]);
        }
        float2* j0 = reinterpret_cast<float2*>(smem + M_J0);
        if (g < 4) {
#pragma unroll
            for (int i = 0; i < 4; i++) j0[(warp - 4) * 64 + g * 16 + i * 4 + t] = make_float2(acc[i][0], acc[i][1]);
        }
        asm volatile("bar.sync 1, 128;" ::: "memory");
        const bool again = sl == blk && blk + 128 - nblk >= nblk;
        if (again && tid == 224) {
            mbar_expect_tx(jbar, 36864);
            tma3d(sbase + J0W, &p.tm_j0, (blk + 128 - nblk) * 32, 0, 0, jbar, pol);
        }
        if (warp < 6) {
            const float2 v0 = j0[j], v1 = j0[64 + j], v2 = j0[128 + j], v3 = j0[192 + j];
            st_relaxed64(&g_qll[(j >> 4) * 2048 + sl * 16 + (j & 15)],
                         (unsigned long long)pack_bf16((v0.x + v1.x) + (v2.x + v3.x), (v0.y + v1.y) + (v2.y + v3.y)) |
                             ((unsigned long long)(epoch + 1) << 32));
            __syncwarp();
            if (lane == 0) asm volatile("red.relaxed.cta.shared::cta.add.u32 [%0], 1;" ::"r"(sbase + M_HELP + 24) : "memory");
        } else if (warp == 7) {
            if (blk < C_LINES) g_ctl[(epoch & 1) ^ 1][blk][lane] = 0;
        }
        TS(1);
        if (!again) break;
        asm volatile("bar.sync 1, 128;" ::: "memory");
        }
    }
    if (isB) {
        b_chain<CLU>(p, smem, sbase, bi, epoch, pol);
        return;
    }
    if (warp < NW + XW) {
        a_worker<CLU>(p, u0, warp >= NW + ((nb & 3) < (CLU ? X3C : X3) ? 1 : 0), hold, nstatic, wslot, wbar, warp < NEARLY && !hold ? fbar : wbar,
                      sbase + M_HELP, epoch, pol);
        if (CLU && nb < NFIN) {
            if (warp == 3) out_issue_sum(p, sbase, nb >> 3, nb & 7, pol);
            else if (warp == 0) out_late(sbase, nb & 7);
        }
        return;
    } else if (warp == 7) {
#pragma unroll 1
        for (int i = nb; i < 4 * NH; i += nnb) g_oacc[i * 32 + lane] = make_float4(0.f, 0.f, 0.f, 0.f);
        if (nb < NREP * NH) g_vdone[nb][lane] = 0;
        __syncwarp();
        k_helper(sbase + M_HELP, epoch);
        if (nb == 0 && lane == 0) g_epoch = epoch + 1;
        __syncwarp();
        if (CLU && nb < NFIN) out_early(sbase, nb & 7, epoch + 1);
    } else if (CLU) {
    } else if (warp == 6 && nb < NFIN) {
        finisher(p, sbase, nb);
        TS(4);
    } else if (warp >= 6 - NPOLL && nb < NFIN) {
        v_poller(sbase, nb, warp - (6 - NPOLL));
    }
    if (CLU && nb < NFIN) out_project(sbase, nb & 7, warp - 4);
}

}

typedef CUresult (*EncodeFn)(CUtensorMap*, CUtensorMapDataType, cuuint32_t, void*, const cuuint64_t*, const cuuint64_t*,
                             const cuuint32_t*, const cuuint32_t*, CUtensorMapInterleave, CUtensorMapSwizzle,
                             CUtensorMapL2promotion, CUtensorMapFloatOOBfill);

extern "C" void kernel_launch(void* const* d_in, const int* in_sizes, int n_in, void* d_out, int out_size) {
    (void)in_sizes; (void)n_in; (void)out_size;
    static int nsm = 0, ncl = 0;
    static EncodeFn encode = nullptr;
    static const char* epoch_ptr = nullptr;
    cudaLaunchConfig_t cfg = {};
    cudaLaunchAttribute at[1];
    at[0].id = cudaLaunchAttributeClusterDimension;
    at[0].val.clusterDim.x = 8; at[0].val.clusterDim.y = 1; at[0].val.clusterDim.z = 1;
    cfg.blockDim = dim3(256); cfg.dynamicSmemBytes = SMEM_BYTES; cfg.stream = cudaStreamPerThread; cfg.attrs = at; cfg.numAttrs = 1;
    if (nsm == 0) {
        int dev = 0;
        cudaGetDevice(&dev);
        cudaDeviceGetAttribute(&nsm, cudaDevAttrMultiProcessorCount, dev);
        cudaFuncSetAttribute(fused_decode_kernel<false>, cudaFuncAttributeMaxDynamicSharedMemorySize, SMEM_BYTES);
        cudaFuncSetAttribute(fused_decode_kernel<true>, cudaFuncAttributeMaxDynamicSharedMemorySize, SMEM_BYTES);
        cfg.gridDim = dim3(128);
        if (cudaOccupancyMaxActiveClusters(&ncl, fused_decode_kernel<true>, &cfg) != cudaSuccess) { ncl = 0; (void)cudaGetLastError(); }
        if (ncl > MINCL) ncl = MINCL;
        cudaGetSymbolAddress((void**)&epoch_ptr, g_epoch);
        void* fn = nullptr;
        cudaDriverEntryPointQueryResult qr;
        cudaGetDriverEntryPoint("cuTensorMapEncodeTiled", &fn, cudaEnableDefault, &qr);
        encode = (EncodeFn)fn;
    }
    Params p;
    auto panels = [&](CUtensorMap* tm, void* ptr, int rows, int cols, int box_rows, int box_panels) {
        const cuuint64_t gd[3] = {64, (cuuint64_t)rows, (cuuint64_t)(cols / 64)}, gs[2] = {(cuuint64_t)cols * 2, 128};
        const cuuint32_t box[3] = {64, (cuuint32_t)box_rows, (cuuint32_t)box_panels}, es[3] = {1, 1, 1};
        encode(tm, CU_TENSOR_MAP_DATA_TYPE_BFLOAT16, 3, ptr, gd, gs, box, es, CU_TENSOR_MAP_INTERLEAVE_NONE,
               CU_TENSOR_MAP_SWIZZLE_128B, CU_TENSOR_MAP_L2_PROMOTION_L2_256B, CU_TENSOR_MAP_FLOAT_OOB_FILL_NONE);
    };
    panels(&p.tm_wq, d_in[7], DM, 4096, 128, 2);
    panels(&p.tm_wuk, d_in[8], 512, 4096, 128, 2);
    panels(&p.tm_wuv, d_in[9], 512, 4096, 128, 2);
    panels(&p.tm_wo, d_in[10], 4096, DM, 32, 9);
    panels(&p.tm_wf, d_in[10], 4096, DM, 128, 1);
    panels(&p.tm_ckv, d_in[6], 4 * SK, 512, 32, 8);
    {
        const cuuint64_t gd[3] = {4096, 192, 3}, gs[2] = {8192, 192 * 8192};
        const cuuint32_t box[3] = {32, 192, 3}, es[3] = {1, 1, 1};
        encode(&p.tm_j0, CU_TENSOR_MAP_DATA_TYPE_BFLOAT16, 3, d_in[3], gd, gs, box, es, CU_TENSOR_MAP_INTERLEAVE_NONE,
               CU_TENSOR_MAP_SWIZZLE_64B, CU_TENSOR_MAP_L2_PROMOTION_L2_128B, CU_TENSOR_MAP_FLOAT_OOB_FILL_NONE);
    }
    {
        const cuuint64_t gd[3] = {DM, 512, 8}, gs[2] = {8 * DM * 2, DM * 2};
        const cuuint32_t box[3] = {64, 16, 8}, es[3] = {1, 1, 1};
        encode(&p.tm_wl, CU_TENSOR_MAP_DATA_TYPE_BFLOAT16, 3, d_in[4], gd, gs, box, es, CU_TENSOR_MAP_INTERLEAVE_NONE,
               CU_TENSOR_MAP_SWIZZLE_128B, CU_TENSOR_MAP_L2_PROMOTION_L2_256B, CU_TENSOR_MAP_FLOAT_OOB_FILL_NONE);
    }
    p.kc = (const __nv_bfloat16*)d_in[1];
    p.vc = (const __nv_bfloat16*)d_in[2];
    p.wo = (const __nv_bfloat16*)d_in[4];
    p.xb = (const __nv_bfloat16*)d_in[5];
    p.out = (__nv_bfloat16*)d_out;
    const First f = {{(const char*)d_in[3], (const char*)d_in[1], (const char*)d_in[0], epoch_ptr}};
    if (ncl >= MINCL) {
        cfg.gridDim = dim3(8 * ncl);
        cudaLaunchKernelEx(&cfg, fused_decode_kernel<true>, f, p);
    } else {
        fused_decode_kernel<false><<<nsm, 256, SMEM_BYTES, cudaStreamPerThread>>>(f, p);
    }
}
```

```cpp
#include <cuda_runtime.h>
#include <cuda.h>
#include <cuda_bf16.h>
#include <stdint.h>

namespace {

constexpr int NH = 32, SK = 4096, DM = 576;
constexpr int KEYS = 128;
constexpr int UPP = SK / KEYS;
constexpr int NUK = 4 * NH * UPP;
constexpr int TILE_BYTES = KEYS * 256;
#define NWORK 2
constexpr int NW = NWORK;
constexpr int NBCTA = 32;
constexpr int MINCL = 15;
constexpr int NFIN = 72;
constexpr int SLOT = 32768;
constexpr int NSLOT = 6;
constexpr int BRING = 5;
constexpr int J0W = 5 * SLOT;
constexpr int MISC = NSLOT * SLOT + 4096;
constexpr int XP = 1168, CP = 1040, QP = 272;
constexpr int M_XA = MISC;
constexpr int M_XB = M_XA + 4 * XP;
constexpr int M_CH = M_XB + 4 * XP;
constexpr int M_CL = M_CH + 4 * CP;
constexpr int M_QB = M_CL + 4 * CP;
constexpr int M_QA = M_CH;
constexpr int M_J0 = M_QB + 4 * QP;
constexpr int M_P = M_J0 + 2048;
constexpr int M_ALPHA = M_P + 2560;
constexpr int M_OMEGA = M_ALPHA + 128;
constexpr int M_BAR = M_OMEGA + 128;
constexpr int M_HELP = M_BAR + 128;
constexpr int F_W = 3 * SLOT;
constexpr int F_X = NSLOT * SLOT, FXP = 1088;
constexpr int F_RECV = F_X + 8 * FXP;
constexpr int F_BAR = M_P;
constexpr int SMEM_BYTES = M_HELP + 128 + 1024;
static_assert(F_RECV + 2048 <= M_J0, "output phase layout");
static_assert(SMEM_BYTES <= 232448 && M_BAR % 8 == 0 && M_QA % 16 == 0 && M_P % 16 == 0, "smem layout");
#define XW 2
#define X3 1
#define X3C 2
#define NEARLY 2
#define BD 5
#define FPF 3
#define FSLEEP 800
#define FJ 260
#define FP 376
#define NPOLL 2
#define PGAP 200
static_assert(NW + XW == 4 && 4 % NEARLY == 0 && BD <= BRING, "slots 4 and 5 hold the finisher weights");
constexpr float SCALE = 0.08838834764831845f;
constexpr float LOG2E = 1.4426950408889634f;
constexpr unsigned SPIN_LIMIT = 1u << 24;

#define NREP 2
constexpr int C_QUEUE = 0, C_KDONE = 1, C_BBAR = 3, C_LINES = 5;

struct First { const char* ptr[4]; };
struct Params {
    const __nv_bfloat16 *kc, *vc, *wo, *xb;
    __nv_bfloat16* out;
    CUtensorMap tm_j0;
    CUtensorMap tm_wq, tm_wuk, tm_ckv, tm_wuv, tm_wo;
    CUtensorMap tm_wl;
    CUtensorMap tm_wf;
};

__device__ unsigned g_epoch;
__device__ unsigned g_ctl[2][C_LINES][32];
__device__ uint2 g_qll[4 * 2048];
__device__ uint2 g_scores[128 * SK / 4];
__device__ float2 g_stats[128 * UPP];
__device__ float4 g_oacc[128 * 32];
__device__ unsigned g_vdone[NREP * NH][32];
__device__ uint4 g_qabs[4 * 8 * 4 * 4 * 32];
__device__ float2 g_bpart[NBCTA * NH * 256];
__device__ float2 g_bml[NBCTA * NH];
__device__ uint4 g_ctx[NH * 128];
__device__ uint4 g_outb[NBCTA * NH * 36];

__device__ __forceinline__ int cluster_role(int b) {
    const int i = b - NFIN, q = ((i >> 1) * 43 >> 7) * 2, r = i - 3 * q;
    int x = i - q;
    asm("{\n.reg .pred p;\nsetp.ge.s32 p, %1, 4;\nselp.s32 %0, %2, %0, p;\nsetp.lt.s32 p, %3, 0;\nselp.s32 %0, %4, %0, p;\n}"
        : "+r"(x) : "r"(r), "r"(NBCTA + NFIN - 4 + q + r), "r"(i), "r"(b + NBCTA));
    return x;
}

#define TS(i)
#define TSV(i, v)
#define LAND(i)
#define CLK(x)
#define ACC(a, x, y)

__device__ __forceinline__ uint32_t smem_u32(const void* p) { return (uint32_t)__cvta_generic_to_shared(p); }
__device__ __forceinline__ void mbar_init(uint32_t bar, uint32_t cnt) {
    asm volatile("mbarrier.init.shared::cta.b64 [%0], %1;" ::"r"(bar), "r"(cnt) : "memory");
}
__device__ __forceinline__ void mbar_expect_tx(uint32_t bar, uint32_t bytes) {
    asm volatile("mbarrier.arrive.expect_tx.shared::cta.b64 _, [%0], %1;" ::"r"(bar), "r"(bytes) : "memory");
}
__device__ __forceinline__ bool mbar_try(uint32_t bar, uint32_t parity) {
    uint32_t ok;
    asm volatile("{\n.reg .pred p;\nmbarrier.try_wait.parity.shared::cta.b64 p, [%1], %2;\nselp.u32 %0, 1, 0, p;\n}\n"
                 : "=r"(ok) : "r"(bar), "r"(parity) : "memory");
    return ok;
}
__device__ __forceinline__ void mbar_wait(uint32_t bar, uint32_t parity) {
    unsigned n = 0;
    while (!mbar_try(bar, parity)) { if (++n > SPIN_LIMIT) __trap(); }
}
__device__ __forceinline__ void bulk_load(uint32_t dst, const void* src, uint32_t bytes, uint32_t bar, uint64_t pol) {
    asm volatile("cp.async.bulk.shared::cluster.global.mbarrier::complete_tx::bytes.L2::cache_hint [%0], [%1], %2, [%3], %4;"
                 ::"r"(dst), "l"(src), "r"(bytes), "r"(bar), "l"(pol) : "memory");
}
__device__ __forceinline__ void tma3d(uint32_t dst, const CUtensorMap* tm, int c0, int c1, int c2, uint32_t bar, uint64_t pol) {
    asm volatile("cp.async.bulk.tensor.3d.shared::cluster.global.mbarrier::complete_tx::bytes.L2::cache_hint [%0], [%1, {%3,%4,%5}], [%2], %6;"
                 ::"r"(dst), "l"(tm), "r"(bar), "r"(c0), "r"(c1), "r"(c2), "l"(pol) : "memory");
}
__device__ __forceinline__ void l2_prefetch(const void* src, uint32_t bytes) {
    asm volatile("cp.async.bulk.prefetch.L2.global [%0], %1;" ::"l"(src), "r"(bytes) : "memory");
}
__device__ __forceinline__ void ldsm4(uint32_t (&r)[4], uint32_t addr) {
    asm volatile("ldmatrix.sync.aligned.m8n8.x4.shared.b16 {%0,%1,%2,%3}, [%4];"
                 : "=r"(r[0]), "=r"(r[1]), "=r"(r[2]), "=r"(r[3]) : "r"(addr));
}
__device__ __forceinline__ void ldsm4t(uint32_t (&r)[4], uint32_t addr) {
    asm volatile("ldmatrix.sync.aligned.m8n8.x4.trans.shared.b16 {%0,%1,%2,%3}, [%4];"
                 : "=r"(r[0]), "=r"(r[1]), "=r"(r[2]), "=r"(r[3]) : "r"(addr));
}
__device__ __forceinline__ void mma16816(float (&d)[4], const uint32_t (&a)[4], uint32_t b0, uint32_t b1) {
    asm("mma.sync.aligned.m16n8k16.row.col.f32.bf16.bf16.f32 {%0,%1,%2,%3}, {%4,%5,%6,%7}, {%8,%9}, {%0,%1,%2,%3};"
        : "+f"(d[0]), "+f"(d[1]), "+f"(d[2]), "+f"(d[3])
        : "r"(a[0]), "r"(a[1]), "r"(a[2]), "r"(a[3]), "r"(b0), "r"(b1));
}
__device__ __forceinline__ void wgmma_tile(float (&d)[4], uint32_t da, uint32_t db, int accumulate) {
    asm volatile("{\n.reg .pred p;\n.reg .b32 x, y;\n.reg .b64 a, b;\nsetp.ne.u32 p, %6, 0;\nwgmma.fence.sync.aligned;\n"
                 "add.u32 x, %4, 0;\nadd.u32 y, %5, 0;\nmov.b64 a, {x, 0x40000040};\nmov.b64 b, {y, 1};\n"
                 "wgmma.mma_async.sync.aligned.m64n8k16.f32.bf16.bf16 {%0,%1,%2,%3}, a, b, p, 1, 1, 1, 0;\n"
                 "add.u32 x, %4, 128;\nadd.u32 y, %5, 8;\nmov.b64 a, {x, 0x40000040};\nmov.b64 b, {y, 1};\n"
                 "wgmma.mma_async.sync.aligned.m64n8k16.f32.bf16.bf16 {%0,%1,%2,%3}, a, b, 1, 1, 1, 1, 0;\n"
                 "add.u32 x, %4, 256;\nadd.u32 y, %5, 16;\nmov.b64 a, {x, 0x40000040};\nmov.b64 b, {y, 1};\n"
                 "wgmma.mma_async.sync.aligned.m64n8k16.f32.bf16.bf16 {%0,%1,%2,%3}, a, b, 1, 1, 1, 1, 0;\n"
                 "add.u32 x, %4, 384;\nadd.u32 y, %5, 24;\nmov.b64 a, {x, 0x40000040};\nmov.b64 b, {y, 1};\n"
                 "wgmma.mma_async.sync.aligned.m64n8k16.f32.bf16.bf16 {%0,%1,%2,%3}, a, b, 1, 1, 1, 1, 0;\n"
                 "add.u32 x, %4, 512;\nadd.u32 y, %5, 32;\nmov.b64 a, {x, 0x40000040};\nmov.b64 b, {y, 1};\n"
                 "wgmma.mma_async.sync.aligned.m64n8k16.f32.bf16.bf16 {%0,%1,%2,%3}, a, b, 1, 1, 1, 1, 0;\n"
                 "add.u32 x, %4, 640;\nadd.u32 y, %5, 40;\nmov.b64 a, {x, 0x40000040};\nmov.b64 b, {y, 1};\n"
                 "wgmma.mma_async.sync.aligned.m64n8k16.f32.bf16.bf16 {%0,%1,%2,%3}, a, b, 1, 1, 1, 1, 0;\n"
                 "add.u32 x, %4, 768;\nadd.u32 y, %5, 48;\nmov.b64 a, {x, 0x40000040};\nmov.b64 b, {y, 1};\n"
                 "wgmma.mma_async.sync.aligned.m64n8k16.f32.bf16.bf16 {%0,%1,%2,%3}, a, b, 1, 1, 1, 1, 0;\n"
                 "add.u32 x, %4, 896;\nadd.u32 y, %5, 56;\nmov.b64 a, {x, 0x40000040};\nmov.b64 b, {y, 1};\n"
                 "wgmma.mma_async.sync.aligned.m64n8k16.f32.bf16.bf16 {%0,%1,%2,%3}, a, b, 1, 1, 1, 1, 0;\n"
                 "wgmma.commit_group.sync.aligned;\n}"
                 : "+f"(d[0]), "+f"(d[1]), "+f"(d[2]), "+f"(d[3]) : "r"(da), "r"(db), "r"(accumulate) : "memory");
}
__device__ __forceinline__ uint32_t lds32(uint32_t a) {
    uint32_t v;
    asm volatile("ld.shared.u32 %0, [%1];" : "=r"(v) : "r"(a));
    return v;
}
__device__ __forceinline__ unsigned ld_acquire(const unsigned* p) {
    unsigned v;
    asm volatile("ld.acquire.gpu.global.u32 %0, [%1];" : "=r"(v) : "l"(p) : "memory");
    return v;
}
__device__ __forceinline__ uint2 ld_relaxed8(const void* p) {
    uint2 v;
    asm volatile("ld.relaxed.gpu.global.v2.u32 {%0,%1}, [%2];" : "=r"(v.x), "=r"(v.y) : "l"(p) : "memory");
    return v;
}
__device__ __forceinline__ unsigned ld_relaxed4(const void* p) {
    unsigned v;
    asm volatile("ld.relaxed.gpu.global.u32 %0, [%1];" : "=r"(v) : "l"(p) : "memory");
    return v;
}
__device__ __forceinline__ unsigned atom_inc(unsigned* p) {
    unsigned v;
    asm volatile("atom.relaxed.gpu.global.inc.u32 %0, [%1], 0x7fffffff;" : "=r"(v) : "l"(p) : "memory");
    return v;
}
__device__ __forceinline__ unsigned long long ld_relaxed64(const void* p) {
    unsigned long long v;
    asm volatile("ld.relaxed.gpu.global.u64 %0, [%1];" : "=l"(v) : "l"(p) : "memory");
    return v;
}
__device__ __forceinline__ void st_relaxed64(void* p, unsigned long long v) {
    asm volatile("st.relaxed.gpu.global.u64 [%0], %1;" ::"l"(p), "l"(v) : "memory");
}
__device__ __forceinline__ float4 ld_relaxed16(const void* p) {
    float4 v;
    asm volatile("ld.relaxed.gpu.global.v4.f32 {%0,%1,%2,%3}, [%4];" : "=f"(v.x), "=f"(v.y), "=f"(v.z), "=f"(v.w) : "l"(p) : "memory");
    return v;
}
__device__ __forceinline__ uint32_t mapa(uint32_t a, uint32_t rank) {
    uint32_t r;
    asm("mapa.shared::cluster.u32 %0, %1, %2;" : "=r"(r) : "r"(a), "r"(rank));
    return r;
}
__device__ __forceinline__ void mbar_spin(uint32_t bar) {
    asm volatile("{\n.reg .pred p, q;\n.reg .u32 n;\nmov.u32 n, 0;\n"
                 "SPIN:\nmbarrier.test_wait.parity.shared::cta.b64 p, [%0], 0;\nadd.u32 n, n, 1;\nsetp.gt.u32 q, n, 0x4000000;\n@q trap;\n"
                 "@!p bra.uni SPIN;\n}" ::"r"(bar) : "memory");
}
__device__ __forceinline__ void mbar_spin_cluster(uint32_t bar) {
    asm volatile("{\n.reg .pred p, q;\n.reg .u32 n;\nmov.u32 n, 0;\n"
                 "SPIN:\nmbarrier.test_wait.parity.relaxed.cluster.shared::cta.b64 p, [%0], 0;\nadd.u32 n, n, 1;\nsetp.gt.u32 q, n, 0x4000000;\n@q trap;\n"
                 "@!p bra.uni SPIN;\nfence.acquire.sync_restrict::shared::cluster.cluster;\n}" ::"r"(bar) : "memory");
}
__device__ __forceinline__ uint32_t now_ns() {
    unsigned long long t;
    asm volatile("mov.u64 %0, %globaltimer;" : "=l"(t));
    return (uint32_t)t;
}
__device__ __forceinline__ void fence_gpu() { asm volatile("fence.acq_rel.gpu;" ::: "memory"); }
__device__ __forceinline__ void red_add_u32(unsigned* p, unsigned v) {
    asm volatile("red.relaxed.gpu.global.add.u32 [%0], %1;" ::"l"(p), "r"(v) : "memory");
}
__device__ __forceinline__ void st_tagged2(void* p, float a, float b, unsigned tag) {
    const unsigned long long hi = (unsigned long long)tag << 32;
    asm volatile("st.relaxed.gpu.global.v2.b64 [%0], {%1,%2};" ::"l"(p), "l"(hi | __float_as_uint(a)), "l"(hi | __float_as_uint(b)) : "memory");
}
__device__ __forceinline__ ulonglong2 ld_tagged2(const void* p) {
    ulonglong2 v;
    asm volatile("ld.relaxed.gpu.global.v2.b64 {%0,%1}, [%2];" : "=l"(v.x), "=l"(v.y) : "l"(p) : "memory");
    return v;
}
__device__ __forceinline__ float4 atom_add_f4(void* p, float a, float b, float c, float d) {
    float4 r;
    asm volatile("atom.relaxed.gpu.global.add.v4.f32 {%0,%1,%2,%3}, [%4], {%5,%6,%7,%8};"
                 : "=f"(r.x), "=f"(r.y), "=f"(r.z), "=f"(r.w) : "l"(p), "f"(a), "f"(b), "f"(c), "f"(d) : "memory");
    return r;
}
__device__ __forceinline__ void red_release_cta_shared(uint32_t a, unsigned v) {
    asm volatile("red.release.cta.shared::cta.add.u32 [%0], %1;" ::"r"(a), "r"(v) : "memory");
}
__device__ __forceinline__ unsigned ld_acquire_cta_shared(uint32_t a) {
    unsigned v;
    asm volatile("ld.acquire.cta.shared::cta.u32 %0, [%1];" : "=r"(v) : "r"(a) : "memory");
    return v;
}
__device__ __forceinline__ void st_release_cta_shared(uint32_t a, unsigned v) {
    asm volatile("st.release.cta.shared::cta.u32 [%0], %1;" ::"r"(a), "r"(v) : "memory");
}
__device__ __forceinline__ void wait_count(const unsigned* p, unsigned target) {
    unsigned n = 0;
    while (ld_acquire(p) < target) { if (++n > SPIN_LIMIT) __trap(); }
}
__device__ __forceinline__ uint32_t pack_bf16(float lo, float hi) {
    uint32_t r;
    asm("cvt.rn.bf16x2.f32 %0, %1, %2;" : "=r"(r) : "f"(hi), "f"(lo));
    return r;
}
__device__ __forceinline__ float bf_lo(uint32_t v) { return __uint_as_float(v << 16); }
__device__ __forceinline__ float bf_hi(uint32_t v) { return __uint_as_float(v & 0xffff0000u); }
__device__ __forceinline__ float ex2(float x) { float y; asm("ex2.approx.ftz.f32 %0, %1;" : "=f"(y) : "f"(x)); return y; }
__device__ __forceinline__ float expsub(float a, float b) { return ex2((a - b) * LOG2E); }
__device__ __forceinline__ float warp_max(float v) {
#pragma unroll
    for (int m = 16; m; m >>= 1) v = fmaxf(v, __shfl_xor_sync(~0u, v, m));
    return v;
}
__device__ __forceinline__ float warp_sum(float v) {
#pragma unroll
    for (int m = 16; m; m >>= 1) v += __shfl_xor_sync(~0u, v, m);
    return v;
}
__device__ __forceinline__ unsigned unit_block(int u) {
    const unsigned v = u & (NUK - 1);
    return u < NUK ? (v & ~0x78u) | (v & 0x18u) << 2 | (v & 0x60u) >> 2 : v;
}
__device__ __forceinline__ const char* block_src(const void* base, unsigned blk) {
    const unsigned po = blk / UPP;
    return reinterpret_cast<const char*>(base) + (size_t)(((po & 3) * NH + (po >> 2)) * UPP + blk % UPP) * TILE_BYTES;
}

template <bool CLU>
__device__ __forceinline__ void a_worker(const Params& p, int un, bool once, bool hold, int nstatic, uint32_t slot, uint32_t bar, uint32_t wb,
                                         uint32_t help, unsigned epoch, uint64_t pol) {
    constexpr int NU = 2 * NUK;
    const int lane = threadIdx.x & 31, g = lane >> 2, t = lane & 3;
    const int li = lane & 7;
    uint32_t kaddr[4], vaddr[8];
    {
        const int e = (lane >> 3) & 1, kk = lane >> 4;
#pragma unroll
        for (int s = 0; s < 4; s++) kaddr[s] = slot + (16 * li + e) * 256 + ((2 * s + kk + li) & 7) * 16;
        const int vrow = 4 * (li >> 1) + (li & 1) + 2 * kk;
#pragma unroll
        for (int c = 0; c < 8; c++) vaddr[c] = slot + vrow * 256 + e * 128 + ((c + li) & 7) * 16;
#pragma unroll
        for (int c = 0; c < 8; c++) asm volatile("" : "+r"(vaddr[c]));
    }
    const uint32_t vmask = (g >> 1) != t ? 0u : ((g & 1) ? 0xffff0000u : 0xffffu);
    int kseen = -1;
    unsigned long long H0 = 0, H1 = 0;
    auto header = [&](int v, unsigned vb) {
        if (v >= NU) return;
        const void *a0, *a1;
        if (v < NUK) {
            const unsigned po = vb / UPP;
            a0 = g_qll + (po & 3) * 2048 + (po >> 2) * 64 + lane;
            a1 = reinterpret_cast<const uint2*>(a0) + 32;
        } else {
            const int half = vb / (NUK / 2);
            if (half > kseen) {
                unsigned n = 0;
                while (ld_acquire_cta_shared(help + 12 + 4 * half) == 0) { if (++n > (SPIN_LIMIT << 4)) __trap(); }
                kseen = half;
            }
            a0 = &g_scores[vb * (KEYS / 4) + lane];
            a1 = &g_stats[(vb / UPP) * UPP + lane];
        }
        H0 = ld_relaxed64(a0);
        H1 = ld_relaxed64(a1);
    };
    epoch = __shfl_sync(~0u, epoch, 0);
    if (hold) { unsigned n = 0; while (ld_acquire_cta_shared(help + 24) < 2) { if (++n > (SPIN_LIMIT << 4)) __trap(); } }
    unsigned (*ctl)[32] = g_ctl[epoch & 1];
    const unsigned tag = epoch + 1;
    unsigned nxt = once ? NU : 0;
    int u = -1;
    unsigned bu = 0, bn = unit_block(un);
    bool have = false;
    uint32_t phase = 0;
    unsigned kpend = 0;
    const unsigned zero = gridDim.x >> 24;
    uint32_t Q[16];
    float4 oret = make_float4(0.f, 0.f, 0.f, 0.f);
    while (true) {
        const char* nsrc = block_src(un < NUK ? p.kc : p.vc, bn);
        float4* odst = &g_oacc[(bu / UPP) * 32 + lane];
        unsigned* vdst = &g_vdone[(lane & (NREP - 1)) * NH + bu / (4 * UPP)][0];
        float d[8][4];
        CLK(c1);
        asm volatile("" : "+l"(odst));
        if (u >= NUK) {
#pragma unroll
            for (int j = 0; j < 8; j++) { d[j][0] = d[j][1] = d[j][2] = d[j][3] = 0.f; }
            mbar_wait(wb, phase);
            LAND(NUK + bu);
            uint32_t a[2][8][4];
#pragma unroll
            for (int c = 0; c < 8; c++) ldsm4t(a[0][c], vaddr[c]);
#pragma unroll
            for (int j = 0; j < 8; j++) {
                if (j < 7) {
#pragma unroll
                    for (int c = 0; c < 8; c++) ldsm4t(a[(j + 1) & 1][c], vaddr[c] + (j + 1) * 4096);
                }
#pragma unroll
                for (int c = 0; c < 8; c++) mma16816(d[c], a[j & 1][c], Q[2 * j], Q[2 * j + 1]);
            }
            float o[4];
#pragma unroll
            for (int r = 0; r < 2; r++) {
                o[2 * r] = d[0][2 * r] + d[7][2 * r + 1];
                o[2 * r + 1] = d[0][2 * r + 1] + d[1][2 * r];
#pragma unroll
                for (int k = 1; k < 4; k++) {
                    const int src = (lane & 28) | ((t - k) & 3);
                    o[2 * r] += __shfl_sync(~0u, d[2 * k][2 * r] + d[2 * k - 1][2 * r + 1], src);
                    o[2 * r + 1] += __shfl_sync(~0u, d[2 * k][2 * r + 1] + d[2 * k + 1][2 * r], src);
                }
            }
            oret = atom_add_f4(odst, o[0], o[1], o[2], o[3]);
        } else if (u >= 0) {
#pragma unroll
            for (int j = 0; j < 8; j++) { d[j][0] = d[j][1] = d[j][2] = d[j][3] = 0.f; }
            mbar_wait(wb, phase);
            LAND(bu);
            uint32_t a[2][8][4];
#pragma unroll
            for (int j = 0; j < 8; j++) ldsm4(a[0][j], kaddr[0] + (4 * (j & 3) + 2 * (j >> 2)) * 256);
#pragma unroll
            for (int s = 0; s < 8; s++) {
                if (s < 7) {
#pragma unroll
                    for (int j = 0; j < 8; j++)
                        ldsm4(a[(s + 1) & 1][j], kaddr[(s + 1) & 3] + (4 * (j & 3) + 2 * (j >> 2)) * 256 + ((s + 1) >> 2) * 128);
                }
#pragma unroll
                for (int j = 0; j < 8; j++)
                    mma16816(d[j], a[s & 1][j], Q[(s & 4) * 2 + ((2 * s - 2 * j) & 7)], Q[(s & 4) * 2 + ((2 * s + 1 - 2 * j) & 7)]);
            }
        }
        const bool pre = wb != bar;
        if (u >= 0) { phase = pre ? 0 : phase ^ 1; wb = bar; }
        CLK(c2b);
        if (un < NU && lane == 0) {
            if (!once) nxt = atom_inc(&ctl[C_QUEUE][0]);
            if (u >= 0 || !pre) {
                mbar_expect_tx(bar, TILE_BYTES);
                bulk_load(slot, nsrc, TILE_BYTES, bar, pol);
            }
        }
        const uint32_t tiss = now_ns();
        CLK(c3);
        if ((unsigned)u < (unsigned)NUK) {
            const int j0 = (t - (g >> 1)) & 3;
            float v[4];
#pragma unroll
            for (int q = 0; q < 4; q++) {
                const int jq = (q >> 1) * 4, e = (q & 1) * 2;
                const float x0 = (g & 1) ? d[jq + 0][e + 1] : d[jq + 0][e];
                const float x1 = (g & 1) ? d[jq + 1][e + 1] : d[jq + 1][e];
                const float x2 = (g & 1) ? d[jq + 2][e + 1] : d[jq + 2][e];
                const float x3 = (g & 1) ? d[jq + 3][e + 1] : d[jq + 3][e];
                const float y0 = (j0 & 1) ? x1 : x0, y1 = (j0 & 1) ? x3 : x2;
                v[q] = (j0 & 2) ? y1 : y0;
            }
            const uint32_t r0 = pack_bf16(v[0], v[1]), r1 = pack_bf16(v[2], v[3]);
            const uint32_t s0 = pack_bf16(bf_lo(r0) * SCALE, bf_hi(r0) * SCALE);
            const uint32_t s1 = pack_bf16(bf_lo(r1) * SCALE, bf_hi(r1) * SCALE);
            g_scores[bu * (KEYS / 4) + 4 * g + j0] = make_uint2(s0, s1);
            const float f0 = bf_lo(s0), f1 = bf_hi(s0), f2 = bf_lo(s1), f3 = bf_hi(s1);
            const float m = warp_max(fmaxf(fmaxf(f0, f1), fmaxf(f2, f3)));
            const float l = warp_sum((expsub(f0, m) + expsub(f1, m)) + (expsub(f2, m) + expsub(f3, m)));
            if (lane == 0) g_stats[bu] = make_float2(m, l);
            kpend++;
            if (un / (NUK / 2) != u / (NUK / 2)) {
                __syncwarp();
                if (lane == 0) {
                    red_release_cta_shared(help + 4 * (u / (NUK / 2)), kpend);
                    if (un >= NUK) red_release_cta_shared(help + 8, 1u);
                }
                kpend = 0;
            }
        }
        CLK(c4);
        int unn = NU;
        if (un < NU) {
            unsigned n = 0;
            while (true) {
                if (!have) header(un, bn);
                if (un >= NUK || __all_sync(~0u, (uint32_t)(H0 >> 32) == tag && (uint32_t)(H1 >> 32) == tag)) break;
                if (++n > SPIN_LIMIT) __trap();
                have = false;
            }
            if (un >= NUK) {
                const uint32_t s0 = (uint32_t)H0, s1 = (uint32_t)(H0 >> 32);
                const float mu = __uint_as_float((uint32_t)H1);
                const float m = warp_max(mu);
                const float l = warp_sum(__uint_as_float((uint32_t)(H1 >> 32)) * expsub(mu, m));
                const float inv = 1.0f / l;
                const uint32_t w0 = pack_bf16(expsub(bf_lo(s0), m) * inv, expsub(bf_hi(s0), m) * inv);
                const uint32_t w1 = pack_bf16(expsub(bf_lo(s1), m) * inv, expsub(bf_hi(s1), m) * inv);
#pragma unroll
                for (int j = 0; j < 8; j++) {
                    Q[2 * j] = __shfl_sync(~0u, w0, 4 * j + t) & vmask;
                    Q[2 * j + 1] = __shfl_sync(~0u, w1, 4 * j + t) & vmask;
                }
            } else {
#pragma unroll
                for (int j = 0; j < 8; j++) {
                    const int src = (((j + g) & 7) << 2) + t;
                    Q[j] = __shfl_sync(~0u, (uint32_t)H0, src);
                    Q[8 + j] = __shfl_sync(~0u, (uint32_t)H1, src);
                }
            }
            unn = nstatic + (int)__shfl_sync(~0u, nxt, 0);
            if (CLU && !once && unn >= NU && lane == 0)
                asm volatile("st.relaxed.cta.shared::cta.u32 [%0], %1;" ::"r"(help + 28), "r"((tiss + (FJ - (unn - NU)) * 10) | 1u) : "memory");
        }
        if (u >= NUK && lane < (CLU ? 1 : NREP))
            red_add_u32(vdst,
                        1u + ((__float_as_uint(oret.x) | __float_as_uint(oret.y) | __float_as_uint(oret.z) | __float_as_uint(oret.w)) & zero));
        if (un >= NU) break;
        bu = bn;
        have = !(un < NUK && unn >= NUK && !(un >= NUK / 2 && unn < NUK + NUK / 2));
        bn = unit_block(unn);
        if (have) header(unn, bn);
        u = un;
        un = unn;
    }
}

__device__ __forceinline__ void k_helper(uint32_t help, unsigned epoch) {
    if ((threadIdx.x & 31) != 0) return;
    unsigned (*ctl)[32] = g_ctl[epoch & 1];
    unsigned sent0 = 0, sent1 = 0, n = 0;
    int seen = 0;
    bool fin = false;
    while (!fin || seen < 2) {
        if (!fin) {
            fin = ld_acquire_cta_shared(help + 8) == NW + XW;
            const unsigned c0 = ld_acquire_cta_shared(help), c1 = ld_acquire_cta_shared(help + 4);
            if (c0 != sent0 || c1 != sent1) {
                fence_gpu();
                if (c0 != sent0) red_add_u32(&ctl[C_KDONE][0], c0 - sent0);
                if (c1 != sent1) red_add_u32(&ctl[C_KDONE + 1][0], c1 - sent1);
                sent0 = c0; sent1 = c1;
            }
        }
        if (seen < 2 && ld_acquire(&ctl[C_KDONE + seen][0]) >= NUK / 2) {
            st_release_cta_shared(help + 12 + 4 * seen, 1u);
            seen++;
        } else {
            __nanosleep(300);
        }
        if (++n > SPIN_LIMIT) __trap();
    }
}

__device__ __forceinline__ void v_poller(uint32_t sbase, int f, int w) {
    const int lane = threadIdx.x & 31;
    const unsigned (*cp)[32] = &g_vdone[((f * NPOLL + w) % NREP) * NH];
    unsigned n = 0;
    while (ld_acquire_cta_shared(sbase + M_HELP + 12) == 0) { __nanosleep(1000); if (++n > SPIN_LIMIT) __trap(); }
    int h = 0;
    bool fast = false;
    while (h < NH) {
        const unsigned r = __ballot_sync(~0u, ld_acquire(&cp[min(h + (lane & 3), NH - 1)][0]) >= 4 * UPP) & 15u;
        if (r & 1) {
            h = min(NH, h + __ffs(~r) - 1);
            __syncwarp();
            if (lane == 0) asm volatile("red.release.cta.shared::cta.max.u32 [%0], %1;" ::"r"(sbase + M_HELP + 20), "r"(h) : "memory");
        }
        if (h < NH - 4) {
            __nanosleep(h ? 300 : 1000);
        } else if (!fast) {
            fast = true;
            const long long t0 = clock64();
            while (clock64() - t0 < w * PGAP) {}
        }
        if (++n > SPIN_LIMIT) __trap();
    }
}
__device__ __forceinline__ void finisher(const Params& p, uint32_t sbase, int f) {
    const int lane = threadIdx.x & 31;
    {
        const char* wg = reinterpret_cast<const char*>(p.wo);
        const uint32_t dst = sbase + 4 * SLOT + (16 * (lane & 7) + (lane >> 3)) * 16;
#pragma unroll 1
        for (int h = -FPF - 4; h < NH; h++) {
            if (lane == 0 && (unsigned)(h + FPF) < (unsigned)NH) l2_prefetch(wg + (size_t)(h + FPF) * 147456 + f * 2048, 2048);
            if (h >= 0) {
#pragma unroll
                for (int r = 0; r < 4; r++)
                    asm volatile("cp.async.cg.shared.global [%0], [%1], 16;" ::"r"(dst + h * 2048 + ((r & 1) * 4 + (r >> 1) * 8) * 16),
                                 "l"(wg + (size_t)(h * 128 + r * 32 + lane) * (DM * 2) + f * 16) : "memory");
            }
            __nanosleep(FSLEEP);
        }
        asm volatile("cp.async.wait_all;" ::: "memory");
        __syncwarp();
    }
    TS(11);
    const float4* vec = g_oacc + ((lane >> 2) & 3) * 32 + (lane >> 4) * 16 + (lane & 3);
    float acc[2][2][4];
#pragma unroll
    for (int i = 0; i < 16; i++) acc[i >> 3][(i >> 2) & 1][i & 3] = 0.f;
    uint32_t* outp = reinterpret_cast<uint32_t*>(p.out + (lane >> 2) * (2 * DM) + f * 8 + (lane & 3) * 2);
    uint32_t wa = sbase + 4 * SLOT + lane * 16;
    auto project = [&](const float4 (&x)[4], const uint32_t (&w)[4][4]) {
#pragma unroll
        for (int s = 0; s < 4; s++) {
            const uint32_t a[4] = {pack_bf16(x[s].x, x[s].y), 0u, pack_bf16(x[s].z, x[s].w), 0u};
            mma16816(acc[0][s & 1], a, w[s >> 1][(s & 1) * 2], w[s >> 1][(s & 1) * 2 + 1]);
            mma16816(acc[1][s & 1], a, w[2 + (s >> 1)][(s & 1) * 2], w[2 + (s >> 1)][(s & 1) * 2 + 1]);
        }
    };
    int h = 0;
    unsigned n = 0;
    while (h < NH) {
        uint32_t w[4][4];
#pragma unroll
        for (int q = 0; q < 4; q++) ldsm4t(w[q], wa + q * 512);
        int ready;
        while ((ready = ld_acquire_cta_shared(sbase + M_HELP + 20)) <= h) {
            if (h < NH - 3) __nanosleep(100);
            if (++n > (SPIN_LIMIT << 4)) __trap();
        }
        float4 x[4], y[4];
#pragma unroll
        for (int s = 0; s < 4; s++) x[s] = ld_relaxed16(vec + s * 4);
        const bool two = ready > h + 1;
        if (two) {
#pragma unroll
            for (int s = 0; s < 4; s++) y[s] = ld_relaxed16(vec + 128 + s * 4);
        }
        project(x, w);
        if (two) {
#pragma unroll
            for (int q = 0; q < 4; q++) ldsm4t(w[q], wa + 2048 + q * 512);
            project(y, w);
        }
        const int nr = two ? 2 : 1;
        h += nr;
        vec += nr * 128;
        wa += nr * 2048;
        const float o0 = acc[0][0][0] + acc[0][1][0] + __shfl_down_sync(~0u, acc[1][0][0] + acc[1][1][0], 16);
        const float o1 = acc[0][0][1] + acc[0][1][1] + __shfl_down_sync(~0u, acc[1][0][1] + acc[1][1][1], 16);
        asm volatile("{\n.reg .pred p;\nsetp.ne.u32 p, %2, 0;\n@p st.global.u32 [%0], %1;\n}" ::"l"(outp), "r"(pack_bf16(o0, o1)),
                     "r"((uint32_t)(lane < 16 && h == NH)) : "memory");
    }
}

__device__ __forceinline__ void out_fetch(uint32_t sbase, int step, int h) {
    const int lane = threadIdx.x & 31, g = lane >> 2;
    float4 x[4];
#pragma unroll
    for (int b = 0; b < 4; b++) x[b] = ld_relaxed16(&g_oacc[(h * 4 + ((b + g) & 3)) * 32 + lane]);
#pragma unroll
    for (int b = 0; b < 4; b++) {
        const uint32_t a = sbase + F_X + step * FXP + g * 128 + ((b + g) & 3) * 16 + (lane & 3) * 4;
        asm volatile("st.shared.u32 [%0], %1;\nst.shared.u32 [%0 + 64], %2;" ::"r"(a), "r"(pack_bf16(x[b].x, x[b].y)), "r"(pack_bf16(x[b].z, x[b].w)) : "memory");
    }
    asm volatile("fence.proxy.async.shared::cta;" ::: "memory");
}
__device__ __forceinline__ void out_early(uint32_t sbase, int rank, unsigned tag) {
    const int lane = threadIdx.x & 31;
    if (lane < 10) {
        mbar_init(sbase + F_BAR + 16 + lane * 8, lane < 7 ? 1 : lane == 7 ? 2 : 4);
        if (lane < 8) mbar_expect_tx(sbase + F_BAR + 16 + lane * 8, 16384);
    }
    asm volatile("fence.mbarrier_init.release.cluster;" ::: "memory");
    unsigned n = 0;
#pragma unroll 1
    for (int i = 0; i < 3; i++) {
        while (ld_acquire(&g_vdone[8 * i + rank][0]) < 4 * UPP) { __nanosleep(500); if (++n > SPIN_LIMIT) __trap(); }
        out_fetch(sbase, 4 + i, 8 * i + rank);
#pragma unroll 1
        for (int j = 0; j < 16 && i == 0;) {
            const ulonglong2 v = ld_tagged2(&g_ctx[((j >> 2) * 8 + rank) * 128 + (j & 3) * 32 + lane]);
            if (__all_sync(~0u, (unsigned)(v.x >> 32) == tag && (unsigned)(v.y >> 32) == tag)) {
                asm volatile("st.shared.v2.u32 [%0], {%1,%2};" ::"r"(sbase + F_X + (j >> 2) * FXP + ((j & 3) * 32 + lane) * 8), "r"((uint32_t)v.x), "r"((uint32_t)v.y) : "memory");
                j++;
            } else {
                __nanosleep(500);
                if (++n > SPIN_LIMIT) __trap();
            }
        }
    }
    __syncwarp();
    if (lane == 0) st_release_cta_shared(sbase + M_HELP + 32, 1u);
}
__device__ __forceinline__ void out_late(uint32_t sbase, int rank) {
    unsigned n = 0;
    while (ld_acquire_cta_shared(sbase + M_HELP + 32) == 0) { if (++n > (SPIN_LIMIT << 4)) __trap(); }
    while (ld_acquire(&g_vdone[24 + rank][0]) < 4 * UPP) { if (++n > SPIN_LIMIT) __trap(); }
    TS(12);
    out_fetch(sbase, 7, 24 + rank);
    __syncwarp();
    if ((threadIdx.x & 31) == 0) asm volatile("mbarrier.arrive.shared::cta.b64 _, [%0];" ::"r"(sbase + F_BAR + 72) : "memory");
    TS(13);
}
__device__ __forceinline__ void out_project(uint32_t sbase, int rank, int w) {
    const int lane = threadIdx.x & 31, g = lane >> 2, t = lane & 3;
    unsigned n = 0;
    while (ld_acquire_cta_shared(sbase + M_HELP + 32) == 0) { __nanosleep(500); if (++n > SPIN_LIMIT) __trap(); }
    asm volatile("barrier.cluster.wait.acquire.aligned;" ::: "memory");
    const uint32_t rdst = mapa(sbase + F_RECV + 1024 + rank * 128 + (g & 3) * 32 + t * 16, 2 * w + (g >> 2));
    const uint32_t rbar = mapa(sbase + F_BAR + 8, 2 * w + (g >> 2));
    while (ld_acquire_cta_shared(sbase + M_HELP + 28) == 0) { __nanosleep(200); if (++n > SPIN_LIMIT) __trap(); }
    const uint32_t da = (1u << 16) | (((sbase + F_W) & 0x3ffff) >> 4), db = (4u << 16) | (((sbase + F_X) & 0x3ffff) >> 4);
    float d[4] = {0.f, 0.f, 0.f, 0.f};
#pragma unroll
    for (int i = 0; i < 8; i++) {
        mbar_spin(sbase + F_BAR + 16 + i * 8);
        wgmma_tile(d, da + (i % 6) * 1024, db + i * (FXP / 16), i & 3);
        if (i < 2 || (i & 3) == 3) asm volatile("wgmma.wait_group.sync.aligned 0;" : "+f"(d[0]), "+f"(d[1]), "+f"(d[2]), "+f"(d[3])::"memory");
        if (i < 2) {
            asm volatile("{\n.reg .pred p;\nsetp.eq.u32 p, %1, 0;\n@p mbarrier.arrive.shared::cta.b64 _, [%0];\n}"
                         ::"r"(sbase + F_BAR + 80 + i * 8), "r"(lane) : "memory");
        } else if ((i & 3) == 3) {
            if (t < 2)
                asm volatile("st.async.weak.shared::cluster.mbarrier::complete_tx::bytes.v4.f32 [%0], {%1,%2,%3,%4}, [%5];"
                             ::"r"(rdst - (i < 4 ? 1024 : 0)), "f"(d[0]), "f"(d[1]), "f"(d[2]), "f"(d[3]), "r"(rbar - (i < 4 ? 8 : 0)) : "memory");
            __syncwarp();
        }
    }
}
__device__ __forceinline__ void out_issue_sum(const Params& p, uint32_t sbase, int c, int rank, uint64_t pol) {
    const int lane = threadIdx.x & 31;
    if (lane == 0) {
        unsigned n = 0;
        while (ld_acquire_cta_shared(sbase + M_HELP + 32) == 0) { __nanosleep(500); if (++n > SPIN_LIMIT) __trap(); }
        asm volatile("prefetch.tensormap [%0];" ::"l"(&p.tm_wf) : "memory");
        asm volatile("prefetch.tensormap [%0];" ::"l"(&p.tm_wl) : "memory");
        uint32_t t0;
        while ((t0 = ld_acquire_cta_shared(sbase + M_HELP + 28)) == 0) { __nanosleep(100); if (++n > SPIN_LIMIT) __trap(); }
#pragma unroll 1
        for (int i = 0; i < 8; i++) {
            const int h = (i & 3) * 8 + rank;
            if (i >= 6) mbar_wait(sbase + F_BAR + 32 + i * 8, 0);
            for (int k = 0; k < 4096 && (int)(now_ns() - t0) < 0; k++) {}
            if (i == 0) TS(16);
            tma3d(sbase + F_W + (i < 6 ? i : i - 6) * 16384, i < 4 ? &p.tm_wf : &p.tm_wl, i < 4 ? 0 : c * 64, i < 4 ? h * 128 : h * 16,
                  i < 4 ? c : 0, sbase + F_BAR + 16 + i * 8, pol);
            t0 += FP;
        }
        TS(17);
    }
    __syncwarp();
    __nv_bfloat16* dst = p.out + (((lane >> 1) & 2) + (lane & 1)) * (2 * DM) + DM + c * 64 + (rank >> 1) * 16 + (lane & 2) * 4 +
                         (rank & 1) * 4 + (lane >> 3);
    uint32_t src = sbase + F_RECV + lane * 4;
#pragma unroll 1
    for (int r = 0; r < 2; r++) {
        asm volatile("" : "+l"(dst), "+r"(src));
        mbar_spin_cluster(sbase + F_BAR + r * 8);
        float x[8];
#pragma unroll
        for (int i = 0; i < 8; i++) asm volatile("ld.shared.f32 %0, [%1];" : "=f"(x[i]) : "r"(src + i * 128) : "memory");
        const float v = (((x[0] + x[1]) + (x[2] + x[3])) + (x[4] + x[5])) + (x[6] + x[7]);
        asm volatile("{\n.reg .b16 h;\ncvt.rn.bf16.f32 h, %1;\nst.global.b16 [%0], h;\n}" ::"l"(dst), "f"(v) : "memory");
        TS(14 + r);
        dst -= DM;
        src += 1024;
    }
}

constexpr int BS_WUK = 5, BS_Q = 9, BS_CKV = 11, BS_PART = 27, BS_WUV = 29, BS_END = 33;

__device__ __noinline__ void b_issue(const Params& p, int n, int bi, uint32_t sbase, uint64_t pol) {
    if (n >= BS_END || (n >= BS_Q && n < BS_CKV) || (n >= BS_PART && n < BS_WUV)) return;
    const uint32_t bar = sbase + M_BAR + (NSLOT + n % BRING) * 8;
    const CUtensorMap* tm;
    int row, panel = 2 * bi;
    if (n < BS_WUK) { tm = &p.tm_wq; row = n * 128; }
    else if (n < BS_Q) { tm = &p.tm_wuk; row = (n - BS_WUK) * 128; }
    else if (n < BS_PART) {
        tm = &p.tm_ckv; panel = 0;
        row = (bi >> 3) * SK + ((n - BS_CKV) * 8 + (bi & 7)) * 32;
    }
    else { tm = &p.tm_wuv; row = (n - BS_WUV) * 128; }
    mbar_expect_tx(bar, n == 0 ? 32768 + 4 * 1152 : 32768);
    tma3d(sbase + (n % BRING) * SLOT, tm, 0, row, panel, bar, pol);
}
__device__ __forceinline__ void b_issue_xchg(int n, const void* src, uint32_t sbase, uint64_t pol) {
    asm volatile("fence.proxy.async;" ::: "memory");
#pragma unroll
    for (int i = 0; i < 2; i++) {
        const uint32_t bar = sbase + M_BAR + (NSLOT + (n + i) % BRING) * 8;
        mbar_expect_tx(bar, 32768);
        bulk_load(sbase + ((n + i) % BRING) * SLOT, reinterpret_cast<const char*>(src) + i * 32768, 32768, bar, pol);
    }
}
__device__ __forceinline__ void b_wait(int n, uint32_t sbase) {
    mbar_wait(sbase + M_BAR + (NSLOT + n % BRING) * 8, (n / BRING) & 1);
}

__device__ __noinline__ void b_gemm(const Params& p, uint32_t sbase, int n0, int n1, int ktot, uint32_t xh, uint32_t xl, int pitch,
                                    int bi, uint64_t pol) {
    const int tid = threadIdx.x, warp = tid >> 5, lane = tid & 31, g = lane >> 2, t = lane & 3;
    const uint32_t woff = (warp >> 2) * 16384 + (lane & 15) * 128 + ((((warp & 3) * 2 + (lane >> 4)) ^ (lane & 7)) * 16);
    const uint32_t xoff = (g & 3) * pitch + t * 4;
    float acc[2][4];
#pragma unroll
    for (int i = 0; i < 8; i++) acc[i >> 2][i & 3] = 0.f;
#pragma unroll 1
    for (int n = n0; n < n1; n++) {
        b_wait(n, sbase);
        const uint32_t slot = sbase + (n % BRING) * SLOT + woff;
        const int k0 = (n - n0) * 128;
        const int ns = min(8, (ktot - k0) >> 4);
#pragma unroll 2
        for (int s = 0; s < ns; s++) {
            uint32_t a[4], w[4];
            const uint32_t xo = xoff + (k0 + 16 * s) * 2;
            a[0] = lds32(xh + xo); a[2] = lds32(xh + xo + 16);
            a[1] = xl ? lds32(xl + xo) : 0u; a[3] = xl ? lds32(xl + xo + 16) : 0u;
            ldsm4t(w, slot + s * 2048);
            mma16816(acc[0], a, w[0], w[1]);
            mma16816(acc[1], a, w[2], w[3]);
        }
        __syncthreads();
        if (tid == 0) b_issue(p, n + BD, bi, sbase, pol);
    }
    if (g < 4) {
#pragma unroll
        for (int j = 0; j < 2; j++)
            asm volatile("st.shared.u32 [%0], %1;" ::"r"(sbase + M_QB + g * QP + (warp * 16 + j * 8 + t * 2) * 2),
                         "r"(pack_bf16(acc[j][0] + acc[j][2], acc[j][1] + acc[j][3])) : "memory");
    }
    __syncthreads();
}

__device__ __forceinline__ void b_exchange(unsigned* c, int n, const void* src, uint32_t sbase, uint64_t pol) {
    TS(n == BS_Q ? 24 : 28);
    __syncthreads();
    if (threadIdx.x == 0) {
        TS(n == BS_Q ? 25 : 29);
        fence_gpu();
        TS(n == BS_Q ? 26 : 30);
        red_add_u32(c, 1u);
        wait_count(c, NBCTA);
        TS(n == BS_Q ? 27 : 31);
        b_issue_xchg(n, src, sbase, pol);
    }
}

template <bool CLU>
__device__ __noinline__ void b_chain(const Params& p, char* smem, uint32_t sbase, int bi, unsigned epoch, uint64_t pol) {
    const int tid = threadIdx.x, warp = tid >> 5, lane = tid & 31, g = lane >> 2, t = lane & 3;
    unsigned (*ctl)[32] = g_ctl[epoch & 1];
    float* red = reinterpret_cast<float*>(smem + 5 * SLOT);
    b_gemm(p, sbase, 0, BS_WUK, DM, sbase + M_XB, 0, XP, bi, pol);
    TS(6);
    {
        uint32_t Q[16];
#pragma unroll
        for (int c = 0; c < 16; c++) Q[c] = lds32(sbase + M_QB + (g & 3) * QP + c * 16 + t * 4);
        float* qa = reinterpret_cast<float*>(smem + M_QA);
#pragma unroll 1
        for (int n = BS_WUK; n < BS_Q; n++) {
            b_wait(n, sbase);
            const uint32_t base = sbase + (n % BRING) * SLOT + (warp * 16 + (lane & 15)) * 128;
            float d[2][4];
#pragma unroll
            for (int i = 0; i < 8; i++) d[i >> 2][i & 3] = 0.f;
#pragma unroll
            for (int s = 0; s < 8; s++) {
                uint32_t a[4];
                ldsm4(a, base + (s >> 2) * 16384 + (((2 * (s & 3) + (lane >> 4)) ^ (lane & 7)) * 16));
                mma16816(d[s & 1], a, Q[2 * s], Q[2 * s + 1]);
            }
            const int c = (n - BS_WUK) * 128 + warp * 16 + g + 8 * (t >> 1);
            qa[(2 * (t & 1)) * 512 + c] = (t & 2) ? d[0][2] + d[1][2] : d[0][0] + d[1][0];
            qa[(2 * (t & 1) + 1) * 512 + c] = (t & 2) ? d[0][3] + d[1][3] : d[0][1] + d[1][1];
            __syncthreads();
            if (tid == 0) b_issue(p, n + BD, bi, sbase, pol);
        }
#pragma unroll 1
        for (int r = 0; r < 2; r++) {
            const int id = tid + r * 256;
            const int b = id >> 7, c0 = ((id >> 2) & 31) * 16 + (id & 3) * 2;
            const float2 u0 = *reinterpret_cast<const float2*>(qa + b * 512 + c0);
            const float2 u1 = *reinterpret_cast<const float2*>(qa + b * 512 + c0 + 8);
            const uint32_t h0 = pack_bf16(u0.x, u0.y), h1 = pack_bf16(u1.x, u1.y);
            const uint32_t l0 = pack_bf16(u0.x - bf_lo(h0), u0.y - bf_hi(h0)), l1 = pack_bf16(u1.x - bf_lo(h1), u1.y - bf_hi(h1));
            g_qabs[((id >> 2) * 4 + (bi >> 3)) * 32 + (bi & 7) * 4 + (id & 3)] = make_uint4(h0, l0, h1, l1);
        }
    }
    b_exchange(&ctl[C_BBAR][0], BS_Q, &g_qabs[(bi >> 3) * 4096], sbase, pol);
    {
        uint32_t qf[4][4][4];
        b_wait(BS_Q + (warp >> 2), sbase);
        TS(7);
        {
            const uint4* qs = reinterpret_cast<const uint4*>(smem + ((BS_Q + (warp >> 2)) % BRING) * SLOT) + (warp & 3) * 512 + lane;
#pragma unroll
            for (int s = 0; s < 4; s++)
#pragma unroll
                for (int i = 0; i < 4; i++) {
                    const uint4 v = qs[(s * 4 + i) * 32];
                    qf[i][s][0] = v.x; qf[i][s][1] = v.y; qf[i][s][2] = v.z; qf[i][s][3] = v.w;
                }
        }
        __syncthreads();
        if (tid == 0) { b_issue(p, BS_Q + BD, bi, sbase, pol); b_issue(p, BS_Q + 1 + BD, bi, sbase, pol); }
        float acc[2][8][4];
#pragma unroll
        for (int i = 0; i < 2; i++)
#pragma unroll
            for (int j = 0; j < 8; j++) { acc[i][j][0] = acc[i][j][1] = acc[i][j][2] = acc[i][j][3] = 0.f; }
        float mrun = -INFINITY, lrun = 0.f;
        const int head = tid >> 3, kq = tid & 7;
        float* alpha = reinterpret_cast<float*>(smem + M_ALPHA);
        for (int n = BS_CKV; n < BS_PART; n++) {
            b_wait(n, sbase);
            const uint32_t slot = sbase + (n % BRING) * SLOT;
            float sc[4][4][4];
#pragma unroll
            for (int i = 0; i < 4; i++)
#pragma unroll
                for (int j = 0; j < 4; j++) { sc[i][j][0] = sc[i][j][1] = sc[i][j][2] = sc[i][j][3] = 0.f; }
#pragma unroll
            for (int j = 0; j < 4; j++)
#pragma unroll
                for (int sp = 0; sp < 2; sp++) {
                    uint32_t bf[4];
                    ldsm4(bf, slot + warp * 4096 + (8 * j + (lane & 7)) * 128 + (((4 * sp + (lane >> 3)) ^ (lane & 7)) * 16));
#pragma unroll
                    for (int i = 0; i < 4; i++) {
                        mma16816(sc[i][j], qf[i][2 * sp], bf[0], bf[1]);
                        mma16816(sc[i][j], qf[i][2 * sp + 1], bf[2], bf[3]);
                    }
                }
#pragma unroll
            for (int i = 0; i < 4; i++)
#pragma unroll
                for (int j = 0; j < 4; j++)
                    *reinterpret_cast<float2*>(red + warp * 1024 + (8 * i + g) * 32 + ((8 * j) ^ (8 * (g & 3))) + 2 * t) =
                        make_float2(sc[i][j][0] + sc[i][j][2], sc[i][j][1] + sc[i][j][3]);
            __syncthreads();
            if (tid == 0 && n > BS_CKV) b_issue(p, n - 1 + BD, bi, sbase, pol);
            {
                float4 s = make_float4(0.f, 0.f, 0.f, 0.f);
#pragma unroll
                for (int w = 0; w < 8; w++) {
                    const float4 v = *reinterpret_cast<const float4*>(red + w * 1024 + head * 32 + ((4 * kq) ^ (8 * (head & 3))));
                    s.x += v.x; s.y += v.y; s.z += v.z; s.w += v.w;
                }
                const uint32_t r0 = pack_bf16(s.x, s.y), r1 = pack_bf16(s.z, s.w);
                const uint32_t s0 = pack_bf16(bf_lo(r0) * SCALE, bf_hi(r0) * SCALE);
                const uint32_t s1 = pack_bf16(bf_lo(r1) * SCALE, bf_hi(r1) * SCALE);
                const float f0 = bf_lo(s0), f1 = bf_hi(s0), f2 = bf_lo(s1), f3 = bf_hi(s1);
                float mx = fmaxf(fmaxf(f0, f1), fmaxf(f2, f3));
                mx = fmaxf(mx, __shfl_xor_sync(~0u, mx, 1));
                mx = fmaxf(mx, __shfl_xor_sync(~0u, mx, 2));
                mx = fmaxf(mx, __shfl_xor_sync(~0u, mx, 4));
                const float mnew = fmaxf(mrun, mx);
                const float al = expsub(mrun, mnew);
                const float p0 = expsub(f0, mnew), p1 = expsub(f1, mnew), p2 = expsub(f2, mnew), p3 = expsub(f3, mnew);
                lrun = lrun * al + ((p0 + p1) + (p2 + p3));
                mrun = mnew;
                *reinterpret_cast<uint2*>(smem + M_P + head * 80 + kq * 8) = make_uint2(pack_bf16(p0, p1), pack_bf16(p2, p3));
                if (kq == 0) alpha[head] = al;
            }
            __syncthreads();
            {
                uint32_t pf[2][2][4];
#pragma unroll
                for (int i = 0; i < 2; i++)
#pragma unroll
                    for (int ks = 0; ks < 2; ks++)
                        ldsm4(pf[i][ks], sbase + M_P + (16 * i + (lane & 15)) * 80 + (16 * ks + 8 * (lane >> 4)) * 2);
#pragma unroll
                for (int i = 0; i < 2; i++) {
                    const float a0 = alpha[16 * i + g], a1 = alpha[16 * i + 8 + g];
#pragma unroll
                    for (int j = 0; j < 8; j++) { acc[i][j][0] *= a0; acc[i][j][1] *= a0; acc[i][j][2] *= a1; acc[i][j][3] *= a1; }
                }
#pragma unroll
                for (int j = 0; j < 8; j++) {
                    uint32_t bf[4];
                    ldsm4t(bf, slot + warp * 4096 + lane * 128 + ((j ^ (lane & 7)) * 16));
#pragma unroll
                    for (int i = 0; i < 2; i++) {
                        mma16816(acc[i][j], pf[i][0], bf[0], bf[1]);
                        mma16816(acc[i][j], pf[i][1], bf[2], bf[3]);
                    }
                }
            }
        }
        __syncthreads();
        if (tid == 0) b_issue(p, BS_PART - 1 + BD, bi, sbase, pol);
        lrun += __shfl_xor_sync(~0u, lrun, 1);
        lrun += __shfl_xor_sync(~0u, lrun, 2);
        lrun += __shfl_xor_sync(~0u, lrun, 4);
        if (kq == 0) g_bml[head * NBCTA + bi] = make_float2(mrun, lrun);
#pragma unroll
        for (int i = 0; i < 2; i++)
#pragma unroll
            for (int j = 0; j < 8; j++) {
                g_bpart[((16 * i + g) * NBCTA + bi) * 256 + warp * 32 + j * 4 + t] = make_float2(acc[i][j][0], acc[i][j][1]);
                g_bpart[((16 * i + 8 + g) * NBCTA + bi) * 256 + warp * 32 + j * 4 + t] = make_float2(acc[i][j][2], acc[i][j][3]);
            }
    }
#pragma unroll 1
    for (int i = tid; i < NH * 36 && !(CLU); i += 256) g_outb[bi * NH * 36 + i] = make_uint4(0u, epoch, 0u, epoch);
    b_exchange(&ctl[C_BBAR + 1][0], BS_PART, &g_bpart[bi * NBCTA * 256], sbase, pol);
    {
        float* omega = reinterpret_cast<float*>(smem + M_OMEGA);
        if (warp == 0) {
            __syncwarp();
            const uint2 ml = ld_relaxed8(&g_bml[bi * NBCTA + lane]);
            const float ms = __uint_as_float(ml.x);
            float m = ms;
            m = fmaxf(m, __shfl_xor_sync(~0u, m, 1));
            m = fmaxf(m, __shfl_xor_sync(~0u, m, 2));
            m = fmaxf(m, __shfl_xor_sync(~0u, m, 4));
            const float w = expsub(ms, m);
            float l = w * __uint_as_float(ml.y);
            l += __shfl_xor_sync(~0u, l, 1);
            l += __shfl_xor_sync(~0u, l, 2);
            l += __shfl_xor_sync(~0u, l, 4);
            omega[lane] = w / l;
        }
        __syncthreads();
        b_wait(BS_PART, sbase);
        b_wait(BS_PART + 1, sbase);
#pragma unroll 1
        for (int b = 0; b < 4; b++) {
            const float2* ps = reinterpret_cast<const float2*>(smem + ((BS_PART + (b >> 1)) % BRING) * SLOT) + (b & 1) * 2048 + tid;
            float c0 = 0.f, c1 = 0.f;
#pragma unroll
            for (int s = 0; s < 8; s++) {
                const float w = omega[b * 8 + s];
                const float2 v = ps[s * 256];
                c0 = fmaf(w, v.x, c0);
                c1 = fmaf(w, v.y, c1);
            }
            const uint32_t hi = pack_bf16(c0, c1);
            *reinterpret_cast<uint32_t*>(smem + M_CH + b * CP + tid * 4) = hi;
            *reinterpret_cast<uint32_t*>(smem + M_CL + b * CP + tid * 4) = pack_bf16(c0 - bf_lo(hi), c1 - bf_hi(hi));
        }
        __syncthreads();
        if (tid == 0) { b_issue(p, BS_PART + BD, bi, sbase, pol); b_issue(p, BS_PART + 1 + BD, bi, sbase, pol); }
    }
    b_gemm(p, sbase, BS_WUV, BS_END, 512, sbase + M_CH, sbase + M_CL, CP, bi, pol);
    TS(12);
    if (CLU) {
        if (tid < 128) {
            const uint32_t xo = sbase + M_QB + ((tid >> 1) & 3) * QP + (tid >> 3) * 16 + (tid & 1) * 8;
            st_tagged2(&g_ctx[bi * 128 + tid], __uint_as_float(lds32(xo)), __uint_as_float(lds32(xo + 4)), epoch + 1);
        }
        return;
    }
    if (tid == 0) {
#pragma unroll 1
        for (int i = 0; i < 4; i++) {
            mbar_expect_tx(sbase + M_BAR + i * 8, 36864);
            tma3d(sbase + i * 36864, &p.tm_wo, 0, bi * 128 + i * 32, 0, sbase + M_BAR + i * 8, pol);
        }
    }
    TS(8);
    {
        float acc[9][4];
#pragma unroll
        for (int j = 0; j < 9; j++) { acc[j][0] = acc[j][1] = acc[j][2] = acc[j][3] = 0.f; }
#pragma unroll 1
        for (int i = 0; i < 4; i++) {
            const uint32_t xo = sbase + M_QB + (g & 3) * QP + i * 64 + t * 4;
            const uint32_t a0[4] = {lds32(xo), 0u, lds32(xo + 16), 0u}, a1[4] = {lds32(xo + 32), 0u, lds32(xo + 48), 0u};
            mbar_wait(sbase + M_BAR + i * 8, 0);
#pragma unroll
            for (int j = 0; j < 9; j++) {
                const int nt = warp * 9 + j;
                uint32_t w[4];
                ldsm4t(w, sbase + i * 36864 + (nt >> 3) * 4096 + lane * 128 + (((nt & 7) ^ (lane & 7)) * 16));
                mma16816(acc[j], a0, w[0], w[1]);
                mma16816(acc[j], a1, w[2], w[3]);
            }
        }
        if (g < 4) {
#pragma unroll
            for (int j = 0; j < 9; j++) {
                const int c2 = (warp * 9 + j) * 4 + t;
                st_tagged2(&g_outb[((c2 / 9) * NH + bi) * 36 + g * 9 + c2 % 9], acc[j][0], acc[j][1], epoch + 1);
            }
        }
    }
    TS(9);
    {
        const uint4* src = g_outb + (bi * NH + (tid >> 3)) * 36 + (tid & 7);
        float2* part = reinterpret_cast<float2*>(red);
        unsigned n = 0;
        while (true) {
            ulonglong2 v[5];
            bool ok = true;
#pragma unroll
            for (int i = 0; i < 5; i++)
                if (i < 4 || (tid & 7) < 4) v[i] = ld_tagged2(src + i * 8);
#pragma unroll
            for (int i = 0; i < 5; i++)
                if (i < 4 || (tid & 7) < 4) {
                    ok = ok && (unsigned)(v[i].x >> 32) == epoch + 1 && (unsigned)(v[i].y >> 32) == epoch + 1;
                    part[(tid >> 3) * 36 + (tid & 7) + i * 8] = make_float2(__uint_as_float((unsigned)v[i].x), __uint_as_float((unsigned)v[i].y));
                }
            if (ok) break;
            __nanosleep(400);
            if (++n > SPIN_LIMIT) __trap();
        }
        __syncthreads();
        if (tid < 36) {
            float s0 = 0.f, s1 = 0.f;
#pragma unroll 8
            for (int h = 0; h < NH; h++) { const float2 v = part[h * 36 + tid]; s0 += v.x; s1 += v.y; }
            *reinterpret_cast<uint32_t*>(p.out + (tid / 9) * 2 * DM + DM + bi * 18 + (tid % 9) * 2) = pack_bf16(s0, s1);
        }
    }
    TS(10);
}

template <bool CLU>
__global__ void __launch_bounds__(256, 1) fused_decode_kernel(const __grid_constant__ First f, const __grid_constant__ Params p) {
    extern __shared__ __align__(1024) char smem_raw[];
    const uint32_t sbase = (smem_u32(smem_raw) + 1023u) & ~1023u;
    char* smem = smem_raw + (sbase - smem_u32(smem_raw));
    const int tid = threadIdx.x, warp = tid >> 5, lane = tid & 31;
    asm volatile("{\n.reg .pred p;\nsetp.ne.u32 p, %1, 0;\n@p prefetch.global.L2 [%0];\n}"
                 ::"l"(f.ptr[tid >> 10] + (blockIdx.x * 8 + warp) * 8192 + lane * 128), "r"((uint32_t)(blockIdx.x < DM / 8 && lane < 16)) : "memory");
    const char* eptr = f.ptr[3 + (tid >> 10)];
    const int blk = CLU ? cluster_role(blockIdx.x) : blockIdx.x;
    const bool isB = CLU ? blk < NBCTA : (blk & 3) == 0 && (blk >> 2) < NBCTA;
    const int bi = CLU ? blk : blk >> 2;
    const int nb = CLU ? blk - NBCTA : blk - min(NBCTA, (blk + 3) >> 2);
    const int nblk = CLU ? 8 * MINCL : gridDim.x, nnb = nblk - NBCTA;
    const int nstatic = nnb * (NW + XW);
    uint64_t pol, poln;
    asm volatile("createpolicy.fractional.L2::evict_first.b64 %0, 1.0;" : "=l"(pol));
    asm volatile("createpolicy.fractional.L2::evict_normal.b64 %0, 1.0;" : "=l"(poln));
    const uint32_t wbar = sbase + M_BAR + warp * 8, wslot = sbase + warp * SLOT;
    const bool hold = blk < 16;
    const uint32_t jbar = sbase + M_BAR + (NSLOT + BRING) * 8, fbar = sbase + M_BAR + 4 * 8;
    if (warp < 4) {
        if (lane == 0) {
            if (warp == 0) {
                mbar_init(jbar, 1);
                asm volatile("fence.mbarrier_init.release.cluster;" ::: "memory");
                mbar_expect_tx(jbar, 36864 + 4 * 1152);
                if (CLU || blk < 128) tma3d(sbase + J0W, &p.tm_j0, blk * 32, 0, 0, jbar, poln);
            } else if (warp & 1) {
                if (warp & 2) {
#pragma unroll
                    for (int i = 0; i < NSLOT + BRING; i++) mbar_init(sbase + M_BAR + i * 8, 1);
                    mbar_expect_tx(fbar, NEARLY * TILE_BYTES);
                } else if (CLU && !isB) {
#pragma unroll
                    for (int i = 0; i < 2; i++) {
                        mbar_init(sbase + F_BAR + i * 8, 1);
                        mbar_expect_tx(sbase + F_BAR + i * 8, 1024);
                    }
                }
                asm volatile("fence.mbarrier_init.release.cluster;" ::: "memory");
            } else {
#pragma unroll
                for (int i = 0; i < 4; i++) asm volatile("st.shared.v4.u32 [%0], {%1,%1,%1,%1};" ::"r"(sbase + M_HELP + i * 16), "r"(0) : "memory");
            }
        }
    } else if (blockIdx.x >= DM / 8) {
        if (tid == 128) {
            asm volatile("prefetch.tensormap [%0];" ::"l"(&p.tm_j0) : "memory");
            asm volatile("prefetch.tensormap [%0];" ::"l"(&p.tm_wq) : "memory");
        } else if (blockIdx.x == DM / 8 + 4 && tid >= 220) {
            asm volatile("prefetch.global.L2 [%0];" ::"l"(f.ptr[2 + (tid >> 10)] + (tid - 220) * 128) : "memory");
        }
    }
    __syncthreads();
    if (tid == 128) {
        if (CLU || blk < 128) bulk_load(sbase + M_XA, f.ptr[2], 4608, jbar, poln);
        if (!isB && !hold) bulk_load(sbase, block_src(f.ptr[1], unit_block(nb * NEARLY)), NEARLY * TILE_BYTES, fbar, pol);
    }
    const int u0 = ((warp / NEARLY) * nnb + nb) * NEARLY + warp % NEARLY;
    unsigned epoch = 0;
    if (lane == 0) epoch = ld_relaxed4(eptr);
    TS(0);
    if (CLU && (unsigned)nb < NFIN) asm volatile("barrier.cluster.arrive.relaxed.aligned;" ::: "memory");
    if ((warp >> 1) == 2 && blk < 128) st_relaxed64(&g_qll[((tid - 128) >> 4) * 2048 + blk * 16 + (tid & 15)], 0ull);
    if (isB || warp >= NW + XW) epoch = __shfl_sync(~0u, epoch, 0);
    if (isB && tid == 96) {
        if (hold) { unsigned n = 0; while (ld_acquire_cta_shared(sbase + M_HELP + 24) < 2) { if (++n > (SPIN_LIMIT << 4)) __trap(); } }
#pragma unroll 1
        for (int b = 0; b < 4; b++) bulk_load(sbase + M_XB + b * XP, p.xb + b * DM, 1152, sbase + M_BAR + NSLOT * 8, pol);
#pragma unroll 1
        for (int n = 0; n < BD; n++) b_issue(p, n, bi, sbase, pol);
    }
    if (warp >= 4 && blk < 128) {
        const int g = lane >> 2, t = lane & 3, j = tid - 128;
#pragma unroll 1
        for (int sl = blk, ph = 0;; sl += 128 - nblk, ph = 1) {
        mbar_wait(jbar, ph);
        TS(13);
        float acc[4][4];
#pragma unroll
        for (int i = 0; i < 16; i++) acc[i >> 2][i & 3] = 0.f;
        const uint32_t wa = sbase + J0W + ((warp - 4) * 144 + (lane & 15)) * 64;
        const uint32_t sw = (lane >> 1) & 3, xa = sbase + M_XA + (g & 3) * 1152 + (warp - 4) * 288 + t * 4;
#pragma unroll 3
        for (int s = 0; s < 9; s++) {
            const uint32_t a[4] = {lds32(xa + s * 32), 0u, lds32(xa + s * 32 + 16), 0u};
            uint32_t w0[4], w1[4];
            ldsm4t(w0, wa + s * 1024 + (((lane >> 4) ^ sw) * 16));
            ldsm4t(w1, wa + s * 1024 + (((2 + (lane >> 4)) ^ sw) * 16));
            mma16816(acc[0], a, w0[0], w0[1]);
            mma16816(acc[1], a, w0[2], w0[3]);
            mma16816(acc[2], a, w1[0], w1[1]);
            mma16816(acc[3], a, w1[2], w1[3]);
        }
        float2* j0 = reinterpret_cast<float2*>(smem + M_J0);
        if (g < 4) {
#pragma unroll
            for (int i = 0; i < 4; i++) j0[(warp - 4) * 64 + g * 16 + i * 4 + t] = make_float2(acc[i][0], acc[i][1]);
        }
        asm volatile("bar.sync 1, 128;" ::: "memory");
        const bool again = sl == blk && blk + 128 - nblk >= nblk;
        if (again && tid == 224) {
            mbar_expect_tx(jbar, 36864);
            tma3d(sbase + J0W, &p.tm_j0, (blk + 128 - nblk) * 32, 0, 0, jbar, pol);
        }
        if (warp < 6) {
            const float2 v0 = j0[j], v1 = j0[64 + j], v2 = j0[128 + j], v3 = j0[192 + j];
            st_relaxed64(&g_qll[(j >> 4) * 2048 + sl * 16 + (j & 15)],
                         (unsigned long long)pack_bf16((v0.x + v1.x) + (v2.x + v3.x), (v0.y + v1.y) + (v2.y + v3.y)) |
                             ((unsigned long long)(epoch + 1) << 32));
            __syncwarp();
            if (lane == 0) asm volatile("red.relaxed.cta.shared::cta.add.u32 [%0], 1;" ::"r"(sbase + M_HELP + 24) : "memory");
        } else if (warp == 7) {
            if (blk < C_LINES) g_ctl[(epoch & 1) ^ 1][blk][lane] = 0;
        }
        TS(1);
        if (!again) break;
        asm volatile("bar.sync 1, 128;" ::: "memory");
        }
    }
    if (isB) {
        b_chain<CLU>(p, smem, sbase, bi, epoch, pol);
        return;
    }
    if (warp < NW + XW) {
        a_worker<CLU>(p, u0, warp >= NW + ((nb & 3) < (CLU ? X3C : X3) ? 1 : 0), hold, nstatic, wslot, wbar, warp < NEARLY && !hold ? fbar : wbar,
                      sbase + M_HELP, epoch, pol);
        if (CLU && nb < NFIN) {
            if (warp == 3) out_issue_sum(p, sbase, nb >> 3, nb & 7, pol);
            else if (warp == 0) out_late(sbase, nb & 7);
        }
        return;
    } else if (warp == 7) {
#pragma unroll 1
        for (int i = nb; i < 4 * NH; i += nnb) g_oacc[i * 32 + lane] = make_float4(0.f, 0.f, 0.f, 0.f);
        if (nb < NREP * NH) g_vdone[nb][lane] = 0;
        __syncwarp();
        k_helper(sbase + M_HELP, epoch);
        if (nb == 0 && lane == 0) g_epoch = epoch + 1;
        __syncwarp();
        if (CLU && nb < NFIN) out_early(sbase, nb & 7, epoch + 1);
    } else if (CLU) {
    } else if (warp == 6 && nb < NFIN) {
        finisher(p, sbase, nb);
        TS(4);
    } else if (warp >= 6 - NPOLL && nb < NFIN) {
        v_poller(sbase, nb, warp - (6 - NPOLL));
    }
    if (CLU && nb < NFIN) out_project(sbase, nb & 7, warp - 4);
}

}

typedef CUresult (*EncodeFn)(CUtensorMap*, CUtensorMapDataType, cuuint32_t, void*, const cuuint64_t*, const cuuint64_t*,
                             const cuuint32_t*, const cuuint32_t*, CUtensorMapInterleave, CUtensorMapSwizzle,
                             CUtensorMapL2promotion, CUtensorMapFloatOOBfill);

extern "C" void kernel_launch(void* const* d_in, const int* in_sizes, int n_in, void* d_out, int out_size) {
    (void)in_sizes; (void)n_in; (void)out_size;
    static int nsm = 0, ncl = 0;
    static EncodeFn encode = nullptr;
    static const char* epoch_ptr = nullptr;
    cudaLaunchConfig_t cfg = {};
    cudaLaunchAttribute at[1];
    at[0].id = cudaLaunchAttributeClusterDimension;
    at[0].val.clusterDim.x = 8; at[0].val.clusterDim.y = 1; at[0].val.clusterDim.z = 1;
    cfg.blockDim = dim3(256); cfg.dynamicSmemBytes = SMEM_BYTES; cfg.stream = cudaStreamPerThread; cfg.attrs = at; cfg.numAttrs = 1;
    if (nsm == 0) {
        int dev = 0;
        cudaGetDevice(&dev);
        cudaDeviceGetAttribute(&nsm, cudaDevAttrMultiProcessorCount, dev);
        cudaFuncSetAttribute(fused_decode_kernel<false>, cudaFuncAttributeMaxDynamicSharedMemorySize, SMEM_BYTES);
        cudaFuncSetAttribute(fused_decode_kernel<true>, cudaFuncAttributeMaxDynamicSharedMemorySize, SMEM_BYTES);
        cfg.gridDim = dim3(128);
        if (cudaOccupancyMaxActiveClusters(&ncl, fused_decode_kernel<true>, &cfg) != cudaSuccess) { ncl = 0; (void)cudaGetLastError(); }
        if (ncl > MINCL) ncl = MINCL;
        cudaGetSymbolAddress((void**)&epoch_ptr, g_epoch);
        void* fn = nullptr;
        cudaDriverEntryPointQueryResult qr;
        cudaGetDriverEntryPoint("cuTensorMapEncodeTiled", &fn, cudaEnableDefault, &qr);
        encode = (EncodeFn)fn;
    }
    Params p;
    auto panels = [&](CUtensorMap* tm, void* ptr, int rows, int cols, int box_rows, int box_panels) {
        const cuuint64_t gd[3] = {64, (cuuint64_t)rows, (cuuint64_t)(cols / 64)}, gs[2] = {(cuuint64_t)cols * 2, 128};
        const cuuint32_t box[3] = {64, (cuuint32_t)box_rows, (cuuint32_t)box_panels}, es[3] = {1, 1, 1};
        encode(tm, CU_TENSOR_MAP_DATA_TYPE_BFLOAT16, 3, ptr, gd, gs, box, es, CU_TENSOR_MAP_INTERLEAVE_NONE,
               CU_TENSOR_MAP_SWIZZLE_128B, CU_TENSOR_MAP_L2_PROMOTION_L2_256B, CU_TENSOR_MAP_FLOAT_OOB_FILL_NONE);
    };
    panels(&p.tm_wq, d_in[7], DM, 4096, 128, 2);
    panels(&p.tm_wuk, d_in[8], 512, 4096, 128, 2);
    panels(&p.tm_wuv, d_in[9], 512, 4096, 128, 2);
    panels(&p.tm_wo, d_in[10], 4096, DM, 32, 9);
    panels(&p.tm_wf, d_in[10], 4096, DM, 128, 1);
    panels(&p.tm_ckv, d_in[6], 4 * SK, 512, 32, 8);
    {
        const cuuint64_t gd[3] = {4096, 192, 3}, gs[2] = {8192, 192 * 8192};
        const cuuint32_t box[3] = {32, 192, 3}, es[3] = {1, 1, 1};
        encode(&p.tm_j0, CU_TENSOR_MAP_DATA_TYPE_BFLOAT16, 3, d_in[3], gd, gs, box, es, CU_TENSOR_MAP_INTERLEAVE_NONE,
               CU_TENSOR_MAP_SWIZZLE_64B, CU_TENSOR_MAP_L2_PROMOTION_L2_128B, CU_TENSOR_MAP_FLOAT_OOB_FILL_NONE);
    }
    {
        const cuuint64_t gd[3] = {DM, 512, 8}, gs[2] = {8 * DM * 2, DM * 2};
        const cuuint32_t box[3] = {64, 16, 8}, es[3] = {1, 1, 1};
        encode(&p.tm_wl, CU_TENSOR_MAP_DATA_TYPE_BFLOAT16, 3, d_in[4], gd, gs, box, es, CU_TENSOR_MAP_INTERLEAVE_NONE,
               CU_TENSOR_MAP_SWIZZLE_128B, CU_TENSOR_MAP_L2_PROMOTION_L2_256B, CU_TENSOR_MAP_FLOAT_OOB_FILL_NONE);
    }
    p.kc = (const __nv_bfloat16*)d_in[1];
    p.vc = (const __nv_bfloat16*)d_in[2];
    p.wo = (const __nv_bfloat16*)d_in[4];
    p.xb = (const __nv_bfloat16*)d_in[5];
    p.out = (__nv_bfloat16*)d_out;
    const First f = {{(const char*)d_in[3], (const char*)d_in[1], (const char*)d_in[0], epoch_ptr}};
    if (ncl >= MINCL) {
        cfg.gridDim = dim3(8 * ncl);
        cudaLaunchKernelEx(&cfg, fused_decode_kernel<true>, f, p);
    } else {
        fused_decode_kernel<false><<<nsm, 256, SMEM_BYTES, cudaStreamPerThread>>>(f, p);
    }
}
```

```cpp
#include <cuda_runtime.h>
#include <cuda.h>
#include <cuda_bf16.h>
#include <stdint.h>

namespace {

constexpr int NH = 32, SK = 4096, DM = 576;
constexpr int KEYS = 128;
constexpr int UPP = SK / KEYS;
constexpr int NUK = 4 * NH * UPP;
constexpr int TILE_BYTES = KEYS * 256;
#define NWORK 2
constexpr int NW = NWORK;
constexpr int NBCTA = 32;
constexpr int MINCL = 15;
constexpr int NFIN = 72;
constexpr int SLOT = 32768;
constexpr int NSLOT = 6;
constexpr int BRING = 5;
constexpr int J0W = 5 * SLOT;
constexpr int MISC = NSLOT * SLOT + 4096;
constexpr int XP = 1168, CP = 1040, QP = 272;
constexpr int M_XA = MISC;
constexpr int M_XB = M_XA + 4 * XP;
constexpr int M_CH = M_XB + 4 * XP;
constexpr int M_CL = M_CH + 4 * CP;
constexpr int M_QB = M_CL + 4 * CP;
constexpr int M_QA = M_CH;
constexpr int M_J0 = M_QB + 4 * QP;
constexpr int M_P = M_J0 + 2048;
constexpr int M_ALPHA = M_P + 2560;
constexpr int M_OMEGA = M_ALPHA + 128;
constexpr int M_BAR = M_OMEGA + 128;
constexpr int M_HELP = M_BAR + 128;
constexpr int F_W = 3 * SLOT;
constexpr int F_X = NSLOT * SLOT, FXP = 1088;
constexpr int F_RECV = F_X + 8 * FXP;
constexpr int F_BAR = M_P;
constexpr int SMEM_BYTES = M_HELP + 128 + 1024;
static_assert(F_RECV + 2048 <= M_J0, "output phase layout");
static_assert(SMEM_BYTES <= 232448 && M_BAR % 8 == 0 && M_QA % 16 == 0 && M_P % 16 == 0, "smem layout");
#define XW 2
#define X3 1
#define X3C 2
#define NEARLY 2
#define BD 5
#define FPF 3
#define FSLEEP 800
#define FJ 260
#define FP 376
#define NPOLL 2
#define PGAP 200
static_assert(NW + XW == 4 && 4 % NEARLY == 0 && BD <= BRING, "slots 4 and 5 hold the finisher weights");
constexpr float SCALE = 0.08838834764831845f;
constexpr float LOG2E = 1.4426950408889634f;
constexpr unsigned SPIN_LIMIT = 1u << 24;

#define NREP 2
constexpr int C_QUEUE = 0, C_KDONE = 1, C_BBAR = 3, C_LINES = 5;

struct First { const char* ptr[4]; };
struct Params {
    const __nv_bfloat16 *kc, *vc, *wo, *xb;
    __nv_bfloat16* out;
    CUtensorMap tm_j0;
    CUtensorMap tm_wq, tm_wuk, tm_ckv, tm_wuv, tm_wo;
    CUtensorMap tm_wl;
    CUtensorMap tm_wf;
};

__device__ unsigned g_epoch;
__device__ unsigned g_ctl[2][C_LINES][32];
__device__ uint2 g_qll[4 * 2048];
__device__ uint2 g_scores[128 * SK / 4];
__device__ float2 g_stats[128 * UPP];
__device__ float4 g_oacc[128 * 32];
__device__ unsigned g_vdone[NREP * NH][32];
__device__ uint4 g_qabs[4 * 8 * 4 * 4 * 32];
__device__ float2 g_bpart[NBCTA * NH * 256];
__device__ float2 g_bml[NBCTA * NH];
__device__ uint4 g_ctx[NH * 128];
__device__ uint4 g_outb[NBCTA * NH * 36];

__device__ __forceinline__ int cluster_role(int b) {
    const int i = b - NFIN, q = ((i >> 1) * 43 >> 7) * 2, r = i - 3 * q;
    int x = i - q;
    asm("{\n.reg .pred p;\nsetp.ge.s32 p, %1, 4;\nselp.s32 %0, %2, %0, p;\nsetp.lt.s32 p, %3, 0;\nselp.s32 %0, %4, %0, p;\n}"
        : "+r"(x) : "r"(r), "r"(NBCTA + NFIN - 4 + q + r), "r"(i), "r"(b + NBCTA));
    return x;
}

#define TS(i)
#define TSV(i, v)
#define LAND(i)
#define CLK(x)
#define ACC(a, x, y)

__device__ __forceinline__ uint32_t smem_u32(const void* p) { return (uint32_t)__cvta_generic_to_shared(p); }
__device__ __forceinline__ void mbar_init(uint32_t bar, uint32_t cnt) {
    asm volatile("mbarrier.init.shared::cta.b64 [%0], %1;" ::"r"(bar), "r"(cnt) : "memory");
}
__device__ __forceinline__ void mbar_expect_tx(uint32_t bar, uint32_t bytes) {
    asm volatile("mbarrier.arrive.expect_tx.shared::cta.b64 _, [%0], %1;" ::"r"(bar), "r"(bytes) : "memory");
}
__device__ __forceinline__ bool mbar_try(uint32_t bar, uint32_t parity) {
    uint32_t ok;
    asm volatile("{\n.reg .pred p;\nmbarrier.try_wait.parity.shared::cta.b64 p, [%1], %2;\nselp.u32 %0, 1, 0, p;\n}\n"
                 : "=r"(ok) : "r"(bar), "r"(parity) : "memory");
    return ok;
}
__device__ __forceinline__ void mbar_wait(uint32_t bar, uint32_t parity) {
    unsigned n = 0;
    while (!mbar_try(bar, parity)) { if (++n > SPIN_LIMIT) __trap(); }
}
__device__ __forceinline__ void bulk_load(uint32_t dst, const void* src, uint32_t bytes, uint32_t bar, uint64_t pol) {
    asm volatile("cp.async.bulk.shared::cluster.global.mbarrier::complete_tx::bytes.L2::cache_hint [%0], [%1], %2, [%3], %4;"
                 ::"r"(dst), "l"(src), "r"(bytes), "r"(bar), "l"(pol) : "memory");
}
__device__ __forceinline__ void tma3d(uint32_t dst, const CUtensorMap* tm, int c0, int c1, int c2, uint32_t bar, uint64_t pol) {
    asm volatile("cp.async.bulk.tensor.3d.shared::cluster.global.mbarrier::complete_tx::bytes.L2::cache_hint [%0], [%1, {%3,%4,%5}], [%2], %6;"
                 ::"r"(dst), "l"(tm), "r"(bar), "r"(c0), "r"(c1), "r"(c2), "l"(pol) : "memory");
}
__device__ __forceinline__ void l2_prefetch(const void* src, uint32_t bytes) {
    asm volatile("cp.async.bulk.prefetch.L2.global [%0], %1;" ::"l"(src), "r"(bytes) : "memory");
}
__device__ __forceinline__ void ldsm4(uint32_t (&r)[4], uint32_t addr) {
    asm volatile("ldmatrix.sync.aligned.m8n8.x4.shared.b16 {%0,%1,%2,%3}, [%4];"
                 : "=r"(r[0]), "=r"(r[1]), "=r"(r[2]), "=r"(r[3]) : "r"(addr));
}
__device__ __forceinline__ void ldsm4t(uint32_t (&r)[4], uint32_t addr) {
    asm volatile("ldmatrix.sync.aligned.m8n8.x4.trans.shared.b16 {%0,%1,%2,%3}, [%4];"
                 : "=r"(r[0]), "=r"(r[1]), "=r"(r[2]), "=r"(r[3]) : "r"(addr));
}
__device__ __forceinline__ void mma16816(float (&d)[4], const uint32_t (&a)[4], uint32_t b0, uint32_t b1) {
    asm("mma.sync.aligned.m16n8k16.row.col.f32.bf16.bf16.f32 {%0,%1,%2,%3}, {%4,%5,%6,%7}, {%8,%9}, {%0,%1,%2,%3};"
        : "+f"(d[0]), "+f"(d[1]), "+f"(d[2]), "+f"(d[3])
        : "r"(a[0]), "r"(a[1]), "r"(a[2]), "r"(a[3]), "r"(b0), "r"(b1));
}
__device__ __forceinline__ void wgmma_tile(float (&d)[4], uint32_t da, uint32_t db, int accumulate) {
    asm volatile("{\n.reg .pred p;\n.reg .b32 x, y;\n.reg .b64 a, b;\nsetp.ne.u32 p, %6, 0;\nwgmma.fence.sync.aligned;\n"
                 "add.u32 x, %4, 0;\nadd.u32 y, %5, 0;\nmov.b64 a, {x, 0x40000040};\nmov.b64 b, {y, 1};\n"
                 "wgmma.mma_async.sync.aligned.m64n8k16.f32.bf16.bf16 {%0,%1,%2,%3}, a, b, p, 1, 1, 1, 0;\n"
                 "add.u32 x, %4, 128;\nadd.u32 y, %5, 8;\nmov.b64 a, {x, 0x40000040};\nmov.b64 b, {y, 1};\n"
                 "wgmma.mma_async.sync.aligned.m64n8k16.f32.bf16.bf16 {%0,%1,%2,%3}, a, b, 1, 1, 1, 1, 0;\n"
                 "add.u32 x, %4, 256;\nadd.u32 y, %5, 16;\nmov.b64 a, {x, 0x40000040};\nmov.b64 b, {y, 1};\n"
                 "wgmma.mma_async.sync.aligned.m64n8k16.f32.bf16.bf16 {%0,%1,%2,%3}, a, b, 1, 1, 1, 1, 0;\n"
                 "add.u32 x, %4, 384;\nadd.u32 y, %5, 24;\nmov.b64 a, {x, 0x40000040};\nmov.b64 b, {y, 1};\n"
                 "wgmma.mma_async.sync.aligned.m64n8k16.f32.bf16.bf16 {%0,%1,%2,%3}, a, b, 1, 1, 1, 1, 0;\n"
                 "add.u32 x, %4, 512;\nadd.u32 y, %5, 32;\nmov.b64 a, {x, 0x40000040};\nmov.b64 b, {y, 1};\n"
                 "wgmma.mma_async.sync.aligned.m64n8k16.f32.bf16.bf16 {%0,%1,%2,%3}, a, b, 1, 1, 1, 1, 0;\n"
                 "add.u32 x, %4, 640;\nadd.u32 y, %5, 40;\nmov.b64 a, {x, 0x40000040};\nmov.b64 b, {y, 1};\n"
                 "wgmma.mma_async.sync.aligned.m64n8k16.f32.bf16.bf16 {%0,%1,%2,%3}, a, b, 1, 1, 1, 1, 0;\n"
                 "add.u32 x, %4, 768;\nadd.u32 y, %5, 48;\nmov.b64 a, {x, 0x40000040};\nmov.b64 b, {y, 1};\n"
                 "wgmma.mma_async.sync.aligned.m64n8k16.f32.bf16.bf16 {%0,%1,%2,%3}, a, b, 1, 1, 1, 1, 0;\n"
                 "add.u32 x, %4, 896;\nadd.u32 y, %5, 56;\nmov.b64 a, {x, 0x40000040};\nmov.b64 b, {y, 1};\n"
                 "wgmma.mma_async.sync.aligned.m64n8k16.f32.bf16.bf16 {%0,%1,%2,%3}, a, b, 1, 1, 1, 1, 0;\n"
                 "wgmma.commit_group.sync.aligned;\n}"
                 : "+f"(d[0]), "+f"(d[1]), "+f"(d[2]), "+f"(d[3]) : "r"(da), "r"(db), "r"(accumulate) : "memory");
}
__device__ __forceinline__ uint32_t lds32(uint32_t a) {
    uint32_t v;
    asm volatile("ld.shared.u32 %0, [%1];" : "=r"(v) : "r"(a));
    return v;
}
__device__ __forceinline__ unsigned ld_acquire(const unsigned* p) {
    unsigned v;
    asm volatile("ld.acquire.gpu.global.u32 %0, [%1];" : "=r"(v) : "l"(p) : "memory");
    return v;
}
__device__ __forceinline__ uint2 ld_relaxed8(const void* p) {
    uint2 v;
    asm volatile("ld.relaxed.gpu.global.v2.u32 {%0,%1}, [%2];" : "=r"(v.x), "=r"(v.y) : "l"(p) : "memory");
    return v;
}
__device__ __forceinline__ unsigned ld_relaxed4(const void* p) {
    unsigned v;
    asm volatile("ld.relaxed.gpu.global.u32 %0, [%1];" : "=r"(v) : "l"(p) : "memory");
    return v;
}
__device__ __forceinline__ unsigned atom_inc(unsigned* p) {
    unsigned v;
    asm volatile("atom.relaxed.gpu.global.inc.u32 %0, [%1], 0x7fffffff;" : "=r"(v) : "l"(p) : "memory");
    return v;
}
__device__ __forceinline__ unsigned long long ld_relaxed64(const void* p) {
    unsigned long long v;
    asm volatile("ld.relaxed.gpu.global.u64 %0, [%1];" : "=l"(v) : "l"(p) : "memory");
    return v;
}
__device__ __forceinline__ void st_relaxed64(void* p, unsigned long long v) {
    asm volatile("st.relaxed.gpu.global.u64 [%0], %1;" ::"l"(p), "l"(v) : "memory");
}
__device__ __forceinline__ float4 ld_relaxed16(const void* p) {
    float4 v;
    asm volatile("ld.relaxed.gpu.global.v4.f32 {%0,%1,%2,%3}, [%4];" : "=f"(v.x), "=f"(v.y), "=f"(v.z), "=f"(v.w) : "l"(p) : "memory");
    return v;
}
__device__ __forceinline__ uint32_t mapa(uint32_t a, uint32_t rank) {
    uint32_t r;
    asm("mapa.shared::cluster.u32 %0, %1, %2;" : "=r"(r) : "r"(a), "r"(rank));
    return r;
}
__device__ __forceinline__ void mbar_first(uint32_t bar) {
    asm volatile("{\n.reg .pred p, q;\n.reg .u32 n;\nmov.u32 n, 0;\n"
                 "SPIN:\nmbarrier.try_wait.parity.shared::cta.b64 p, [%0], 0;\nadd.u32 n, n, 1;\nsetp.gt.u32 q, n, 0x1000000;\n@q trap;\n"
                 "@!p bra.uni SPIN;\n}" ::"r"(bar) : "memory");
}
__device__ __forceinline__ void mbar_first_cluster(uint32_t bar) {
    asm volatile("{\n.reg .pred p, q;\n.reg .u32 n;\nmov.u32 n, 0;\n"
                 "SPIN:\nmbarrier.try_wait.parity.relaxed.cluster.shared::cta.b64 p, [%0], 0;\nadd.u32 n, n, 1;\nsetp.gt.u32 q, n, 0x1000000;\n@q trap;\n"
                 "@!p bra.uni SPIN;\nfence.acquire.sync_restrict::shared::cluster.cluster;\n}" ::"r"(bar) : "memory");
}
__device__ __forceinline__ uint32_t now_ns() {
    unsigned long long t;
    asm volatile("mov.u64 %0, %globaltimer;" : "=l"(t));
    return (uint32_t)t;
}
__device__ __forceinline__ void fence_gpu() { asm volatile("fence.acq_rel.gpu;" ::: "memory"); }
__device__ __forceinline__ void red_add_u32(unsigned* p, unsigned v) {
    asm volatile("red.relaxed.gpu.global.add.u32 [%0], %1;" ::"l"(p), "r"(v) : "memory");
}
__device__ __forceinline__ void st_tagged2(void* p, float a, float b, unsigned tag) {
    const unsigned long long hi = (unsigned long long)tag << 32;
    asm volatile("st.relaxed.gpu.global.v2.b64 [%0], {%1,%2};" ::"l"(p), "l"(hi | __float_as_uint(a)), "l"(hi | __float_as_uint(b)) : "memory");
}
__device__ __forceinline__ ulonglong2 ld_tagged2(const void* p) {
    ulonglong2 v;
    asm volatile("ld.relaxed.gpu.global.v2.b64 {%0,%1}, [%2];" : "=l"(v.x), "=l"(v.y) : "l"(p) : "memory");
    return v;
}
__device__ __forceinline__ float4 atom_add_f4(void* p, float a, float b, float c, float d) {
    float4 r;
    asm volatile("atom.relaxed.gpu.global.add.v4.f32 {%0,%1,%2,%3}, [%4], {%5,%6,%7,%8};"
                 : "=f"(r.x), "=f"(r.y), "=f"(r.z), "=f"(r.w) : "l"(p), "f"(a), "f"(b), "f"(c), "f"(d) : "memory");
    return r;
}
__device__ __forceinline__ void red_release_cta_shared(uint32_t a, unsigned v) {
    asm volatile("red.release.cta.shared::cta.add.u32 [%0], %1;" ::"r"(a), "r"(v) : "memory");
}
__device__ __forceinline__ unsigned ld_acquire_cta_shared(uint32_t a) {
    unsigned v;
    asm volatile("ld.acquire.cta.shared::cta.u32 %0, [%1];" : "=r"(v) : "r"(a) : "memory");
    return v;
}
__device__ __forceinline__ void st_release_cta_shared(uint32_t a, unsigned v) {
    asm volatile("st.release.cta.shared::cta.u32 [%0], %1;" ::"r"(a), "r"(v) : "memory");
}
__device__ __forceinline__ void wait_count(const unsigned* p, unsigned target) {
    unsigned n = 0;
    while (ld_acquire(p) < target) { if (++n > SPIN_LIMIT) __trap(); }
}
__device__ __forceinline__ uint32_t pack_bf16(float lo, float hi) {
    uint32_t r;
    asm("cvt.rn.bf16x2.f32 %0, %1, %2;" : "=r"(r) : "f"(hi), "f"(lo));
    return r;
}
__device__ __forceinline__ float bf_lo(uint32_t v) { return __uint_as_float(v << 16); }
__device__ __forceinline__ float bf_hi(uint32_t v) { return __uint_as_float(v & 0xffff0000u); }
__device__ __forceinline__ float ex2(float x) { float y; asm("ex2.approx.ftz.f32 %0, %1;" : "=f"(y) : "f"(x)); return y; }
__device__ __forceinline__ float expsub(float a, float b) { return ex2((a - b) * LOG2E); }
__device__ __forceinline__ float warp_max(float v) {
#pragma unroll
    for (int m = 16; m; m >>= 1) v = fmaxf(v, __shfl_xor_sync(~0u, v, m));
    return v;
}
__device__ __forceinline__ float warp_sum(float v) {
#pragma unroll
    for (int m = 16; m; m >>= 1) v += __shfl_xor_sync(~0u, v, m);
    return v;
}
__device__ __forceinline__ unsigned unit_block(int u) {
    const unsigned v = u & (NUK - 1);
    return u < NUK ? (v & ~0x78u) | (v & 0x18u) << 2 | (v & 0x60u) >> 2 : v;
}
__device__ __forceinline__ const char* block_src(const void* base, unsigned blk) {
    const unsigned po = blk / UPP;
    return reinterpret_cast<const char*>(base) + (size_t)(((po & 3) * NH + (po >> 2)) * UPP + blk % UPP) * TILE_BYTES;
}

template <bool CLU>
__device__ __forceinline__ void a_worker(const Params& p, int un, bool once, bool hold, int nstatic, uint32_t slot, uint32_t bar, uint32_t wb,
                                         uint32_t help, unsigned epoch, uint64_t pol) {
    constexpr int NU = 2 * NUK;
    const int lane = threadIdx.x & 31, g = lane >> 2, t = lane & 3;
    const int li = lane & 7;
    uint32_t kaddr[4], vaddr[8];
    {
        const int e = (lane >> 3) & 1, kk = lane >> 4;
#pragma unroll
        for (int s = 0; s < 4; s++) kaddr[s] = slot + (16 * li + e) * 256 + ((2 * s + kk + li) & 7) * 16;
        const int vrow = 4 * (li >> 1) + (li & 1) + 2 * kk;
#pragma unroll
        for (int c = 0; c < 8; c++) vaddr[c] = slot + vrow * 256 + e * 128 + ((c + li) & 7) * 16;
#pragma unroll
        for (int c = 0; c < 8; c++) asm volatile("" : "+r"(vaddr[c]));
    }
    const uint32_t vmask = (g >> 1) != t ? 0u : ((g & 1) ? 0xffff0000u : 0xffffu);
    int kseen = -1;
    unsigned long long H0 = 0, H1 = 0;
    auto header = [&](int v, unsigned vb) {
        if (v >= NU) return;
        const void *a0, *a1;
        if (v < NUK) {
            const unsigned po = vb / UPP;
            a0 = g_qll + (po & 3) * 2048 + (po >> 2) * 64 + lane;
            a1 = reinterpret_cast<const uint2*>(a0) + 32;
        } else {
            const int half = vb / (NUK / 2);
            if (half > kseen) {
                unsigned n = 0;
                while (ld_acquire_cta_shared(help + 12 + 4 * half) == 0) { if (++n > (SPIN_LIMIT << 4)) __trap(); }
                kseen = half;
            }
            a0 = &g_scores[vb * (KEYS / 4) + lane];
            a1 = &g_stats[(vb / UPP) * UPP + lane];
        }
        H0 = ld_relaxed64(a0);
        H1 = ld_relaxed64(a1);
    };
    epoch = __shfl_sync(~0u, epoch, 0);
    if (hold) { unsigned n = 0; while (ld_acquire_cta_shared(help + 24) < 2) { if (++n > (SPIN_LIMIT << 4)) __trap(); } }
    unsigned (*ctl)[32] = g_ctl[epoch & 1];
    const unsigned tag = epoch + 1;
    unsigned nxt = once ? NU : 0;
    int u = -1;
    unsigned bu = 0, bn = unit_block(un);
    bool have = false;
    uint32_t phase = 0;
    unsigned kpend = 0;
    const unsigned zero = gridDim.x >> 24;
    uint32_t Q[16];
    float4 oret = make_float4(0.f, 0.f, 0.f, 0.f);
    while (true) {
        const char* nsrc = block_src(un < NUK ? p.kc : p.vc, bn);
        float4* odst = &g_oacc[(bu / UPP) * 32 + lane];
        unsigned* vdst = &g_vdone[(lane & (NREP - 1)) * NH + bu / (4 * UPP)][0];
        float d[8][4];
        CLK(c1);
        asm volatile("" : "+l"(odst));
        if (u >= NUK) {
#pragma unroll
            for (int j = 0; j < 8; j++) { d[j][0] = d[j][1] = d[j][2] = d[j][3] = 0.f; }
            mbar_wait(wb, phase);
            LAND(NUK + bu);
            uint32_t a[2][8][4];
#pragma unroll
            for (int c = 0; c < 8; c++) ldsm4t(a[0][c], vaddr[c]);
#pragma unroll
            for (int j = 0; j < 8; j++) {
                if (j < 7) {
#pragma unroll
                    for (int c = 0; c < 8; c++) ldsm4t(a[(j + 1) & 1][c], vaddr[c] + (j + 1) * 4096);
                }
#pragma unroll
                for (int c = 0; c < 8; c++) mma16816(d[c], a[j & 1][c], Q[2 * j], Q[2 * j + 1]);
            }
            float o[4];
#pragma unroll
            for (int r = 0; r < 2; r++) {
                o[2 * r] = d[0][2 * r] + d[7][2 * r + 1];
                o[2 * r + 1] = d[0][2 * r + 1] + d[1][2 * r];
#pragma unroll
                for (int k = 1; k < 4; k++) {
                    const int src = (lane & 28) | ((t - k) & 3);
                    o[2 * r] += __shfl_sync(~0u, d[2 * k][2 * r] + d[2 * k - 1][2 * r + 1], src);
                    o[2 * r + 1] += __shfl_sync(~0u, d[2 * k][2 * r + 1] + d[2 * k + 1][2 * r], src);
                }
            }
            oret = atom_add_f4(odst, o[0], o[1], o[2], o[3]);
        } else if (u >= 0) {
#pragma unroll
            for (int j = 0; j < 8; j++) { d[j][0] = d[j][1] = d[j][2] = d[j][3] = 0.f; }
            mbar_wait(wb, phase);
            LAND(bu);
            uint32_t a[2][8][4];
#pragma unroll
            for (int j = 0; j < 8; j++) ldsm4(a[0][j], kaddr[0] + (4 * (j & 3) + 2 * (j >> 2)) * 256);
#pragma unroll
            for (int s = 0; s < 8; s++) {
                if (s < 7) {
#pragma unroll
                    for (int j = 0; j < 8; j++)
                        ldsm4(a[(s + 1) & 1][j], kaddr[(s + 1) & 3] + (4 * (j & 3) + 2 * (j >> 2)) * 256 + ((s + 1) >> 2) * 128);
                }
#pragma unroll
                for (int j = 0; j < 8; j++)
                    mma16816(d[j], a[s & 1][j], Q[(s & 4) * 2 + ((2 * s - 2 * j) & 7)], Q[(s & 4) * 2 + ((2 * s + 1 - 2 * j) & 7)]);
            }
        }
        const bool pre = wb != bar;
        if (u >= 0) { phase = pre ? 0 : phase ^ 1; wb = bar; }
        CLK(c2b);
        if (un < NU && lane == 0) {
            if (!once) nxt = atom_inc(&ctl[C_QUEUE][0]);
            if (u >= 0 || !pre) {
                mbar_expect_tx(bar, TILE_BYTES);
                bulk_load(slot, nsrc, TILE_BYTES, bar, pol);
            }
        }
        const uint32_t tiss = now_ns();
        CLK(c3);
        if ((unsigned)u < (unsigned)NUK) {
            const int j0 = (t - (g >> 1)) & 3;
            float v[4];
#pragma unroll
            for (int q = 0; q < 4; q++) {
                const int jq = (q >> 1) * 4, e = (q & 1) * 2;
                const float x0 = (g & 1) ? d[jq + 0][e + 1] : d[jq + 0][e];
                const float x1 = (g & 1) ? d[jq + 1][e + 1] : d[jq + 1][e];
                const float x2 = (g & 1) ? d[jq + 2][e + 1] : d[jq + 2][e];
                const float x3 = (g & 1) ? d[jq + 3][e + 1] : d[jq + 3][e];
                const float y0 = (j0 & 1) ? x1 : x0, y1 = (j0 & 1) ? x3 : x2;
                v[q] = (j0 & 2) ? y1 : y0;
            }
            const uint32_t r0 = pack_bf16(v[0], v[1]), r1 = pack_bf16(v[2], v[3]);
            const uint32_t s0 = pack_bf16(bf_lo(r0) * SCALE, bf_hi(r0) * SCALE);
            const uint32_t s1 = pack_bf16(bf_lo(r1) * SCALE, bf_hi(r1) * SCALE);
            g_scores[bu * (KEYS / 4) + 4 * g + j0] = make_uint2(s0, s1);
            const float f0 = bf_lo(s0), f1 = bf_hi(s0), f2 = bf_lo(s1), f3 = bf_hi(s1);
            const float m = warp_max(fmaxf(fmaxf(f0, f1), fmaxf(f2, f3)));
            const float l = warp_sum((expsub(f0, m) + expsub(f1, m)) + (expsub(f2, m) + expsub(f3, m)));
            if (lane == 0) g_stats[bu] = make_float2(m, l);
            kpend++;
            if (un / (NUK / 2) != u / (NUK / 2)) {
                __syncwarp();
                if (lane == 0) {
                    red_release_cta_shared(help + 4 * (u / (NUK / 2)), kpend);
                    if (un >= NUK) red_release_cta_shared(help + 8, 1u);
                }
                kpend = 0;
            }
        }
        CLK(c4);
        int unn = NU;
        if (un < NU) {
            unsigned n = 0;
            while (true) {
                if (!have) header(un, bn);
                if (un >= NUK || __all_sync(~0u, (uint32_t)(H0 >> 32) == tag && (uint32_t)(H1 >> 32) == tag)) break;
                if (++n > SPIN_LIMIT) __trap();
                have = false;
            }
            if (un >= NUK) {
                const uint32_t s0 = (uint32_t)H0, s1 = (uint32_t)(H0 >> 32);
                const float mu = __uint_as_float((uint32_t)H1);
                const float m = warp_max(mu);
                const float l = warp_sum(__uint_as_float((uint32_t)(H1 >> 32)) * expsub(mu, m));
                const float inv = 1.0f / l;
                const uint32_t w0 = pack_bf16(expsub(bf_lo(s0), m) * inv, expsub(bf_hi(s0), m) * inv);
                const uint32_t w1 = pack_bf16(expsub(bf_lo(s1), m) * inv, expsub(bf_hi(s1), m) * inv);
#pragma unroll
                for (int j = 0; j < 8; j++) {
                    Q[2 * j] = __shfl_sync(~0u, w0, 4 * j + t) & vmask;
                    Q[2 * j + 1] = __shfl_sync(~0u, w1, 4 * j + t) & vmask;
                }
            } else {
#pragma unroll
                for (int j = 0; j < 8; j++) {
                    const int src = (((j + g) & 7) << 2) + t;
                    Q[j] = __shfl_sync(~0u, (uint32_t)H0, src);
                    Q[8 + j] = __shfl_sync(~0u, (uint32_t)H1, src);
                }
            }
            unn = nstatic + (int)__shfl_sync(~0u, nxt, 0);
            if (CLU && !once && unn >= NU && lane == 0)
                asm volatile("st.relaxed.cta.shared::cta.u32 [%0], %1;" ::"r"(help + 28), "r"((tiss + (FJ - (unn - NU)) * 10) | 1u) : "memory");
        }
        if (u >= NUK && lane < (CLU ? 1 : NREP))
            red_add_u32(vdst,
                        1u + ((__float_as_uint(oret.x) | __float_as_uint(oret.y) | __float_as_uint(oret.z) | __float_as_uint(oret.w)) & zero));
        if (un >= NU) break;
        bu = bn;
        have = !(un < NUK && unn >= NUK && !(un >= NUK / 2 && unn < NUK + NUK / 2));
        bn = unit_block(unn);
        if (have) header(unn, bn);
        u = un;
        un = unn;
    }
}

__device__ __forceinline__ void k_helper(uint32_t help, unsigned epoch) {
    if ((threadIdx.x & 31) != 0) return;
    unsigned (*ctl)[32] = g_ctl[epoch & 1];
    unsigned sent0 = 0, sent1 = 0, n = 0;
    int seen = 0;
    bool fin = false;
    while (!fin || seen < 2) {
        if (!fin) {
            fin = ld_acquire_cta_shared(help + 8) == NW + XW;
            const unsigned c0 = ld_acquire_cta_shared(help), c1 = ld_acquire_cta_shared(help + 4);
            if (c0 != sent0 || c1 != sent1) {
                fence_gpu();
                if (c0 != sent0) red_add_u32(&ctl[C_KDONE][0], c0 - sent0);
                if (c1 != sent1) red_add_u32(&ctl[C_KDONE + 1][0], c1 - sent1);
                sent0 = c0; sent1 = c1;
            }
        }
        if (seen < 2 && ld_acquire(&ctl[C_KDONE + seen][0]) >= NUK / 2) {
            st_release_cta_shared(help + 12 + 4 * seen, 1u);
            seen++;
        } else {
            __nanosleep(300);
        }
        if (++n > SPIN_LIMIT) __trap();
    }
}

__device__ __forceinline__ void v_poller(uint32_t sbase, int f, int w) {
    const int lane = threadIdx.x & 31;
    const unsigned (*cp)[32] = &g_vdone[((f * NPOLL + w) % NREP) * NH];
    unsigned n = 0;
    while (ld_acquire_cta_shared(sbase + M_HELP + 12) == 0) { __nanosleep(1000); if (++n > SPIN_LIMIT) __trap(); }
    int h = 0;
    bool fast = false;
    while (h < NH) {
        const unsigned r = __ballot_sync(~0u, ld_acquire(&cp[min(h + (lane & 3), NH - 1)][0]) >= 4 * UPP) & 15u;
        if (r & 1) {
            h = min(NH, h + __ffs(~r) - 1);
            __syncwarp();
            if (lane == 0) asm volatile("red.release.cta.shared::cta.max.u32 [%0], %1;" ::"r"(sbase + M_HELP + 20), "r"(h) : "memory");
        }
        if (h < NH - 4) {
            __nanosleep(h ? 300 : 1000);
        } else if (!fast) {
            fast = true;
            const long long t0 = clock64();
            while (clock64() - t0 < w * PGAP) {}
        }
        if (++n > SPIN_LIMIT) __trap();
    }
}
__device__ __forceinline__ void finisher(const Params& p, uint32_t sbase, int f) {
    const int lane = threadIdx.x & 31;
    {
        const char* wg = reinterpret_cast<const char*>(p.wo);
        const uint32_t dst = sbase + 4 * SLOT + (16 * (lane & 7) + (lane >> 3)) * 16;
#pragma unroll 1
        for (int h = -FPF - 4; h < NH; h++) {
            if (lane == 0 && (unsigned)(h + FPF) < (unsigned)NH) l2_prefetch(wg + (size_t)(h + FPF) * 147456 + f * 2048, 2048);
            if (h >= 0) {
#pragma unroll
                for (int r = 0; r < 4; r++)
                    asm volatile("cp.async.cg.shared.global [%0], [%1], 16;" ::"r"(dst + h * 2048 + ((r & 1) * 4 + (r >> 1) * 8) * 16),
                                 "l"(wg + (size_t)(h * 128 + r * 32 + lane) * (DM * 2) + f * 16) : "memory");
            }
            __nanosleep(FSLEEP);
        }
        asm volatile("cp.async.wait_all;" ::: "memory");
        __syncwarp();
    }
    TS(11);
    const float4* vec = g_oacc + ((lane >> 2) & 3) * 32 + (lane >> 4) * 16 + (lane & 3);
    float acc[2][2][4];
#pragma unroll
    for (int i = 0; i < 16; i++) acc[i >> 3][(i >> 2) & 1][i & 3] = 0.f;
    uint32_t* outp = reinterpret_cast<uint32_t*>(p.out + (lane >> 2) * (2 * DM) + f * 8 + (lane & 3) * 2);
    uint32_t wa = sbase + 4 * SLOT + lane * 16;
    auto project = [&](const float4 (&x)[4], const uint32_t (&w)[4][4]) {
#pragma unroll
        for (int s = 0; s < 4; s++) {
            const uint32_t a[4] = {pack_bf16(x[s].x, x[s].y), 0u, pack_bf16(x[s].z, x[s].w), 0u};
            mma16816(acc[0][s & 1], a, w[s >> 1][(s & 1) * 2], w[s >> 1][(s & 1) * 2 + 1]);
            mma16816(acc[1][s & 1], a, w[2 + (s >> 1)][(s & 1) * 2], w[2 + (s >> 1)][(s & 1) * 2 + 1]);
        }
    };
    int h = 0;
    unsigned n = 0;
    while (h < NH) {
        uint32_t w[4][4];
#pragma unroll
        for (int q = 0; q < 4; q++) ldsm4t(w[q], wa + q * 512);
        int ready;
        while ((ready = ld_acquire_cta_shared(sbase + M_HELP + 20)) <= h) {
            if (h < NH - 3) __nanosleep(100);
            if (++n > (SPIN_LIMIT << 4)) __trap();
        }
        float4 x[4], y[4];
#pragma unroll
        for (int s = 0; s < 4; s++) x[s] = ld_relaxed16(vec + s * 4);
        const bool two = ready > h + 1;
        if (two) {
#pragma unroll
            for (int s = 0; s < 4; s++) y[s] = ld_relaxed16(vec + 128 + s * 4);
        }
        project(x, w);
        if (two) {
#pragma unroll
            for (int q = 0; q < 4; q++) ldsm4t(w[q], wa + 2048 + q * 512);
            project(y, w);
        }
        const int nr = two ? 2 : 1;
        h += nr;
        vec += nr * 128;
        wa += nr * 2048;
        const float o0 = acc[0][0][0] + acc[0][1][0] + __shfl_down_sync(~0u, acc[1][0][0] + acc[1][1][0], 16);
        const float o1 = acc[0][0][1] + acc[0][1][1] + __shfl_down_sync(~0u, acc[1][0][1] + acc[1][1][1], 16);
        asm volatile("{\n.reg .pred p;\nsetp.ne.u32 p, %2, 0;\n@p st.global.u32 [%0], %1;\n}" ::"l"(outp), "r"(pack_bf16(o0, o1)),
                     "r"((uint32_t)(lane < 16 && h == NH)) : "memory");
    }
}

__device__ __forceinline__ void out_fetch(uint32_t sbase, int step, int h) {
    const int lane = threadIdx.x & 31, g = lane >> 2;
    float4 x[4];
#pragma unroll
    for (int b = 0; b < 4; b++) x[b] = ld_relaxed16(&g_oacc[(h * 4 + ((b + g) & 3)) * 32 + lane]);
#pragma unroll
    for (int b = 0; b < 4; b++) {
        const uint32_t a = sbase + F_X + step * FXP + g * 128 + ((b + g) & 3) * 16 + (lane & 3) * 4;
        asm volatile("st.shared.u32 [%0], %1;\nst.shared.u32 [%0 + 64], %2;" ::"r"(a), "r"(pack_bf16(x[b].x, x[b].y)), "r"(pack_bf16(x[b].z, x[b].w)) : "memory");
    }
    asm volatile("fence.proxy.async.shared::cta;" ::: "memory");
}
__device__ __forceinline__ void out_early(uint32_t sbase, int rank, unsigned tag) {
    const int lane = threadIdx.x & 31;
    if (lane < 10) {
        mbar_init(sbase + F_BAR + 16 + lane * 8, lane < 7 ? 1 : lane == 7 ? 2 : 4);
        if (lane < 8) mbar_expect_tx(sbase + F_BAR + 16 + lane * 8, 16384);
    }
    asm volatile("fence.mbarrier_init.release.cluster;" ::: "memory");
    unsigned n = 0;
#pragma unroll 1
    for (int i = 0; i < 3; i++) {
        while (ld_acquire(&g_vdone[8 * i + rank][0]) < 4 * UPP) { __nanosleep(500); if (++n > SPIN_LIMIT) __trap(); }
        out_fetch(sbase, 4 + i, 8 * i + rank);
#pragma unroll 1
        for (int j = 0; j < 16 && i == 0;) {
            const ulonglong2 v = ld_tagged2(&g_ctx[((j >> 2) * 8 + rank) * 128 + (j & 3) * 32 + lane]);
            if (__all_sync(~0u, (unsigned)(v.x >> 32) == tag && (unsigned)(v.y >> 32) == tag)) {
                asm volatile("st.shared.v2.u32 [%0], {%1,%2};" ::"r"(sbase + F_X + (j >> 2) * FXP + ((j & 3) * 32 + lane) * 8), "r"((uint32_t)v.x), "r"((uint32_t)v.y) : "memory");
                j++;
            } else {
                __nanosleep(500);
                if (++n > SPIN_LIMIT) __trap();
            }
        }
    }
    __syncwarp();
    if (lane == 0) st_release_cta_shared(sbase + M_HELP + 32, 1u);
}
__device__ __forceinline__ void out_late(uint32_t sbase, int rank) {
    unsigned n = 0;
    while (ld_acquire_cta_shared(sbase + M_HELP + 32) == 0) { if (++n > (SPIN_LIMIT << 4)) __trap(); }
    while (ld_acquire(&g_vdone[24 + rank][0]) < 4 * UPP) { if (++n > SPIN_LIMIT) __trap(); }
    TS(12);
    out_fetch(sbase, 7, 24 + rank);
    __syncwarp();
    if ((threadIdx.x & 31) == 0) asm volatile("mbarrier.arrive.shared::cta.b64 _, [%0];" ::"r"(sbase + F_BAR + 72) : "memory");
    TS(13);
}
__device__ __forceinline__ void out_project(uint32_t sbase, int rank, int w) {
    const int lane = threadIdx.x & 31, g = lane >> 2, t = lane & 3;
    unsigned n = 0;
    while (ld_acquire_cta_shared(sbase + M_HELP + 32) == 0) { __nanosleep(500); if (++n > SPIN_LIMIT) __trap(); }
    asm volatile("barrier.cluster.wait.acquire.aligned;" ::: "memory");
    const uint32_t rdst = mapa(sbase + F_RECV + 1024 + rank * 128 + (g & 3) * 32 + t * 16, 2 * w + (g >> 2));
    const uint32_t rbar = mapa(sbase + F_BAR + 8, 2 * w + (g >> 2));
    while (ld_acquire_cta_shared(sbase + M_HELP + 28) == 0) { __nanosleep(200); if (++n > SPIN_LIMIT) __trap(); }
    const uint32_t da = (1u << 16) | (((sbase + F_W) & 0x3ffff) >> 4), db = (4u << 16) | (((sbase + F_X) & 0x3ffff) >> 4);
    float d[4] = {0.f, 0.f, 0.f, 0.f};
#pragma unroll
    for (int i = 0; i < 8; i++) {
        mbar_first(sbase + F_BAR + 16 + i * 8);
        wgmma_tile(d, da + (i % 6) * 1024, db + i * (FXP / 16), i & 3);
        if (i < 2 || (i & 3) == 3) asm volatile("wgmma.wait_group.sync.aligned 0;" : "+f"(d[0]), "+f"(d[1]), "+f"(d[2]), "+f"(d[3])::"memory");
        if (i < 2) {
            asm volatile("{\n.reg .pred p;\nsetp.eq.u32 p, %1, 0;\n@p mbarrier.arrive.shared::cta.b64 _, [%0];\n}"
                         ::"r"(sbase + F_BAR + 80 + i * 8), "r"(lane) : "memory");
        } else if ((i & 3) == 3) {
            if (t < 2)
                asm volatile("st.async.weak.shared::cluster.mbarrier::complete_tx::bytes.v4.f32 [%0], {%1,%2,%3,%4}, [%5];"
                             ::"r"(rdst - (i < 4 ? 1024 : 0)), "f"(d[0]), "f"(d[1]), "f"(d[2]), "f"(d[3]), "r"(rbar - (i < 4 ? 8 : 0)) : "memory");
            __syncwarp();
        }
    }
}
__device__ __forceinline__ void out_issue_sum(const Params& p, uint32_t sbase, int c, int rank, uint64_t pol) {
    const int lane = threadIdx.x & 31;
    if (lane == 0) {
        unsigned n = 0;
        while (ld_acquire_cta_shared(sbase + M_HELP + 32) == 0) { __nanosleep(500); if (++n > SPIN_LIMIT) __trap(); }
        asm volatile("prefetch.tensormap [%0];" ::"l"(&p.tm_wf) : "memory");
        asm volatile("prefetch.tensormap [%0];" ::"l"(&p.tm_wl) : "memory");
        uint32_t t0;
        while ((t0 = ld_acquire_cta_shared(sbase + M_HELP + 28)) == 0) { __nanosleep(100); if (++n > SPIN_LIMIT) __trap(); }
#pragma unroll 1
        for (int i = 0; i < 8; i++) {
            const int h = (i & 3) * 8 + rank;
            if (i >= 6) mbar_wait(sbase + F_BAR + 32 + i * 8, 0);
            for (int k = 0; k < 4096 && (int)(now_ns() - t0) < 0; k++) {}
            if (i == 0) TS(16);
            tma3d(sbase + F_W + (i < 6 ? i : i - 6) * 16384, i < 4 ? &p.tm_wf : &p.tm_wl, i < 4 ? 0 : c * 64, i < 4 ? h * 128 : h * 16,
                  i < 4 ? c : 0, sbase + F_BAR + 16 + i * 8, pol);
            t0 += FP;
        }
        TS(17);
    }
    __syncwarp();
    __nv_bfloat16* dst = p.out + (((lane >> 1) & 2) + (lane & 1)) * (2 * DM) + DM + c * 64 + (rank >> 1) * 16 + (lane & 2) * 4 +
                         (rank & 1) * 4 + (lane >> 3);
    uint32_t src = sbase + F_RECV + lane * 4;
#pragma unroll 1
    for (int r = 0; r < 2; r++) {
        asm volatile("" : "+l"(dst), "+r"(src));
        mbar_first_cluster(sbase + F_BAR + r * 8);
        float x[8];
#pragma unroll
        for (int i = 0; i < 8; i++) asm volatile("ld.shared.f32 %0, [%1];" : "=f"(x[i]) : "r"(src + i * 128) : "memory");
        const float v = (((x[0] + x[1]) + (x[2] + x[3])) + (x[4] + x[5])) + (x[6] + x[7]);
        asm volatile("{\n.reg .b16 h;\ncvt.rn.bf16.f32 h, %1;\nst.global.b16 [%0], h;\n}" ::"l"(dst), "f"(v) : "memory");
        TS(14 + r);
        dst -= DM;
        src += 1024;
    }
}

constexpr int BS_WUK = 5, BS_Q = 9, BS_CKV = 11, BS_PART = 27, BS_WUV = 29, BS_END = 33;

__device__ __noinline__ void b_issue(const Params& p, int n, int bi, uint32_t sbase, uint64_t pol) {
    if (n >= BS_END || (n >= BS_Q && n < BS_CKV) || (n >= BS_PART && n < BS_WUV)) return;
    const uint32_t bar = sbase + M_BAR + (NSLOT + n % BRING) * 8;
    const CUtensorMap* tm;
    int row, panel = 2 * bi;
    if (n < BS_WUK) { tm = &p.tm_wq; row = n * 128; }
    else if (n < BS_Q) { tm = &p.tm_wuk; row = (n - BS_WUK) * 128; }
    else if (n < BS_PART) {
        tm = &p.tm_ckv; panel = 0;
        row = (bi >> 3) * SK + ((n - BS_CKV) * 8 + (bi & 7)) * 32;
    }
    else { tm = &p.tm_wuv; row = (n - BS_WUV) * 128; }
    mbar_expect_tx(bar, n == 0 ? 32768 + 4 * 1152 : 32768);
    tma3d(sbase + (n % BRING) * SLOT, tm, 0, row, panel, bar, pol);
}
__device__ __forceinline__ void b_issue_xchg(int n, const void* src, uint32_t sbase, uint64_t pol) {
    asm volatile("fence.proxy.async;" ::: "memory");
#pragma unroll
    for (int i = 0; i < 2; i++) {
        const uint32_t bar = sbase + M_BAR + (NSLOT + (n + i) % BRING) * 8;
        mbar_expect_tx(bar, 32768);
        bulk_load(sbase + ((n + i) % BRING) * SLOT, reinterpret_cast<const char*>(src) + i * 32768, 32768, bar, pol);
    }
}
__device__ __forceinline__ void b_wait(int n, uint32_t sbase) {
    mbar_wait(sbase + M_BAR + (NSLOT + n % BRING) * 8, (n / BRING) & 1);
}

__device__ __noinline__ void b_gemm(const Params& p, uint32_t sbase, int n0, int n1, int ktot, uint32_t xh, uint32_t xl, int pitch,
                                    int bi, uint64_t pol) {
    const int tid = threadIdx.x, warp = tid >> 5, lane = tid & 31, g = lane >> 2, t = lane & 3;
    const uint32_t woff = (warp >> 2) * 16384 + (lane & 15) * 128 + ((((warp & 3) * 2 + (lane >> 4)) ^ (lane & 7)) * 16);
    const uint32_t xoff = (g & 3) * pitch + t * 4;
    float acc[2][4];
#pragma unroll
    for (int i = 0; i < 8; i++) acc[i >> 2][i & 3] = 0.f;
#pragma unroll 1
    for (int n = n0; n < n1; n++) {
        b_wait(n, sbase);
        const uint32_t slot = sbase + (n % BRING) * SLOT + woff;
        const int k0 = (n - n0) * 128;
        const int ns = min(8, (ktot - k0) >> 4);
#pragma unroll 2
        for (int s = 0; s < ns; s++) {
            uint32_t a[4], w[4];
            const uint32_t xo = xoff + (k0 + 16 * s) * 2;
            a[0] = lds32(xh + xo); a[2] = lds32(xh + xo + 16);
            a[1] = xl ? lds32(xl + xo) : 0u; a[3] = xl ? lds32(xl + xo + 16) : 0u;
            ldsm4t(w, slot + s * 2048);
            mma16816(acc[0], a, w[0], w[1]);
            mma16816(acc[1], a, w[2], w[3]);
        }
        __syncthreads();
        if (tid == 0) b_issue(p, n + BD, bi, sbase, pol);
    }
    if (g < 4) {
#pragma unroll
        for (int j = 0; j < 2; j++)
            asm volatile("st.shared.u32 [%0], %1;" ::"r"(sbase + M_QB + g * QP + (warp * 16 + j * 8 + t * 2) * 2),
                         "r"(pack_bf16(acc[j][0] + acc[j][2], acc[j][1] + acc[j][3])) : "memory");
    }
    __syncthreads();
}

__device__ __forceinline__ void b_exchange(unsigned* c, int n, const void* src, uint32_t sbase, uint64_t pol) {
    TS(n == BS_Q ? 24 : 28);
    __syncthreads();
    if (threadIdx.x == 0) {
        TS(n == BS_Q ? 25 : 29);
        fence_gpu();
        TS(n == BS_Q ? 26 : 30);
        red_add_u32(c, 1u);
        wait_count(c, NBCTA);
        TS(n == BS_Q ? 27 : 31);
        b_issue_xchg(n, src, sbase, pol);
    }
}

template <bool CLU>
__device__ __noinline__ void b_chain(const Params& p, char* smem, uint32_t sbase, int bi, unsigned epoch, uint64_t pol) {
    const int tid = threadIdx.x, warp = tid >> 5, lane = tid & 31, g = lane >> 2, t = lane & 3;
    unsigned (*ctl)[32] = g_ctl[epoch & 1];
    float* red = reinterpret_cast<float*>(smem + 5 * SLOT);
    b_gemm(p, sbase, 0, BS_WUK, DM, sbase + M_XB, 0, XP, bi, pol);
    TS(6);
    {
        uint32_t Q[16];
#pragma unroll
        for (int c = 0; c < 16; c++) Q[c] = lds32(sbase + M_QB + (g & 3) * QP + c * 16 + t * 4);
        float* qa = reinterpret_cast<float*>(smem + M_QA);
#pragma unroll 1
        for (int n = BS_WUK; n < BS_Q; n++) {
            b_wait(n, sbase);
            const uint32_t base = sbase + (n % BRING) * SLOT + (warp * 16 + (lane & 15)) * 128;
            float d[2][4];
#pragma unroll
            for (int i = 0; i < 8; i++) d[i >> 2][i & 3] = 0.f;
#pragma unroll
            for (int s = 0; s < 8; s++) {
                uint32_t a[4];
                ldsm4(a, base + (s >> 2) * 16384 + (((2 * (s & 3) + (lane >> 4)) ^ (lane & 7)) * 16));
                mma16816(d[s & 1], a, Q[2 * s], Q[2 * s + 1]);
            }
            const int c = (n - BS_WUK) * 128 + warp * 16 + g + 8 * (t >> 1);
            qa[(2 * (t & 1)) * 512 + c] = (t & 2) ? d[0][2] + d[1][2] : d[0][0] + d[1][0];
            qa[(2 * (t & 1) + 1) * 512 + c] = (t & 2) ? d[0][3] + d[1][3] : d[0][1] + d[1][1];
            __syncthreads();
            if (tid == 0) b_issue(p, n + BD, bi, sbase, pol);
        }
#pragma unroll 1
        for (int r = 0; r < 2; r++) {
            const int id = tid + r * 256;
            const int b = id >> 7, c0 = ((id >> 2) & 31) * 16 + (id & 3) * 2;
            const float2 u0 = *reinterpret_cast<const float2*>(qa + b * 512 + c0);
            const float2 u1 = *reinterpret_cast<const float2*>(qa + b * 512 + c0 + 8);
            const uint32_t h0 = pack_bf16(u0.x, u0.y), h1 = pack_bf16(u1.x, u1.y);
            const uint32_t l0 = pack_bf16(u0.x - bf_lo(h0), u0.y - bf_hi(h0)), l1 = pack_bf16(u1.x - bf_lo(h1), u1.y - bf_hi(h1));
            g_qabs[((id >> 2) * 4 + (bi >> 3)) * 32 + (bi & 7) * 4 + (id & 3)] = make_uint4(h0, l0, h1, l1);
        }
    }
    b_exchange(&ctl[C_BBAR][0], BS_Q, &g_qabs[(bi >> 3) * 4096], sbase, pol);
    {
        uint32_t qf[4][4][4];
        b_wait(BS_Q + (warp >> 2), sbase);
        TS(7);
        {
            const uint4* qs = reinterpret_cast<const uint4*>(smem + ((BS_Q + (warp >> 2)) % BRING) * SLOT) + (warp & 3) * 512 + lane;
#pragma unroll
            for (int s = 0; s < 4; s++)
#pragma unroll
                for (int i = 0; i < 4; i++) {
                    const uint4 v = qs[(s * 4 + i) * 32];
                    qf[i][s][0] = v.x; qf[i][s][1] = v.y; qf[i][s][2] = v.z; qf[i][s][3] = v.w;
                }
        }
        __syncthreads();
        if (tid == 0) { b_issue(p, BS_Q + BD, bi, sbase, pol); b_issue(p, BS_Q + 1 + BD, bi, sbase, pol); }
        float acc[2][8][4];
#pragma unroll
        for (int i = 0; i < 2; i++)
#pragma unroll
            for (int j = 0; j < 8; j++) { acc[i][j][0] = acc[i][j][1] = acc[i][j][2] = acc[i][j][3] = 0.f; }
        float mrun = -INFINITY, lrun = 0.f;
        const int head = tid >> 3, kq = tid & 7;
        float* alpha = reinterpret_cast<float*>(smem + M_ALPHA);
        for (int n = BS_CKV; n < BS_PART; n++) {
            b_wait(n, sbase);
            const uint32_t slot = sbase + (n % BRING) * SLOT;
            float sc[4][4][4];
#pragma unroll
            for (int i = 0; i < 4; i++)
#pragma unroll
                for (int j = 0; j < 4; j++) { sc[i][j][0] = sc[i][j][1] = sc[i][j][2] = sc[i][j][3] = 0.f; }
#pragma unroll
            for (int j = 0; j < 4; j++)
#pragma unroll
                for (int sp = 0; sp < 2; sp++) {
                    uint32_t bf[4];
                    ldsm4(bf, slot + warp * 4096 + (8 * j + (lane & 7)) * 128 + (((4 * sp + (lane >> 3)) ^ (lane & 7)) * 16));
#pragma unroll
                    for (int i = 0; i < 4; i++) {
                        mma16816(sc[i][j], qf[i][2 * sp], bf[0], bf[1]);
                        mma16816(sc[i][j], qf[i][2 * sp + 1], bf[2], bf[3]);
                    }
                }
#pragma unroll
            for (int i = 0; i < 4; i++)
#pragma unroll
                for (int j = 0; j < 4; j++)
                    *reinterpret_cast<float2*>(red + warp * 1024 + (8 * i + g) * 32 + ((8 * j) ^ (8 * (g & 3))) + 2 * t) =
                        make_float2(sc[i][j][0] + sc[i][j][2], sc[i][j][1] + sc[i][j][3]);
            __syncthreads();
            if (tid == 0 && n > BS_CKV) b_issue(p, n - 1 + BD, bi, sbase, pol);
            {
                float4 s = make_float4(0.f, 0.f, 0.f, 0.f);
#pragma unroll
                for (int w = 0; w < 8; w++) {
                    const float4 v = *reinterpret_cast<const float4*>(red + w * 1024 + head * 32 + ((4 * kq) ^ (8 * (head & 3))));
                    s.x += v.x; s.y += v.y; s.z += v.z; s.w += v.w;
                }
                const uint32_t r0 = pack_bf16(s.x, s.y), r1 = pack_bf16(s.z, s.w);
                const uint32_t s0 = pack_bf16(bf_lo(r0) * SCALE, bf_hi(r0) * SCALE);
                const uint32_t s1 = pack_bf16(bf_lo(r1) * SCALE, bf_hi(r1) * SCALE);
                const float f0 = bf_lo(s0), f1 = bf_hi(s0), f2 = bf_lo(s1), f3 = bf_hi(s1);
                float mx = fmaxf(fmaxf(f0, f1), fmaxf(f2, f3));
                mx = fmaxf(mx, __shfl_xor_sync(~0u, mx, 1));
                mx = fmaxf(mx, __shfl_xor_sync(~0u, mx, 2));
                mx = fmaxf(mx, __shfl_xor_sync(~0u, mx, 4));
                const float mnew = fmaxf(mrun, mx);
                const float al = expsub(mrun, mnew);
                const float p0 = expsub(f0, mnew), p1 = expsub(f1, mnew), p2 = expsub(f2, mnew), p3 = expsub(f3, mnew);
                lrun = lrun * al + ((p0 + p1) + (p2 + p3));
                mrun = mnew;
                *reinterpret_cast<uint2*>(smem + M_P + head * 80 + kq * 8) = make_uint2(pack_bf16(p0, p1), pack_bf16(p2, p3));
                if (kq == 0) alpha[head] = al;
            }
            __syncthreads();
            {
                uint32_t pf[2][2][4];
#pragma unroll
                for (int i = 0; i < 2; i++)
#pragma unroll
                    for (int ks = 0; ks < 2; ks++)
                        ldsm4(pf[i][ks], sbase + M_P + (16 * i + (lane & 15)) * 80 + (16 * ks + 8 * (lane >> 4)) * 2);
#pragma unroll
                for (int i = 0; i < 2; i++) {
                    const float a0 = alpha[16 * i + g], a1 = alpha[16 * i + 8 + g];
#pragma unroll
                    for (int j = 0; j < 8; j++) { acc[i][j][0] *= a0; acc[i][j][1] *= a0; acc[i][j][2] *= a1; acc[i][j][3] *= a1; }
                }
#pragma unroll
                for (int j = 0; j < 8; j++) {
                    uint32_t bf[4];
                    ldsm4t(bf, slot + warp * 4096 + lane * 128 + ((j ^ (lane & 7)) * 16));
#pragma unroll
                    for (int i = 0; i < 2; i++) {
                        mma16816(acc[i][j], pf[i][0], bf[0], bf[1]);
                        mma16816(acc[i][j], pf[i][1], bf[2], bf[3]);
                    }
                }
            }
        }
        __syncthreads();
        if (tid == 0) b_issue(p, BS_PART - 1 + BD, bi, sbase, pol);
        lrun += __shfl_xor_sync(~0u, lrun, 1);
        lrun += __shfl_xor_sync(~0u, lrun, 2);
        lrun += __shfl_xor_sync(~0u, lrun, 4);
        if (kq == 0) g_bml[head * NBCTA + bi] = make_float2(mrun, lrun);
#pragma unroll
        for (int i = 0; i < 2; i++)
#pragma unroll
            for (int j = 0; j < 8; j++) {
                g_bpart[((16 * i + g) * NBCTA + bi) * 256 + warp * 32 + j * 4 + t] = make_float2(acc[i][j][0], acc[i][j][1]);
                g_bpart[((16 * i + 8 + g) * NBCTA + bi) * 256 + warp * 32 + j * 4 + t] = make_float2(acc[i][j][2], acc[i][j][3]);
            }
    }
#pragma unroll 1
    for (int i = tid; i < NH * 36 && !(CLU); i += 256) g_outb[bi * NH * 36 + i] = make_uint4(0u, epoch, 0u, epoch);
    b_exchange(&ctl[C_BBAR + 1][0], BS_PART, &g_bpart[bi * NBCTA * 256], sbase, pol);
    {
        float* omega = reinterpret_cast<float*>(smem + M_OMEGA);
        if (warp == 0) {
            __syncwarp();
            const uint2 ml = ld_relaxed8(&g_bml[bi * NBCTA + lane]);
            const float ms = __uint_as_float(ml.x);
            float m = ms;
            m = fmaxf(m, __shfl_xor_sync(~0u, m, 1));
            m = fmaxf(m, __shfl_xor_sync(~0u, m, 2));
            m = fmaxf(m, __shfl_xor_sync(~0u, m, 4));
            const float w = expsub(ms, m);
            float l = w * __uint_as_float(ml.y);
            l += __shfl_xor_sync(~0u, l, 1);
            l += __shfl_xor_sync(~0u, l, 2);
            l += __shfl_xor_sync(~0u, l, 4);
            omega[lane] = w / l;
        }
        __syncthreads();
        b_wait(BS_PART, sbase);
        b_wait(BS_PART + 1, sbase);
#pragma unroll 1
        for (int b = 0; b < 4; b++) {
            const float2* ps = reinterpret_cast<const float2*>(smem + ((BS_PART + (b >> 1)) % BRING) * SLOT) + (b & 1) * 2048 + tid;
            float c0 = 0.f, c1 = 0.f;
#pragma unroll
            for (int s = 0; s < 8; s++) {
                const float w = omega[b * 8 + s];
                const float2 v = ps[s * 256];
                c0 = fmaf(w, v.x, c0);
                c1 = fmaf(w, v.y, c1);
            }
            const uint32_t hi = pack_bf16(c0, c1);
            *reinterpret_cast<uint32_t*>(smem + M_CH + b * CP + tid * 4) = hi;
            *reinterpret_cast<uint32_t*>(smem + M_CL + b * CP + tid * 4) = pack_bf16(c0 - bf_lo(hi), c1 - bf_hi(hi));
        }
        __syncthreads();
        if (tid == 0) { b_issue(p, BS_PART + BD, bi, sbase, pol); b_issue(p, BS_PART + 1 + BD, bi, sbase, pol); }
    }
    b_gemm(p, sbase, BS_WUV, BS_END, 512, sbase + M_CH, sbase + M_CL, CP, bi, pol);
    TS(12);
    if (CLU) {
        if (tid < 128) {
            const uint32_t xo = sbase + M_QB + ((tid >> 1) & 3) * QP + (tid >> 3) * 16 + (tid & 1) * 8;
            st_tagged2(&g_ctx[bi * 128 + tid], __uint_as_float(lds32(xo)), __uint_as_float(lds32(xo + 4)), epoch + 1);
        }
        return;
    }
    if (tid == 0) {
#pragma unroll 1
        for (int i = 0; i < 4; i++) {
            mbar_expect_tx(sbase + M_BAR + i * 8, 36864);
            tma3d(sbase + i * 36864, &p.tm_wo, 0, bi * 128 + i * 32, 0, sbase + M_BAR + i * 8, pol);
        }
    }
    TS(8);
    {
        float acc[9][4];
#pragma unroll
        for (int j = 0; j < 9; j++) { acc[j][0] = acc[j][1] = acc[j][2] = acc[j][3] = 0.f; }
#pragma unroll 1
        for (int i = 0; i < 4; i++) {
            const uint32_t xo = sbase + M_QB + (g & 3) * QP + i * 64 + t * 4;
            const uint32_t a0[4] = {lds32(xo), 0u, lds32(xo + 16), 0u}, a1[4] = {lds32(xo + 32), 0u, lds32(xo + 48), 0u};
            mbar_wait(sbase + M_BAR + i * 8, 0);
#pragma unroll
            for (int j = 0; j < 9; j++) {
                const int nt = warp * 9 + j;
                uint32_t w[4];
                ldsm4t(w, sbase + i * 36864 + (nt >> 3) * 4096 + lane * 128 + (((nt & 7) ^ (lane & 7)) * 16));
                mma16816(acc[j], a0, w[0], w[1]);
                mma16816(acc[j], a1, w[2], w[3]);
            }
        }
        if (g < 4) {
#pragma unroll
            for (int j = 0; j < 9; j++) {
                const int c2 = (warp * 9 + j) * 4 + t;
                st_tagged2(&g_outb[((c2 / 9) * NH + bi) * 36 + g * 9 + c2 % 9], acc[j][0], acc[j][1], epoch + 1);
            }
        }
    }
    TS(9);
    {
        const uint4* src = g_outb + (bi * NH + (tid >> 3)) * 36 + (tid & 7);
        float2* part = reinterpret_cast<float2*>(red);
        unsigned n = 0;
        while (true) {
            ulonglong2 v[5];
            bool ok = true;
#pragma unroll
            for (int i = 0; i < 5; i++)
                if (i < 4 || (tid & 7) < 4) v[i] = ld_tagged2(src + i * 8);
#pragma unroll
            for (int i = 0; i < 5; i++)
                if (i < 4 || (tid & 7) < 4) {
                    ok = ok && (unsigned)(v[i].x >> 32) == epoch + 1 && (unsigned)(v[i].y >> 32) == epoch + 1;
                    part[(tid >> 3) * 36 + (tid & 7) + i * 8] = make_float2(__uint_as_float((unsigned)v[i].x), __uint_as_float((unsigned)v[i].y));
                }
            if (ok) break;
            __nanosleep(400);
            if (++n > SPIN_LIMIT) __trap();
        }
        __syncthreads();
        if (tid < 36) {
            float s0 = 0.f, s1 = 0.f;
#pragma unroll 8
            for (int h = 0; h < NH; h++) { const float2 v = part[h * 36 + tid]; s0 += v.x; s1 += v.y; }
            *reinterpret_cast<uint32_t*>(p.out + (tid / 9) * 2 * DM + DM + bi * 18 + (tid % 9) * 2) = pack_bf16(s0, s1);
        }
    }
    TS(10);
}

template <bool CLU>
__global__ void __launch_bounds__(256, 1) fused_decode_kernel(const __grid_constant__ First f, const __grid_constant__ Params p) {
    extern __shared__ __align__(1024) char smem_raw[];
    const uint32_t sbase = (smem_u32(smem_raw) + 1023u) & ~1023u;
    char* smem = smem_raw + (sbase - smem_u32(smem_raw));
    const int tid = threadIdx.x, warp = tid >> 5, lane = tid & 31;
    asm volatile("{\n.reg .pred p;\nsetp.ne.u32 p, %1, 0;\n@p prefetch.global.L2 [%0];\n}"
                 ::"l"(f.ptr[tid >> 10] + (blockIdx.x * 8 + warp) * 8192 + lane * 128), "r"((uint32_t)(blockIdx.x < DM / 8 && lane < 16)) : "memory");
    const char* eptr = f.ptr[3 + (tid >> 10)];
    const int blk = CLU ? cluster_role(blockIdx.x) : blockIdx.x;
    const bool isB = CLU ? blk < NBCTA : (blk & 3) == 0 && (blk >> 2) < NBCTA;
    const int bi = CLU ? blk : blk >> 2;
    const int nb = CLU ? blk - NBCTA : blk - min(NBCTA, (blk + 3) >> 2);
    const int nblk = CLU ? 8 * MINCL : gridDim.x, nnb = nblk - NBCTA;
    const int nstatic = nnb * (NW + XW);
    uint64_t pol, poln;
    asm volatile("createpolicy.fractional.L2::evict_first.b64 %0, 1.0;" : "=l"(pol));
    asm volatile("createpolicy.fractional.L2::evict_normal.b64 %0, 1.0;" : "=l"(poln));
    const uint32_t wbar = sbase + M_BAR + warp * 8, wslot = sbase + warp * SLOT;
    const bool hold = blk < 16;
    const uint32_t jbar = sbase + M_BAR + (NSLOT + BRING) * 8, fbar = sbase + M_BAR + 4 * 8;
    if (warp < 4) {
        if (lane == 0) {
            if (warp == 0) {
                mbar_init(jbar, 1);
                asm volatile("fence.mbarrier_init.release.cluster;" ::: "memory");
                mbar_expect_tx(jbar, 36864 + 4 * 1152);
                if (CLU || blk < 128) tma3d(sbase + J0W, &p.tm_j0, blk * 32, 0, 0, jbar, poln);
            } else if (warp & 1) {
                if (warp & 2) {
#pragma unroll
                    for (int i = 0; i < NSLOT + BRING; i++) mbar_init(sbase + M_BAR + i * 8, 1);
                    mbar_expect_tx(fbar, NEARLY * TILE_BYTES);
                } else if (CLU && !isB) {
#pragma unroll
                    for (int i = 0; i < 2; i++) {
                        mbar_init(sbase + F_BAR + i * 8, 1);
                        mbar_expect_tx(sbase + F_BAR + i * 8, 1024);
                    }
                }
                asm volatile("fence.mbarrier_init.release.cluster;" ::: "memory");
            } else {
#pragma unroll
                for (int i = 0; i < 4; i++) asm volatile("st.shared.v4.u32 [%0], {%1,%1,%1,%1};" ::"r"(sbase + M_HELP + i * 16), "r"(0) : "memory");
            }
        }
    } else if (blockIdx.x >= DM / 8) {
        if (tid == 128) {
            asm volatile("prefetch.tensormap [%0];" ::"l"(&p.tm_j0) : "memory");
            asm volatile("prefetch.tensormap [%0];" ::"l"(&p.tm_wq) : "memory");
        } else if (blockIdx.x == DM / 8 + 4 && tid >= 220) {
            asm volatile("prefetch.global.L2 [%0];" ::"l"(f.ptr[2 + (tid >> 10)] + (tid - 220) * 128) : "memory");
        }
    }
    __syncthreads();
    if (tid == 128) {
        if (CLU || blk < 128) bulk_load(sbase + M_XA, f.ptr[2], 4608, jbar, poln);
        if (!isB && !hold) bulk_load(sbase, block_src(f.ptr[1], unit_block(nb * NEARLY)), NEARLY * TILE_BYTES, fbar, pol);
    }
    const int u0 = ((warp / NEARLY) * nnb + nb) * NEARLY + warp % NEARLY;
    unsigned epoch = 0;
    if (lane == 0) epoch = ld_relaxed4(eptr);
    TS(0);
    if (CLU && (unsigned)nb < NFIN) asm volatile("barrier.cluster.arrive.relaxed.aligned;" ::: "memory");
    if ((warp >> 1) == 2 && blk < 128) st_relaxed64(&g_qll[((tid - 128) >> 4) * 2048 + blk * 16 + (tid & 15)], 0ull);
    if (isB || warp >= NW + XW) epoch = __shfl_sync(~0u, epoch, 0);
    if (isB && tid == 96) {
        if (hold) { unsigned n = 0; while (ld_acquire_cta_shared(sbase + M_HELP + 24) < 2) { if (++n > (SPIN_LIMIT << 4)) __trap(); } }
#pragma unroll 1
        for (int b = 0; b < 4; b++) bulk_load(sbase + M_XB + b * XP, p.xb + b * DM, 1152, sbase + M_BAR + NSLOT * 8, pol);
#pragma unroll 1
        for (int n = 0; n < BD; n++) b_issue(p, n, bi, sbase, pol);
    }
    if (warp >= 4 && blk < 128) {
        const int g = lane >> 2, t = lane & 3, j = tid - 128;
#pragma unroll 1
        for (int sl = blk, ph = 0;; sl += 128 - nblk, ph = 1) {
        mbar_wait(jbar, ph);
        TS(13);
        float acc[4][4];
#pragma unroll
        for (int i = 0; i < 16; i++) acc[i >> 2][i & 3] = 0.f;
        const uint32_t wa = sbase + J0W + ((warp - 4) * 144 + (lane & 15)) * 64;
        const uint32_t sw = (lane >> 1) & 3, xa = sbase + M_XA + (g & 3) * 1152 + (warp - 4) * 288 + t * 4;
#pragma unroll 3
        for (int s = 0; s < 9; s++) {
            const uint32_t a[4] = {lds32(xa + s * 32), 0u, lds32(xa + s * 32 + 16), 0u};
            uint32_t w0[4], w1[4];
            ldsm4t(w0, wa + s * 1024 + (((lane >> 4) ^ sw) * 16));
            ldsm4t(w1, wa + s * 1024 + (((2 + (lane >> 4)) ^ sw) * 16));
            mma16816(acc[0], a, w0[0], w0[1]);
            mma16816(acc[1], a, w0[2], w0[3]);
            mma16816(acc[2], a, w1[0], w1[1]);
            mma16816(acc[3], a, w1[2], w1[3]);
        }
        float2* j0 = reinterpret_cast<float2*>(smem + M_J0);
        if (g < 4) {
#pragma unroll
            for (int i = 0; i < 4; i++) j0[(warp - 4) * 64 + g * 16 + i * 4 + t] = make_float2(acc[i][0], acc[i][1]);
        }
        asm volatile("bar.sync 1, 128;" ::: "memory");
        const bool again = sl == blk && blk + 128 - nblk >= nblk;
        if (again && tid == 224) {
            mbar_expect_tx(jbar, 36864);
            tma3d(sbase + J0W, &p.tm_j0, (blk + 128 - nblk) * 32, 0, 0, jbar, pol);
        }
        if (warp < 6) {
            const float2 v0 = j0[j], v1 = j0[64 + j], v2 = j0[128 + j], v3 = j0[192 + j];
            st_relaxed64(&g_qll[(j >> 4) * 2048 + sl * 16 + (j & 15)],
                         (unsigned long long)pack_bf16((v0.x + v1.x) + (v2.x + v3.x), (v0.y + v1.y) + (v2.y + v3.y)) |
                             ((unsigned long long)(epoch + 1) << 32));
            __syncwarp();
            if (lane == 0) asm volatile("red.relaxed.cta.shared::cta.add.u32 [%0], 1;" ::"r"(sbase + M_HELP + 24) : "memory");
        } else if (warp == 7) {
            if (blk < C_LINES) g_ctl[(epoch & 1) ^ 1][blk][lane] = 0;
        }
        TS(1);
        if (!again) break;
        asm volatile("bar.sync 1, 128;" ::: "memory");
        }
    }
    if (isB) {
        b_chain<CLU>(p, smem, sbase, bi, epoch, pol);
        return;
    }
    if (warp < NW + XW) {
        a_worker<CLU>(p, u0, warp >= NW + ((nb & 3) < (CLU ? X3C : X3) ? 1 : 0), hold, nstatic, wslot, wbar, warp < NEARLY && !hold ? fbar : wbar,
                      sbase + M_HELP, epoch, pol);
        if (CLU && nb < NFIN) {
            if (warp == 3) out_issue_sum(p, sbase, nb >> 3, nb & 7, pol);
            else if (warp == 0) out_late(sbase, nb & 7);
        }
        return;
    } else if (warp == 7) {
#pragma unroll 1
        for (int i = nb; i < 4 * NH; i += nnb) g_oacc[i * 32 + lane] = make_float4(0.f, 0.f, 0.f, 0.f);
        if (nb < NREP * NH) g_vdone[nb][lane] = 0;
        __syncwarp();
        k_helper(sbase + M_HELP, epoch);
        if (nb == 0 && lane == 0) g_epoch = epoch + 1;
        __syncwarp();
        if (CLU && nb < NFIN) out_early(sbase, nb & 7, epoch + 1);
    } else if (CLU) {
    } else if (warp == 6 && nb < NFIN) {
        finisher(p, sbase, nb);
        TS(4);
    } else if (warp >= 6 - NPOLL && nb < NFIN) {
        v_poller(sbase, nb, warp - (6 - NPOLL));
    }
    if (CLU && nb < NFIN) out_project(sbase, nb & 7, warp - 4);
}

}

typedef CUresult (*EncodeFn)(CUtensorMap*, CUtensorMapDataType, cuuint32_t, void*, const cuuint64_t*, const cuuint64_t*,
                             const cuuint32_t*, const cuuint32_t*, CUtensorMapInterleave, CUtensorMapSwizzle,
                             CUtensorMapL2promotion, CUtensorMapFloatOOBfill);

extern "C" void kernel_launch(void* const* d_in, const int* in_sizes, int n_in, void* d_out, int out_size) {
    (void)in_sizes; (void)n_in; (void)out_size;
    static int nsm = 0, ncl = 0;
    static EncodeFn encode = nullptr;
    static const char* epoch_ptr = nullptr;
    cudaLaunchConfig_t cfg = {};
    cudaLaunchAttribute at[1];
    at[0].id = cudaLaunchAttributeClusterDimension;
    at[0].val.clusterDim.x = 8; at[0].val.clusterDim.y = 1; at[0].val.clusterDim.z = 1;
    cfg.blockDim = dim3(256); cfg.dynamicSmemBytes = SMEM_BYTES; cfg.stream = cudaStreamPerThread; cfg.attrs = at; cfg.numAttrs = 1;
    if (nsm == 0) {
        int dev = 0;
        cudaGetDevice(&dev);
        cudaDeviceGetAttribute(&nsm, cudaDevAttrMultiProcessorCount, dev);
        cudaFuncSetAttribute(fused_decode_kernel<false>, cudaFuncAttributeMaxDynamicSharedMemorySize, SMEM_BYTES);
        cudaFuncSetAttribute(fused_decode_kernel<true>, cudaFuncAttributeMaxDynamicSharedMemorySize, SMEM_BYTES);
        cfg.gridDim = dim3(128);
        if (cudaOccupancyMaxActiveClusters(&ncl, fused_decode_kernel<true>, &cfg) != cudaSuccess) { ncl = 0; (void)cudaGetLastError(); }
        if (ncl > MINCL) ncl = MINCL;
        cudaGetSymbolAddress((void**)&epoch_ptr, g_epoch);
        void* fn = nullptr;
        cudaDriverEntryPointQueryResult qr;
        cudaGetDriverEntryPoint("cuTensorMapEncodeTiled", &fn, cudaEnableDefault, &qr);
        encode = (EncodeFn)fn;
    }
    Params p;
    auto panels = [&](CUtensorMap* tm, void* ptr, int rows, int cols, int box_rows, int box_panels) {
        const cuuint64_t gd[3] = {64, (cuuint64_t)rows, (cuuint64_t)(cols / 64)}, gs[2] = {(cuuint64_t)cols * 2, 128};
        const cuuint32_t box[3] = {64, (cuuint32_t)box_rows, (cuuint32_t)box_panels}, es[3] = {1, 1, 1};
        encode(tm, CU_TENSOR_MAP_DATA_TYPE_BFLOAT16, 3, ptr, gd, gs, box, es, CU_TENSOR_MAP_INTERLEAVE_NONE,
               CU_TENSOR_MAP_SWIZZLE_128B, CU_TENSOR_MAP_L2_PROMOTION_L2_256B, CU_TENSOR_MAP_FLOAT_OOB_FILL_NONE);
    };
    panels(&p.tm_wq, d_in[7], DM, 4096, 128, 2);
    panels(&p.tm_wuk, d_in[8], 512, 4096, 128, 2);
    panels(&p.tm_wuv, d_in[9], 512, 4096, 128, 2);
    panels(&p.tm_wo, d_in[10], 4096, DM, 32, 9);
    panels(&p.tm_wf, d_in[10], 4096, DM, 128, 1);
    panels(&p.tm_ckv, d_in[6], 4 * SK, 512, 32, 8);
    {
        const cuuint64_t gd[3] = {4096, 192, 3}, gs[2] = {8192, 192 * 8192};
        const cuuint32_t box[3] = {32, 192, 3}, es[3] = {1, 1, 1};
        encode(&p.tm_j0, CU_TENSOR_MAP_DATA_TYPE_BFLOAT16, 3, d_in[3], gd, gs, box, es, CU_TENSOR_MAP_INTERLEAVE_NONE,
               CU_TENSOR_MAP_SWIZZLE_64B, CU_TENSOR_MAP_L2_PROMOTION_L2_128B, CU_TENSOR_MAP_FLOAT_OOB_FILL_NONE);
    }
    {
        const cuuint64_t gd[3] = {DM, 512, 8}, gs[2] = {8 * DM * 2, DM * 2};
        const cuuint32_t box[3] = {64, 16, 8}, es[3] = {1, 1, 1};
        encode(&p.tm_wl, CU_TENSOR_MAP_DATA_TYPE_BFLOAT16, 3, d_in[4], gd, gs, box, es, CU_TENSOR_MAP_INTERLEAVE_NONE,
               CU_TENSOR_MAP_SWIZZLE_128B, CU_TENSOR_MAP_L2_PROMOTION_L2_256B, CU_TENSOR_MAP_FLOAT_OOB_FILL_NONE);
    }
    p.kc = (const __nv_bfloat16*)d_in[1];
    p.vc = (const __nv_bfloat16*)d_in[2];
    p.wo = (const __nv_bfloat16*)d_in[4];
    p.xb = (const __nv_bfloat16*)d_in[5];
    p.out = (__nv_bfloat16*)d_out;
    const First f = {{(const char*)d_in[3], (const char*)d_in[1], (const char*)d_in[0], epoch_ptr}};
    if (ncl >= MINCL) {
        cfg.gridDim = dim3(8 * ncl);
        cudaLaunchKernelEx(&cfg, fused_decode_kernel<true>, f, p);
    } else {
        fused_decode_kernel<false><<<nsm, 256, SMEM_BYTES, cudaStreamPerThread>>>(f, p);
    }
}
```

```cpp
#include <cuda_runtime.h>
#include <cuda.h>
#include <cuda_bf16.h>
#include <stdint.h>

namespace {

constexpr int NH = 32, SK = 4096, DM = 576;
constexpr int KEYS = 128;
constexpr int UPP = SK / KEYS;
constexpr int NUK = 4 * NH * UPP;
constexpr int TILE_BYTES = KEYS * 256;
#define NWORK 2
constexpr int NW = NWORK;
constexpr int NBCTA = 32;
constexpr int MINCL = 15;
constexpr int NFIN = 72;
constexpr int SLOT = 32768;
constexpr int NSLOT = 6;
constexpr int BRING = 5;
constexpr int J0W = 5 * SLOT;
constexpr int MISC = NSLOT * SLOT + 4096;
constexpr int XP = 1168, CP = 1040, QP = 272;
constexpr int M_XA = MISC;
constexpr int M_XB = M_XA + 4 * XP;
constexpr int M_CH = M_XB + 4 * XP;
constexpr int M_CL = M_CH + 4 * CP;
constexpr int M_QB = M_CL + 4 * CP;
constexpr int M_QA = M_CH;
constexpr int M_J0 = M_QB + 4 * QP;
constexpr int M_P = M_J0 + 2048;
constexpr int M_ALPHA = M_P + 2560;
constexpr int M_OMEGA = M_ALPHA + 128;
constexpr int M_BAR = M_OMEGA + 128;
constexpr int M_HELP = M_BAR + 128;
constexpr int F_W = 3 * SLOT;
constexpr int F_X = NSLOT * SLOT, FXP = 1088;
constexpr int F_RECV = F_X + 8 * FXP;
constexpr int F_BAR = M_P;
constexpr int SMEM_BYTES = M_HELP + 128 + 1024;
static_assert(F_RECV + 2048 <= M_J0, "output phase layout");
static_assert(SMEM_BYTES <= 232448 && M_BAR % 8 == 0 && M_QA % 16 == 0 && M_P % 16 == 0, "smem layout");
#define XW 2
#define X3 2
#define X3C 3
#define NEARLY 2
#define BD 5
#define FPF 3
#define FSLEEP 800
#define FJ 250
#define FP 384
#define NPOLL 2
#define PGAP 200
static_assert(NW + XW == 4 && 4 % NEARLY == 0 && BD <= BRING, "slots 4 and 5 hold the finisher weights");
constexpr float SCALE = 0.08838834764831845f;
constexpr float LOG2E = 1.4426950408889634f;
constexpr unsigned SPIN_LIMIT = 1u << 24;

#define NREP 2
constexpr int C_QUEUE = 0, C_KDONE = 1, C_BBAR = 3, C_LINES = 5;

struct First { const char* ptr[4]; };
struct Params {
    const __nv_bfloat16 *kc, *vc, *wo, *xb;
    __nv_bfloat16* out;
    CUtensorMap tm_j0;
    CUtensorMap tm_wq, tm_wuk, tm_ckv, tm_wuv, tm_wo;
    CUtensorMap tm_wl;
    CUtensorMap tm_wf;
};

__device__ unsigned g_epoch;
__device__ unsigned g_ctl[2][C_LINES][32];
__device__ uint2 g_qll[4 * 2048];
__device__ uint2 g_scores[128 * SK / 4];
__device__ float2 g_stats[128 * UPP];
__device__ float4 g_oacc[128 * 32];
__device__ unsigned g_vdone[NREP * NH][32];
__device__ uint4 g_qabs[4 * 8 * 4 * 4 * 32];
__device__ float2 g_bpart[NBCTA * NH * 256];
__device__ float2 g_bml[NBCTA * NH];
__device__ uint4 g_ctx[NH * 128];
__device__ uint4 g_outb[NBCTA * NH * 36];

__device__ __forceinline__ int cluster_role(int b) {
    const int i = b - NFIN, q = ((i >> 1) * 43 >> 7) * 2, r = i - 3 * q;
    int x = i - q;
    asm("{\n.reg .pred p;\nsetp.ge.s32 p, %1, 4;\nselp.s32 %0, %2, %0, p;\nsetp.lt.s32 p, %3, 0;\nselp.s32 %0, %4, %0, p;\n}"
        : "+r"(x) : "r"(r), "r"(NBCTA + NFIN - 4 + q + r), "r"(i), "r"(b + NBCTA));
    return x;
}

#define TS(i)
#define TSV(i, v)
#define LAND(i)
#define CLK(x)
#define ACC(a, x, y)

__device__ __forceinline__ uint32_t smem_u32(const void* p) { return (uint32_t)__cvta_generic_to_shared(p); }
__device__ __forceinline__ void mbar_init(uint32_t bar, uint32_t cnt) {
    asm volatile("mbarrier.init.shared::cta.b64 [%0], %1;" ::"r"(bar), "r"(cnt) : "memory");
}
__device__ __forceinline__ void mbar_expect_tx(uint32_t bar, uint32_t bytes) {
    asm volatile("mbarrier.arrive.expect_tx.shared::cta.b64 _, [%0], %1;" ::"r"(bar), "r"(bytes) : "memory");
}
__device__ __forceinline__ bool mbar_try(uint32_t bar, uint32_t parity) {
    uint32_t ok;
    asm volatile("{\n.reg .pred p;\nmbarrier.try_wait.parity.shared::cta.b64 p, [%1], %2;\nselp.u32 %0, 1, 0, p;\n}\n"
                 : "=r"(ok) : "r"(bar), "r"(parity) : "memory");
    return ok;
}
__device__ __forceinline__ void mbar_wait(uint32_t bar, uint32_t parity) {
    unsigned n = 0;
    while (!mbar_try(bar, parity)) { if (++n > SPIN_LIMIT) __trap(); }
}
__device__ __forceinline__ void bulk_load(uint32_t dst, const void* src, uint32_t bytes, uint32_t bar, uint64_t pol) {
    asm volatile("cp.async.bulk.shared::cluster.global.mbarrier::complete_tx::bytes.L2::cache_hint [%0], [%1], %2, [%3], %4;"
                 ::"r"(dst), "l"(src), "r"(bytes), "r"(bar), "l"(pol) : "memory");
}
__device__ __forceinline__ void tma3d(uint32_t dst, const CUtensorMap* tm, int c0, int c1, int c2, uint32_t bar, uint64_t pol) {
    asm volatile("cp.async.bulk.tensor.3d.shared::cluster.global.mbarrier::complete_tx::bytes.L2::cache_hint [%0], [%1, {%3,%4,%5}], [%2], %6;"
                 ::"r"(dst), "l"(tm), "r"(bar), "r"(c0), "r"(c1), "r"(c2), "l"(pol) : "memory");
}
__device__ __forceinline__ void l2_prefetch(const void* src, uint32_t bytes) {
    asm volatile("cp.async.bulk.prefetch.L2.global [%0], %1;" ::"l"(src), "r"(bytes) : "memory");
}
__device__ __forceinline__ void ldsm4(uint32_t (&r)[4], uint32_t addr) {
    asm volatile("ldmatrix.sync.aligned.m8n8.x4.shared.b16 {%0,%1,%2,%3}, [%4];"
                 : "=r"(r[0]), "=r"(r[1]), "=r"(r[2]), "=r"(r[3]) : "r"(addr));
}
__device__ __forceinline__ void ldsm4t(uint32_t (&r)[4], uint32_t addr) {
    asm volatile("ldmatrix.sync.aligned.m8n8.x4.trans.shared.b16 {%0,%1,%2,%3}, [%4];"
                 : "=r"(r[0]), "=r"(r[1]), "=r"(r[2]), "=r"(r[3]) : "r"(addr));
}
__device__ __forceinline__ void mma16816(float (&d)[4], const uint32_t (&a)[4], uint32_t b0, uint32_t b1) {
    asm("mma.sync.aligned.m16n8k16.row.col.f32.bf16.bf16.f32 {%0,%1,%2,%3}, {%4,%5,%6,%7}, {%8,%9}, {%0,%1,%2,%3};"
        : "+f"(d[0]), "+f"(d[1]), "+f"(d[2]), "+f"(d[3])
        : "r"(a[0]), "r"(a[1]), "r"(a[2]), "r"(a[3]), "r"(b0), "r"(b1));
}
__device__ __forceinline__ void wgmma_tile(float (&d)[4], uint32_t da, uint32_t db, int accumulate) {
    asm volatile("{\n.reg .pred p;\n.reg .b32 x, y;\n.reg .b64 a, b;\nsetp.ne.u32 p, %6, 0;\nwgmma.fence.sync.aligned;\n"
                 "add.u32 x, %4, 0;\nadd.u32 y, %5, 0;\nmov.b64 a, {x, 0x40000040};\nmov.b64 b, {y, 1};\n"
                 "wgmma.mma_async.sync.aligned.m64n8k16.f32.bf16.bf16 {%0,%1,%2,%3}, a, b, p, 1, 1, 1, 0;\n"
                 "add.u32 x, %4, 128;\nadd.u32 y, %5, 8;\nmov.b64 a, {x, 0x40000040};\nmov.b64 b, {y, 1};\n"
                 "wgmma.mma_async.sync.aligned.m64n8k16.f32.bf16.bf16 {%0,%1,%2,%3}, a, b, 1, 1, 1, 1, 0;\n"
                 "add.u32 x, %4, 256;\nadd.u32 y, %5, 16;\nmov.b64 a, {x, 0x40000040};\nmov.b64 b, {y, 1};\n"
                 "wgmma.mma_async.sync.aligned.m64n8k16.f32.bf16.bf16 {%0,%1,%2,%3}, a, b, 1, 1, 1, 1, 0;\n"
                 "add.u32 x, %4, 384;\nadd.u32 y, %5, 24;\nmov.b64 a, {x, 0x40000040};\nmov.b64 b, {y, 1};\n"
                 "wgmma.mma_async.sync.aligned.m64n8k16.f32.bf16.bf16 {%0,%1,%2,%3}, a, b, 1, 1, 1, 1, 0;\n"
                 "add.u32 x, %4, 512;\nadd.u32 y, %5, 32;\nmov.b64 a, {x, 0x40000040};\nmov.b64 b, {y, 1};\n"
                 "wgmma.mma_async.sync.aligned.m64n8k16.f32.bf16.bf16 {%0,%1,%2,%3}, a, b, 1, 1, 1, 1, 0;\n"
                 "add.u32 x, %4, 640;\nadd.u32 y, %5, 40;\nmov.b64 a, {x, 0x40000040};\nmov.b64 b, {y, 1};\n"
                 "wgmma.mma_async.sync.aligned.m64n8k16.f32.bf16.bf16 {%0,%1,%2,%3}, a, b, 1, 1, 1, 1, 0;\n"
                 "add.u32 x, %4, 768;\nadd.u32 y, %5, 48;\nmov.b64 a, {x, 0x40000040};\nmov.b64 b, {y, 1};\n"
                 "wgmma.mma_async.sync.aligned.m64n8k16.f32.bf16.bf16 {%0,%1,%2,%3}, a, b, 1, 1, 1, 1, 0;\n"
                 "add.u32 x, %4, 896;\nadd.u32 y, %5, 56;\nmov.b64 a, {x, 0x40000040};\nmov.b64 b, {y, 1};\n"
                 "wgmma.mma_async.sync.aligned.m64n8k16.f32.bf16.bf16 {%0,%1,%2,%3}, a, b, 1, 1, 1, 1, 0;\n"
                 "wgmma.commit_group.sync.aligned;\n}"
                 : "+f"(d[0]), "+f"(d[1]), "+f"(d[2]), "+f"(d[3]) : "r"(da), "r"(db), "r"(accumulate) : "memory");
}
__device__ __forceinline__ uint32_t lds32(uint32_t a) {
    uint32_t v;
    asm volatile("ld.shared.u32 %0, [%1];" : "=r"(v) : "r"(a));
    return v;
}
__device__ __forceinline__ unsigned ld_acquire(const unsigned* p) {
    unsigned v;
    asm volatile("ld.acquire.gpu.global.u32 %0, [%1];" : "=r"(v) : "l"(p) : "memory");
    return v;
}
__device__ __forceinline__ uint2 ld_relaxed8(const void* p) {
    uint2 v;
    asm volatile("ld.relaxed.gpu.global.v2.u32 {%0,%1}, [%2];" : "=r"(v.x), "=r"(v.y) : "l"(p) : "memory");
    return v;
}
__device__ __forceinline__ unsigned ld_relaxed4(const void* p) {
    unsigned v;
    asm volatile("ld.relaxed.gpu.global.u32 %0, [%1];" : "=r"(v) : "l"(p) : "memory");
    return v;
}
__device__ __forceinline__ unsigned atom_inc(unsigned* p) {
    unsigned v;
    asm volatile("atom.relaxed.gpu.global.inc.u32 %0, [%1], 0x7fffffff;" : "=r"(v) : "l"(p) : "memory");
    return v;
}
__device__ __forceinline__ unsigned long long ld_relaxed64(const void* p) {
    unsigned long long v;
    asm volatile("ld.relaxed.gpu.global.u64 %0, [%1];" : "=l"(v) : "l"(p) : "memory");
    return v;
}
__device__ __forceinline__ void st_relaxed64(void* p, unsigned long long v) {
    asm volatile("st.relaxed.gpu.global.u64 [%0], %1;" ::"l"(p), "l"(v) : "memory");
}
__device__ __forceinline__ float4 ld_relaxed16(const void* p) {
    float4 v;
    asm volatile("ld.relaxed.gpu.global.v4.f32 {%0,%1,%2,%3}, [%4];" : "=f"(v.x), "=f"(v.y), "=f"(v.z), "=f"(v.w) : "l"(p) : "memory");
    return v;
}
__device__ __forceinline__ uint32_t mapa(uint32_t a, uint32_t rank) {
    uint32_t r;
    asm("mapa.shared::cluster.u32 %0, %1, %2;" : "=r"(r) : "r"(a), "r"(rank));
    return r;
}
__device__ __forceinline__ void mbar_first(uint32_t bar) {
    asm volatile("{\n.reg .pred p, q;\n.reg .u32 n;\nmov.u32 n, 0;\n"
                 "SPIN:\nmbarrier.try_wait.parity.shared::cta.b64 p, [%0], 0;\nadd.u32 n, n, 1;\nsetp.gt.u32 q, n, 0x1000000;\n@q trap;\n"
                 "@!p bra.uni SPIN;\n}" ::"r"(bar) : "memory");
}
__device__ __forceinline__ void mbar_first_cluster(uint32_t bar) {
    asm volatile("{\n.reg .pred p, q;\n.reg .u32 n;\nmov.u32 n, 0;\n"
                 "SPIN:\nmbarrier.try_wait.parity.relaxed.cluster.shared::cta.b64 p, [%0], 0;\nadd.u32 n, n, 1;\nsetp.gt.u32 q, n, 0x1000000;\n@q trap;\n"
                 "@!p bra.uni SPIN;\nfence.acquire.sync_restrict::shared::cluster.cluster;\n}" ::"r"(bar) : "memory");
}
__device__ __forceinline__ uint32_t now_ns() {
    unsigned long long t;
    asm volatile("mov.u64 %0, %globaltimer;" : "=l"(t));
    return (uint32_t)t;
}
__device__ __forceinline__ void fence_gpu() { asm volatile("fence.acq_rel.gpu;" ::: "memory"); }
__device__ __forceinline__ void red_add_u32(unsigned* p, unsigned v) {
    asm volatile("red.relaxed.gpu.global.add.u32 [%0], %1;" ::"l"(p), "r"(v) : "memory");
}
__device__ __forceinline__ void st_tagged2(void* p, float a, float b, unsigned tag) {
    const unsigned long long hi = (unsigned long long)tag << 32;
    asm volatile("st.relaxed.gpu.global.v2.b64 [%0], {%1,%2};" ::"l"(p), "l"(hi | __float_as_uint(a)), "l"(hi | __float_as_uint(b)) : "memory");
}
__device__ __forceinline__ ulonglong2 ld_tagged2(const void* p) {
    ulonglong2 v;
    asm volatile("ld.relaxed.gpu.global.v2.b64 {%0,%1}, [%2];" : "=l"(v.x), "=l"(v.y) : "l"(p) : "memory");
    return v;
}
__device__ __forceinline__ float4 atom_add_f4(void* p, float a, float b, float c, float d) {
    float4 r;
    asm volatile("atom.relaxed.gpu.global.add.v4.f32 {%0,%1,%2,%3}, [%4], {%5,%6,%7,%8};"
                 : "=f"(r.x), "=f"(r.y), "=f"(r.z), "=f"(r.w) : "l"(p), "f"(a), "f"(b), "f"(c), "f"(d) : "memory");
    return r;
}
__device__ __forceinline__ void red_release_cta_shared(uint32_t a, unsigned v) {
    asm volatile("red.release.cta.shared::cta.add.u32 [%0], %1;" ::"r"(a), "r"(v) : "memory");
}
__device__ __forceinline__ unsigned ld_acquire_cta_shared(uint32_t a) {
    unsigned v;
    asm volatile("ld.acquire.cta.shared::cta.u32 %0, [%1];" : "=r"(v) : "r"(a) : "memory");
    return v;
}
__device__ __forceinline__ void st_release_cta_shared(uint32_t a, unsigned v) {
    asm volatile("st.release.cta.shared::cta.u32 [%0], %1;" ::"r"(a), "r"(v) : "memory");
}
__device__ __forceinline__ void wait_count(const unsigned* p, unsigned target) {
    unsigned n = 0;
    while (ld_acquire(p) < target) { if (++n > SPIN_LIMIT) __trap(); }
}
__device__ __forceinline__ uint32_t pack_bf16(float lo, float hi) {
    uint32_t r;
    asm("cvt.rn.bf16x2.f32 %0, %1, %2;" : "=r"(r) : "f"(hi), "f"(lo));
    return r;
}
__device__ __forceinline__ float bf_lo(uint32_t v) { return __uint_as_float(v << 16); }
__device__ __forceinline__ float bf_hi(uint32_t v) { return __uint_as_float(v & 0xffff0000u); }
__device__ __forceinline__ float ex2(float x) { float y; asm("ex2.approx.ftz.f32 %0, %1;" : "=f"(y) : "f"(x)); return y; }
__device__ __forceinline__ float expsub(float a, float b) { return ex2((a - b) * LOG2E); }
__device__ __forceinline__ float warp_max(float v) {
#pragma unroll
    for (int m = 16; m; m >>= 1) v = fmaxf(v, __shfl_xor_sync(~0u, v, m));
    return v;
}
__device__ __forceinline__ float warp_sum(float v) {
#pragma unroll
    for (int m = 16; m; m >>= 1) v += __shfl_xor_sync(~0u, v, m);
    return v;
}
__device__ __forceinline__ unsigned unit_block(int u) {
    const unsigned v = u & (NUK - 1);
    return u < NUK ? (v & ~0x78u) | (v & 0x18u) << 2 | (v & 0x60u) >> 2 : v;
}
__device__ __forceinline__ const char* block_src(const void* base, unsigned blk) {
    const unsigned po = blk / UPP;
    return reinterpret_cast<const char*>(base) + (size_t)(((po & 3) * NH + (po >> 2)) * UPP + blk % UPP) * TILE_BYTES;
}

template <bool CLU>
__device__ __forceinline__ void a_worker(const Params& p, int un, bool once, bool hold, int nstatic, uint32_t slot, uint32_t bar, uint32_t wb,
                                         uint32_t help, unsigned epoch, uint64_t pol) {
    constexpr int NU = 2 * NUK;
    const int lane = threadIdx.x & 31, g = lane >> 2, t = lane & 3;
    const int li = lane & 7;
    uint32_t kaddr[4], vaddr[8];
    {
        const int e = (lane >> 3) & 1, kk = lane >> 4;
#pragma unroll
        for (int s = 0; s < 4; s++) kaddr[s] = slot + (16 * li + e) * 256 + ((2 * s + kk + li) & 7) * 16;
        const int vrow = 4 * (li >> 1) + (li & 1) + 2 * kk;
#pragma unroll
        for (int c = 0; c < 8; c++) vaddr[c] = slot + vrow * 256 + e * 128 + ((c + li) & 7) * 16;
#pragma unroll
        for (int c = 0; c < 8; c++) asm volatile("" : "+r"(vaddr[c]));
    }
    const uint32_t vmask = (g >> 1) != t ? 0u : ((g & 1) ? 0xffff0000u : 0xffffu);
    int kseen = -1;
    unsigned long long H0 = 0, H1 = 0;
    auto header = [&](int v, unsigned vb) {
        if (v >= NU) return;
        const void *a0, *a1;
        if (v < NUK) {
            const unsigned po = vb / UPP;
            a0 = g_qll + (po & 3) * 2048 + (po >> 2) * 64 + lane;
            a1 = reinterpret_cast<const uint2*>(a0) + 32;
        } else {
            const int half = vb / (NUK / 2);
            if (half > kseen) {
                unsigned n = 0;
                while (ld_acquire_cta_shared(help + 12 + 4 * half) == 0) { if (++n > (SPIN_LIMIT << 4)) __trap(); }
                kseen = half;
            }
            a0 = &g_scores[vb * (KEYS / 4) + lane];
            a1 = &g_stats[(vb / UPP) * UPP + lane];
        }
        H0 = ld_relaxed64(a0);
        H1 = ld_relaxed64(a1);
    };
    epoch = __shfl_sync(~0u, epoch, 0);
    if (hold) { unsigned n = 0; while (ld_acquire_cta_shared(help + 24) < 2) { if (++n > (SPIN_LIMIT << 4)) __trap(); } }
    unsigned (*ctl)[32] = g_ctl[epoch & 1];
    const unsigned tag = epoch + 1;
    unsigned nxt = once ? NU : 0;
    int u = -1;
    unsigned bu = 0, bn = unit_block(un);
    bool have = false;
    uint32_t phase = 0;
    unsigned kpend = 0;
    const unsigned zero = gridDim.x >> 24;
    uint32_t Q[16];
    float4 oret = make_float4(0.f, 0.f, 0.f, 0.f);
    while (true) {
        const char* nsrc = block_src(un < NUK ? p.kc : p.vc, bn);
        float4* odst = &g_oacc[(bu / UPP) * 32 + lane];
        unsigned* vdst = &g_vdone[(lane & (NREP - 1)) * NH + bu / (4 * UPP)][0];
        float d[8][4];
        CLK(c1);
        asm volatile("" : "+l"(odst));
        if (u >= NUK) {
#pragma unroll
            for (int j = 0; j < 8; j++) { d[j][0] = d[j][1] = d[j][2] = d[j][3] = 0.f; }
            mbar_wait(wb, phase);
            LAND(NUK + bu);
            uint32_t a[2][8][4];
#pragma unroll
            for (int c = 0; c < 8; c++) ldsm4t(a[0][c], vaddr[c]);
#pragma unroll
            for (int j = 0; j < 8; j++) {
                if (j < 7) {
#pragma unroll
                    for (int c = 0; c < 8; c++) ldsm4t(a[(j + 1) & 1][c], vaddr[c] + (j + 1) * 4096);
                }
#pragma unroll
                for (int c = 0; c < 8; c++) mma16816(d[c], a[j & 1][c], Q[2 * j], Q[2 * j + 1]);
            }
            float o[4];
#pragma unroll
            for (int r = 0; r < 2; r++) {
                o[2 * r] = d[0][2 * r] + d[7][2 * r + 1];
                o[2 * r + 1] = d[0][2 * r + 1] + d[1][2 * r];
#pragma unroll
                for (int k = 1; k < 4; k++) {
                    const int src = (lane & 28) | ((t - k) & 3);
                    o[2 * r] += __shfl_sync(~0u, d[2 * k][2 * r] + d[2 * k - 1][2 * r + 1], src);
                    o[2 * r + 1] += __shfl_sync(~0u, d[2 * k][2 * r + 1] + d[2 * k + 1][2 * r], src);
                }
            }
            oret = atom_add_f4(odst, o[0], o[1], o[2], o[3]);
        } else if (u >= 0) {
#pragma unroll
            for (int j = 0; j < 8; j++) { d[j][0] = d[j][1] = d[j][2] = d[j][3] = 0.f; }
            mbar_wait(wb, phase);
            LAND(bu);
            uint32_t a[2][8][4];
#pragma unroll
            for (int j = 0; j < 8; j++) ldsm4(a[0][j], kaddr[0] + (4 * (j & 3) + 2 * (j >> 2)) * 256);
#pragma unroll
            for (int s = 0; s < 8; s++) {
                if (s < 7) {
#pragma unroll
                    for (int j = 0; j < 8; j++)
                        ldsm4(a[(s + 1) & 1][j], kaddr[(s + 1) & 3] + (4 * (j & 3) + 2 * (j >> 2)) * 256 + ((s + 1) >> 2) * 128);
                }
#pragma unroll
                for (int j = 0; j < 8; j++)
                    mma16816(d[j], a[s & 1][j], Q[(s & 4) * 2 + ((2 * s - 2 * j) & 7)], Q[(s & 4) * 2 + ((2 * s + 1 - 2 * j) & 7)]);
            }
        }
        const bool pre = wb != bar;
        if (u >= 0) { phase = pre ? 0 : phase ^ 1; wb = bar; }
        CLK(c2b);
        if (un < NU && lane == 0) {
            if (!once) nxt = atom_inc(&ctl[C_QUEUE][0]);
            if (u >= 0 || !pre) {
                mbar_expect_tx(bar, TILE_BYTES);
                bulk_load(slot, nsrc, TILE_BYTES, bar, pol);
            }
        }
        const uint32_t tiss = now_ns();
        CLK(c3);
        if ((unsigned)u < (unsigned)NUK) {
            const int j0 = (t - (g >> 1)) & 3;
            float v[4];
#pragma unroll
            for (int q = 0; q < 4; q++) {
                const int jq = (q >> 1) * 4, e = (q & 1) * 2;
                const float x0 = (g & 1) ? d[jq + 0][e + 1] : d[jq + 0][e];
                const float x1 = (g & 1) ? d[jq + 1][e + 1] : d[jq + 1][e];
                const float x2 = (g & 1) ? d[jq + 2][e + 1] : d[jq + 2][e];
                const float x3 = (g & 1) ? d[jq + 3][e + 1] : d[jq + 3][e];
                const float y0 = (j0 & 1) ? x1 : x0, y1 = (j0 & 1) ? x3 : x2;
                v[q] = (j0 & 2) ? y1 : y0;
            }
            const uint32_t r0 = pack_bf16(v[0], v[1]), r1 = pack_bf16(v[2], v[3]);
            const uint32_t s0 = pack_bf16(bf_lo(r0) * SCALE, bf_hi(r0) * SCALE);
            const uint32_t s1 = pack_bf16(bf_lo(r1) * SCALE, bf_hi(r1) * SCALE);
            g_scores[bu * (KEYS / 4) + 4 * g + j0] = make_uint2(s0, s1);
            const float f0 = bf_lo(s0), f1 = bf_hi(s0), f2 = bf_lo(s1), f3 = bf_hi(s1);
            const float m = warp_max(fmaxf(fmaxf(f0, f1), fmaxf(f2, f3)));
            const float l = warp_sum((expsub(f0, m) + expsub(f1, m)) + (expsub(f2, m) + expsub(f3, m)));
            if (lane == 0) g_stats[bu] = make_float2(m, l);
            kpend++;
            if (un / (NUK / 2) != u / (NUK / 2)) {
                __syncwarp();
                if (lane == 0) {
                    red_release_cta_shared(help + 4 * (u / (NUK / 2)), kpend);
                    if (un >= NUK) red_release_cta_shared(help + 8, 1u);
                }
                kpend = 0;
            }
        }
        CLK(c4);
        int unn = NU;
        if (un < NU) {
            unsigned n = 0;
            while (true) {
                if (!have) header(un, bn);
                if (un >= NUK || __all_sync(~0u, (uint32_t)(H0 >> 32) == tag && (uint32_t)(H1 >> 32) == tag)) break;
                if (++n > SPIN_LIMIT) __trap();
                have = false;
            }
            if (un >= NUK) {
                const uint32_t s0 = (uint32_t)H0, s1 = (uint32_t)(H0 >> 32);
                const float mu = __uint_as_float((uint32_t)H1);
                const float m = warp_max(mu);
                const float l = warp_sum(__uint_as_float((uint32_t)(H1 >> 32)) * expsub(mu, m));
                const float inv = 1.0f / l;
                const uint32_t w0 = pack_bf16(expsub(bf_lo(s0), m) * inv, expsub(bf_hi(s0), m) * inv);
                const uint32_t w1 = pack_bf16(expsub(bf_lo(s1), m) * inv, expsub(bf_hi(s1), m) * inv);
#pragma unroll
                for (int j = 0; j < 8; j++) {
                    Q[2 * j] = __shfl_sync(~0u, w0, 4 * j + t) & vmask;
                    Q[2 * j + 1] = __shfl_sync(~0u, w1, 4 * j + t) & vmask;
                }
            } else {
#pragma unroll
                for (int j = 0; j < 8; j++) {
                    const int src = (((j + g) & 7) << 2) + t;
                    Q[j] = __shfl_sync(~0u, (uint32_t)H0, src);
                    Q[8 + j] = __shfl_sync(~0u, (uint32_t)H1, src);
                }
            }
            if (u < 0) TS(2);
            unn = nstatic + (int)__shfl_sync(~0u, nxt, 0);
            if (CLU && !once && unn >= NU && lane == 0)
                asm volatile("st.relaxed.cta.shared::cta.u32 [%0], %1;" ::"r"(help + 28), "r"((tiss + (FJ - (unn - NU)) * 10) | 1u) : "memory");
        }
        if (u >= NUK && lane < (CLU ? 1 : NREP))
            red_add_u32(vdst,
                        1u + ((__float_as_uint(oret.x) | __float_as_uint(oret.y) | __float_as_uint(oret.z) | __float_as_uint(oret.w)) & zero));
        if (un >= NU) break;
        bu = bn;
        have = !(un < NUK && unn >= NUK && !(un >= NUK / 2 && unn < NUK + NUK / 2));
        bn = unit_block(unn);
        if (have) header(unn, bn);
        u = un;
        un = unn;
    }
    TS(4);
}

__device__ __forceinline__ void k_helper(uint32_t help, unsigned epoch) {
    if ((threadIdx.x & 31) != 0) return;
    unsigned (*ctl)[32] = g_ctl[epoch & 1];
    unsigned sent0 = 0, sent1 = 0, n = 0;
    int seen = 0;
    bool fin = false;
    while (!fin || seen < 2) {
        if (!fin) {
            fin = ld_acquire_cta_shared(help + 8) == NW + XW;
            const unsigned c0 = ld_acquire_cta_shared(help), c1 = ld_acquire_cta_shared(help + 4);
            if (c0 != sent0 || c1 != sent1) {
                fence_gpu();
                if (c0 != sent0) red_add_u32(&ctl[C_KDONE][0], c0 - sent0);
                if (c1 != sent1) red_add_u32(&ctl[C_KDONE + 1][0], c1 - sent1);
                sent0 = c0; sent1 = c1;
            }
        }
        if (seen < 2 && ld_acquire(&ctl[C_KDONE + seen][0]) >= NUK / 2) {
            st_release_cta_shared(help + 12 + 4 * seen, 1u);
            seen++;
        } else {
            __nanosleep(300);
        }
        if (++n > SPIN_LIMIT) __trap();
    }
}

__device__ __forceinline__ void v_poller(uint32_t sbase, int f, int w) {
    const int lane = threadIdx.x & 31;
    const unsigned (*cp)[32] = &g_vdone[((f * NPOLL + w) % NREP) * NH];
    unsigned n = 0;
    while (ld_acquire_cta_shared(sbase + M_HELP + 12) == 0) { __nanosleep(1000); if (++n > SPIN_LIMIT) __trap(); }
    int h = 0;
    bool fast = false;
    while (h < NH) {
        const unsigned r = __ballot_sync(~0u, ld_acquire(&cp[min(h + (lane & 3), NH - 1)][0]) >= 4 * UPP) & 15u;
        if (r & 1) {
            h = min(NH, h + __ffs(~r) - 1);
            __syncwarp();
            if (lane == 0) asm volatile("red.release.cta.shared::cta.max.u32 [%0], %1;" ::"r"(sbase + M_HELP + 20), "r"(h) : "memory");
        }
        if (h < NH - 4) {
            __nanosleep(h ? 300 : 1000);
        } else if (!fast) {
            fast = true;
            const long long t0 = clock64();
            while (clock64() - t0 < w * PGAP) {}
        }
        if (++n > SPIN_LIMIT) __trap();
    }
}
__device__ __forceinline__ void finisher(const Params& p, uint32_t sbase, int f) {
    const int lane = threadIdx.x & 31;
    {
        const char* wg = reinterpret_cast<const char*>(p.wo);
        const uint32_t dst = sbase + 4 * SLOT + (16 * (lane & 7) + (lane >> 3)) * 16;
#pragma unroll 1
        for (int h = -FPF - 4; h < NH; h++) {
            if (lane == 0 && (unsigned)(h + FPF) < (unsigned)NH) l2_prefetch(wg + (size_t)(h + FPF) * 147456 + f * 2048, 2048);
            if (h >= 0) {
#pragma unroll
                for (int r = 0; r < 4; r++)
                    asm volatile("cp.async.cg.shared.global [%0], [%1], 16;" ::"r"(dst + h * 2048 + ((r & 1) * 4 + (r >> 1) * 8) * 16),
                                 "l"(wg + (size_t)(h * 128 + r * 32 + lane) * (DM * 2) + f * 16) : "memory");
            }
            __nanosleep(FSLEEP);
        }
        asm volatile("cp.async.wait_all;" ::: "memory");
        __syncwarp();
    }
    TS(11);
    const float4* vec = g_oacc + ((lane >> 2) & 3) * 32 + (lane >> 4) * 16 + (lane & 3);
    float acc[2][2][4];
#pragma unroll
    for (int i = 0; i < 16; i++) acc[i >> 3][(i >> 2) & 1][i & 3] = 0.f;
    uint32_t* outp = reinterpret_cast<uint32_t*>(p.out + (lane >> 2) * (2 * DM) + f * 8 + (lane & 3) * 2);
    uint32_t wa = sbase + 4 * SLOT + lane * 16;
    auto project = [&](const float4 (&x)[4], const uint32_t (&w)[4][4]) {
#pragma unroll
        for (int s = 0; s < 4; s++) {
            const uint32_t a[4] = {pack_bf16(x[s].x, x[s].y), 0u, pack_bf16(x[s].z, x[s].w), 0u};
            mma16816(acc[0][s & 1], a, w[s >> 1][(s & 1) * 2], w[s >> 1][(s & 1) * 2 + 1]);
            mma16816(acc[1][s & 1], a, w[2 + (s >> 1)][(s & 1) * 2], w[2 + (s >> 1)][(s & 1) * 2 + 1]);
        }
    };
    int h = 0;
    unsigned n = 0;
    while (h < NH) {
        uint32_t w[4][4];
#pragma unroll
        for (int q = 0; q < 4; q++) ldsm4t(w[q], wa + q * 512);
        int ready;
        while ((ready = ld_acquire_cta_shared(sbase + M_HELP + 20)) <= h) {
            if (h < NH - 3) __nanosleep(100);
            if (++n > (SPIN_LIMIT << 4)) __trap();
        }
        float4 x[4], y[4];
#pragma unroll
        for (int s = 0; s < 4; s++) x[s] = ld_relaxed16(vec + s * 4);
        const bool two = ready > h + 1;
        if (two) {
#pragma unroll
            for (int s = 0; s < 4; s++) y[s] = ld_relaxed16(vec + 128 + s * 4);
        }
        project(x, w);
        if (two) {
#pragma unroll
            for (int q = 0; q < 4; q++) ldsm4t(w[q], wa + 2048 + q * 512);
            project(y, w);
        }
        const int nr = two ? 2 : 1;
        h += nr;
        vec += nr * 128;
        wa += nr * 2048;
        const float o0 = acc[0][0][0] + acc[0][1][0] + __shfl_down_sync(~0u, acc[1][0][0] + acc[1][1][0], 16);
        const float o1 = acc[0][0][1] + acc[0][1][1] + __shfl_down_sync(~0u, acc[1][0][1] + acc[1][1][1], 16);
        asm volatile("{\n.reg .pred p;\nsetp.ne.u32 p, %2, 0;\n@p st.global.u32 [%0], %1;\n}" ::"l"(outp), "r"(pack_bf16(o0, o1)),
                     "r"((uint32_t)(lane < 16 && h == NH)) : "memory");
    }
}

__device__ __forceinline__ void out_fetch(uint32_t sbase, int step, int h) {
    const int lane = threadIdx.x & 31, g = lane >> 2;
    float4 x[4];
#pragma unroll
    for (int b = 0; b < 4; b++) x[b] = ld_relaxed16(&g_oacc[(h * 4 + ((b + g) & 3)) * 32 + lane]);
#pragma unroll
    for (int b = 0; b < 4; b++) {
        const uint32_t a = sbase + F_X + step * FXP + g * 128 + ((b + g) & 3) * 16 + (lane & 3) * 4;
        asm volatile("st.shared.u32 [%0], %1;\nst.shared.u32 [%0 + 64], %2;" ::"r"(a), "r"(pack_bf16(x[b].x, x[b].y)), "r"(pack_bf16(x[b].z, x[b].w)) : "memory");
    }
    asm volatile("fence.proxy.async.shared::cta;" ::: "memory");
}
__device__ __forceinline__ void out_early(uint32_t sbase, int rank, unsigned tag) {
    const int lane = threadIdx.x & 31;
    if (lane < 10) {
        mbar_init(sbase + F_BAR + 16 + lane * 8, lane < 7 ? 1 : lane == 7 ? 2 : 4);
        if (lane < 8) mbar_expect_tx(sbase + F_BAR + 16 + lane * 8, 16384);
    }
    asm volatile("fence.mbarrier_init.release.cluster;" ::: "memory");
    unsigned n = 0;
#pragma unroll 1
    for (int i = 0; i < 3; i++) {
        while (ld_acquire(&g_vdone[8 * i + rank][0]) < 4 * UPP) { __nanosleep(500); if (++n > SPIN_LIMIT) __trap(); }
        out_fetch(sbase, 4 + i, 8 * i + rank);
#pragma unroll 1
        for (int j = 0; j < 16 && i == 0;) {
            const ulonglong2 v = ld_tagged2(&g_ctx[((j >> 2) * 8 + rank) * 128 + (j & 3) * 32 + lane]);
            if (__all_sync(~0u, (unsigned)(v.x >> 32) == tag && (unsigned)(v.y >> 32) == tag)) {
                asm volatile("st.shared.v2.u32 [%0], {%1,%2};" ::"r"(sbase + F_X + (j >> 2) * FXP + ((j & 3) * 32 + lane) * 8), "r"((uint32_t)v.x), "r"((uint32_t)v.y) : "memory");
                j++;
            } else {
                __nanosleep(500);
                if (++n > SPIN_LIMIT) __trap();
            }
        }
    }
    __syncwarp();
    if (lane == 0) st_release_cta_shared(sbase + M_HELP + 32, 1u);
}
__device__ __forceinline__ void out_late(uint32_t sbase, int rank) {
    unsigned n = 0;
    while (ld_acquire_cta_shared(sbase + M_HELP + 32) == 0) { if (++n > (SPIN_LIMIT << 4)) __trap(); }
    while (ld_acquire(&g_vdone[24 + rank][0]) < 4 * UPP) { if (++n > SPIN_LIMIT) __trap(); }
    TS(12);
    out_fetch(sbase, 7, 24 + rank);
    __syncwarp();
    if ((threadIdx.x & 31) == 0) asm volatile("mbarrier.arrive.shared::cta.b64 _, [%0];" ::"r"(sbase + F_BAR + 72) : "memory");
    TS(13);
}
__device__ __forceinline__ void out_project(uint32_t sbase, int rank, int w) {
    const int lane = threadIdx.x & 31, g = lane >> 2, t = lane & 3;
    unsigned n = 0;
    while (ld_acquire_cta_shared(sbase + M_HELP + 32) == 0) { __nanosleep(500); if (++n > SPIN_LIMIT) __trap(); }
    asm volatile("barrier.cluster.wait.acquire.aligned;" ::: "memory");
    const uint32_t rdst = mapa(sbase + F_RECV + 1024 + rank * 128 + (g & 3) * 32 + t * 16, 2 * w + (g >> 2));
    const uint32_t rbar = mapa(sbase + F_BAR + 8, 2 * w + (g >> 2));
    while (ld_acquire_cta_shared(sbase + M_HELP + 28) == 0) { __nanosleep(200); if (++n > SPIN_LIMIT) __trap(); }
    const uint32_t da = (1u << 16) | (((sbase + F_W) & 0x3ffff) >> 4), db = (4u << 16) | (((sbase + F_X) & 0x3ffff) >> 4);
    float d[4] = {0.f, 0.f, 0.f, 0.f};
#pragma unroll
    for (int i = 0; i < 8; i++) {
        mbar_first(sbase + F_BAR + 16 + i * 8);
        wgmma_tile(d, da + (i % 6) * 1024, db + i * (FXP / 16), i & 3);
        if (i < 2 || (i & 3) == 3) asm volatile("wgmma.wait_group.sync.aligned 0;" : "+f"(d[0]), "+f"(d[1]), "+f"(d[2]), "+f"(d[3])::"memory");
        if (i < 2) {
            asm volatile("{\n.reg .pred p;\nsetp.eq.u32 p, %1, 0;\n@p mbarrier.arrive.shared::cta.b64 _, [%0];\n}"
                         ::"r"(sbase + F_BAR + 80 + i * 8), "r"(lane) : "memory");
        } else if ((i & 3) == 3) {
            if (t < 2)
                asm volatile("st.async.weak.shared::cluster.mbarrier::complete_tx::bytes.v4.f32 [%0], {%1,%2,%3,%4}, [%5];"
                             ::"r"(rdst - (i < 4 ? 1024 : 0)), "f"(d[0]), "f"(d[1]), "f"(d[2]), "f"(d[3]), "r"(rbar - (i < 4 ? 8 : 0)) : "memory");
            __syncwarp();
        }
    }
}
__device__ __forceinline__ void out_issue_sum(const Params& p, uint32_t sbase, int c, int rank, uint64_t pol) {
    const int lane = threadIdx.x & 31;
    if (lane == 0) {
        unsigned n = 0;
        while (ld_acquire_cta_shared(sbase + M_HELP + 32) == 0) { __nanosleep(500); if (++n > SPIN_LIMIT) __trap(); }
        asm volatile("prefetch.tensormap [%0];" ::"l"(&p.tm_wf) : "memory");
        asm volatile("prefetch.tensormap [%0];" ::"l"(&p.tm_wl) : "memory");
        uint32_t t0;
        while ((t0 = ld_acquire_cta_shared(sbase + M_HELP + 28)) == 0) { __nanosleep(100); if (++n > SPIN_LIMIT) __trap(); }
#pragma unroll 1
        for (int i = 0; i < 8; i++) {
            const int h = (i & 3) * 8 + rank;
            if (i >= 6) mbar_wait(sbase + F_BAR + 32 + i * 8, 0);
            for (int k = 0; k < 4096 && (int)(now_ns() - t0) < 0; k++) {}
            if (i == 0) TS(16);
            tma3d(sbase + F_W + (i < 6 ? i : i - 6) * 16384, i < 4 ? &p.tm_wf : &p.tm_wl, i < 4 ? 0 : c * 64, i < 4 ? h * 128 : h * 16,
                  i < 4 ? c : 0, sbase + F_BAR + 16 + i * 8, pol);
            t0 += FP;
        }
        TS(17);
    }
    __syncwarp();
    __nv_bfloat16* dst = p.out + (((lane >> 1) & 2) + (lane & 1)) * (2 * DM) + DM + c * 64 + (rank >> 1) * 16 + (lane & 2) * 4 +
                         (rank & 1) * 4 + (lane >> 3);
    uint32_t src = sbase + F_RECV + lane * 4;
#pragma unroll 1
    for (int r = 0; r < 2; r++) {
        asm volatile("" : "+l"(dst), "+r"(src));
        mbar_first_cluster(sbase + F_BAR + r * 8);
        float x[8];
#pragma unroll
        for (int i = 0; i < 8; i++) asm volatile("ld.shared.f32 %0, [%1];" : "=f"(x[i]) : "r"(src + i * 128) : "memory");
        const float v = (((x[0] + x[1]) + (x[2] + x[3])) + (x[4] + x[5])) + (x[6] + x[7]);
        asm volatile("{\n.reg .b16 h;\ncvt.rn.bf16.f32 h, %1;\nst.global.b16 [%0], h;\n}" ::"l"(dst), "f"(v) : "memory");
        TS(14 + r);
        dst -= DM;
        src += 1024;
    }
}

constexpr int BS_WUK = 5, BS_Q = 9, BS_CKV = 11, BS_PART = 27, BS_WUV = 29, BS_END = 33;

__device__ __noinline__ void b_issue(const Params& p, int n, int bi, uint32_t sbase, uint64_t pol) {
    if (n >= BS_END || (n >= BS_Q && n < BS_CKV) || (n >= BS_PART && n < BS_WUV)) return;
    const uint32_t bar = sbase + M_BAR + (NSLOT + n % BRING) * 8;
    const CUtensorMap* tm;
    int row, panel = 2 * bi;
    if (n < BS_WUK) { tm = &p.tm_wq; row = n * 128; }
    else if (n < BS_Q) { tm = &p.tm_wuk; row = (n - BS_WUK) * 128; }
    else if (n < BS_PART) {
        tm = &p.tm_ckv; panel = 0;
        row = (bi >> 3) * SK + ((n - BS_CKV) * 8 + (bi & 7)) * 32;
    }
    else { tm = &p.tm_wuv; row = (n - BS_WUV) * 128; }
    mbar_expect_tx(bar, n == 0 ? 32768 + 4 * 1152 : 32768);
    tma3d(sbase + (n % BRING) * SLOT, tm, 0, row, panel, bar, pol);
}
__device__ __forceinline__ void b_issue_xchg(int n, const void* src, uint32_t sbase, uint64_t pol) {
    asm volatile("fence.proxy.async;" ::: "memory");
#pragma unroll
    for (int i = 0; i < 2; i++) {
        const uint32_t bar = sbase + M_BAR + (NSLOT + (n + i) % BRING) * 8;
        mbar_expect_tx(bar, 32768);
        bulk_load(sbase + ((n + i) % BRING) * SLOT, reinterpret_cast<const char*>(src) + i * 32768, 32768, bar, pol);
    }
}
__device__ __forceinline__ void b_wait(int n, uint32_t sbase) {
    mbar_wait(sbase + M_BAR + (NSLOT + n % BRING) * 8, (n / BRING) & 1);
}

__device__ __noinline__ void b_gemm(const Params& p, uint32_t sbase, int n0, int n1, int ktot, uint32_t xh, uint32_t xl, int pitch,
                                    int bi, uint64_t pol) {
    const int tid = threadIdx.x, warp = tid >> 5, lane = tid & 31, g = lane >> 2, t = lane & 3;
    const uint32_t woff = (warp >> 2) * 16384 + (lane & 15) * 128 + ((((warp & 3) * 2 + (lane >> 4)) ^ (lane & 7)) * 16);
    const uint32_t xoff = (g & 3) * pitch + t * 4;
    float acc[2][4];
#pragma unroll
    for (int i = 0; i < 8; i++) acc[i >> 2][i & 3] = 0.f;
#pragma unroll 1
    for (int n = n0; n < n1; n++) {
        b_wait(n, sbase);
        const uint32_t slot = sbase + (n % BRING) * SLOT + woff;
        const int k0 = (n - n0) * 128;
        const int ns = min(8, (ktot - k0) >> 4);
#pragma unroll 2
        for (int s = 0; s < ns; s++) {
            uint32_t a[4], w[4];
            const uint32_t xo = xoff + (k0 + 16 * s) * 2;
            a[0] = lds32(xh + xo); a[2] = lds32(xh + xo + 16);
            a[1] = xl ? lds32(xl + xo) : 0u; a[3] = xl ? lds32(xl + xo + 16) : 0u;
            ldsm4t(w, slot + s * 2048);
            mma16816(acc[0], a, w[0], w[1]);
            mma16816(acc[1], a, w[2], w[3]);
        }
        __syncthreads();
        if (tid == 0) b_issue(p, n + BD, bi, sbase, pol);
    }
    if (g < 4) {
#pragma unroll
        for (int j = 0; j < 2; j++)
            asm volatile("st.shared.u32 [%0], %1;" ::"r"(sbase + M_QB + g * QP + (warp * 16 + j * 8 + t * 2) * 2),
                         "r"(pack_bf16(acc[j][0] + acc[j][2], acc[j][1] + acc[j][3])) : "memory");
    }
    __syncthreads();
}

__device__ __forceinline__ void b_exchange(unsigned* c, int n, const void* src, uint32_t sbase, uint64_t pol) {
    TS(n == BS_Q ? 24 : 28);
    __syncthreads();
    if (threadIdx.x == 0) {
        TS(n == BS_Q ? 25 : 29);
        fence_gpu();
        TS(n == BS_Q ? 26 : 30);
        red_add_u32(c, 1u);
        wait_count(c, NBCTA);
        TS(n == BS_Q ? 27 : 31);
        b_issue_xchg(n, src, sbase, pol);
    }
}

template <bool CLU>
__device__ __noinline__ void b_chain(const Params& p, char* smem, uint32_t sbase, int bi, unsigned epoch, uint64_t pol) {
    const int tid = threadIdx.x, warp = tid >> 5, lane = tid & 31, g = lane >> 2, t = lane & 3;
    unsigned (*ctl)[32] = g_ctl[epoch & 1];
    float* red = reinterpret_cast<float*>(smem + 5 * SLOT);
    b_gemm(p, sbase, 0, BS_WUK, DM, sbase + M_XB, 0, XP, bi, pol);
    TS(6);
    {
        uint32_t Q[16];
#pragma unroll
        for (int c = 0; c < 16; c++) Q[c] = lds32(sbase + M_QB + (g & 3) * QP + c * 16 + t * 4);
        float* qa = reinterpret_cast<float*>(smem + M_QA);
#pragma unroll 1
        for (int n = BS_WUK; n < BS_Q; n++) {
            b_wait(n, sbase);
            const uint32_t base = sbase + (n % BRING) * SLOT + (warp * 16 + (lane & 15)) * 128;
            float d[2][4];
#pragma unroll
            for (int i = 0; i < 8; i++) d[i >> 2][i & 3] = 0.f;
#pragma unroll
            for (int s = 0; s < 8; s++) {
                uint32_t a[4];
                ldsm4(a, base + (s >> 2) * 16384 + (((2 * (s & 3) + (lane >> 4)) ^ (lane & 7)) * 16));
                mma16816(d[s & 1], a, Q[2 * s], Q[2 * s + 1]);
            }
            const int c = (n - BS_WUK) * 128 + warp * 16 + g + 8 * (t >> 1);
            qa[(2 * (t & 1)) * 512 + c] = (t & 2) ? d[0][2] + d[1][2] : d[0][0] + d[1][0];
            qa[(2 * (t & 1) + 1) * 512 + c] = (t & 2) ? d[0][3] + d[1][3] : d[0][1] + d[1][1];
            __syncthreads();
            if (tid == 0) b_issue(p, n + BD, bi, sbase, pol);
        }
#pragma unroll 1
        for (int r = 0; r < 2; r++) {
            const int id = tid + r * 256;
            const int b = id >> 7, c0 = ((id >> 2) & 31) * 16 + (id & 3) * 2;
            const float2 u0 = *reinterpret_cast<const float2*>(qa + b * 512 + c0);
            const float2 u1 = *reinterpret_cast<const float2*>(qa + b * 512 + c0 + 8);
            const uint32_t h0 = pack_bf16(u0.x, u0.y), h1 = pack_bf16(u1.x, u1.y);
            const uint32_t l0 = pack_bf16(u0.x - bf_lo(h0), u0.y - bf_hi(h0)), l1 = pack_bf16(u1.x - bf_lo(h1), u1.y - bf_hi(h1));
            g_qabs[((id >> 2) * 4 + (bi >> 3)) * 32 + (bi & 7) * 4 + (id & 3)] = make_uint4(h0, l0, h1, l1);
        }
    }
    b_exchange(&ctl[C_BBAR][0], BS_Q, &g_qabs[(bi >> 3) * 4096], sbase, pol);
    {
        uint32_t qf[4][4][4];
        b_wait(BS_Q + (warp >> 2), sbase);
        TS(7);
        {
            const uint4* qs = reinterpret_cast<const uint4*>(smem + ((BS_Q + (warp >> 2)) % BRING) * SLOT) + (warp & 3) * 512 + lane;
#pragma unroll
            for (int s = 0; s < 4; s++)
#pragma unroll
                for (int i = 0; i < 4; i++) {
                    const uint4 v = qs[(s * 4 + i) * 32];
                    qf[i][s][0] = v.x; qf[i][s][1] = v.y; qf[i][s][2] = v.z; qf[i][s][3] = v.w;
                }
        }
        __syncthreads();
        if (tid == 0) { b_issue(p, BS_Q + BD, bi, sbase, pol); b_issue(p, BS_Q + 1 + BD, bi, sbase, pol); }
        float acc[2][8][4];
#pragma unroll
        for (int i = 0; i < 2; i++)
#pragma unroll
            for (int j = 0; j < 8; j++) { acc[i][j][0] = acc[i][j][1] = acc[i][j][2] = acc[i][j][3] = 0.f; }
        float mrun = -INFINITY, lrun = 0.f;
        const int head = tid >> 3, kq = tid & 7;
        float* alpha = reinterpret_cast<float*>(smem + M_ALPHA);
        for (int n = BS_CKV; n < BS_PART; n++) {
            b_wait(n, sbase);
            const uint32_t slot = sbase + (n % BRING) * SLOT;
            float sc[4][4][4];
#pragma unroll
            for (int i = 0; i < 4; i++)
#pragma unroll
                for (int j = 0; j < 4; j++) { sc[i][j][0] = sc[i][j][1] = sc[i][j][2] = sc[i][j][3] = 0.f; }
#pragma unroll
            for (int j = 0; j < 4; j++)
#pragma unroll
                for (int sp = 0; sp < 2; sp++) {
                    uint32_t bf[4];
                    ldsm4(bf, slot + warp * 4096 + (8 * j + (lane & 7)) * 128 + (((4 * sp + (lane >> 3)) ^ (lane & 7)) * 16));
#pragma unroll
                    for (int i = 0; i < 4; i++) {
                        mma16816(sc[i][j], qf[i][2 * sp], bf[0], bf[1]);
                        mma16816(sc[i][j], qf[i][2 * sp + 1], bf[2], bf[3]);
                    }
                }
#pragma unroll
            for (int i = 0; i < 4; i++)
#pragma unroll
                for (int j = 0; j < 4; j++)
                    *reinterpret_cast<float2*>(red + warp * 1024 + (8 * i + g) * 32 + ((8 * j) ^ (8 * (g & 3))) + 2 * t) =
                        make_float2(sc[i][j][0] + sc[i][j][2], sc[i][j][1] + sc[i][j][3]);
            __syncthreads();
            if (tid == 0 && n > BS_CKV) b_issue(p, n - 1 + BD, bi, sbase, pol);
            {
                float4 s = make_float4(0.f, 0.f, 0.f, 0.f);
#pragma unroll
                for (int w = 0; w < 8; w++) {
                    const float4 v = *reinterpret_cast<const float4*>(red + w * 1024 + head * 32 + ((4 * kq) ^ (8 * (head & 3))));
                    s.x += v.x; s.y += v.y; s.z += v.z; s.w += v.w;
                }
                const uint32_t r0 = pack_bf16(s.x, s.y), r1 = pack_bf16(s.z, s.w);
                const uint32_t s0 = pack_bf16(bf_lo(r0) * SCALE, bf_hi(r0) * SCALE);
                const uint32_t s1 = pack_bf16(bf_lo(r1) * SCALE, bf_hi(r1) * SCALE);
                const float f0 = bf_lo(s0), f1 = bf_hi(s0), f2 = bf_lo(s1), f3 = bf_hi(s1);
                float mx = fmaxf(fmaxf(f0, f1), fmaxf(f2, f3));
                mx = fmaxf(mx, __shfl_xor_sync(~0u, mx, 1));
                mx = fmaxf(mx, __shfl_xor_sync(~0u, mx, 2));
                mx = fmaxf(mx, __shfl_xor_sync(~0u, mx, 4));
                const float mnew = fmaxf(mrun, mx);
                const float al = expsub(mrun, mnew);
                const float p0 = expsub(f0, mnew), p1 = expsub(f1, mnew), p2 = expsub(f2, mnew), p3 = expsub(f3, mnew);
                lrun = lrun * al + ((p0 + p1) + (p2 + p3));
                mrun = mnew;
                *reinterpret_cast<uint2*>(smem + M_P + head * 80 + kq * 8) = make_uint2(pack_bf16(p0, p1), pack_bf16(p2, p3));
                if (kq == 0) alpha[head] = al;
            }
            __syncthreads();
            {
                uint32_t pf[2][2][4];
#pragma unroll
                for (int i = 0; i < 2; i++)
#pragma unroll
                    for (int ks = 0; ks < 2; ks++)
                        ldsm4(pf[i][ks], sbase + M_P + (16 * i + (lane & 15)) * 80 + (16 * ks + 8 * (lane >> 4)) * 2);
#pragma unroll
                for (int i = 0; i < 2; i++) {
                    const float a0 = alpha[16 * i + g], a1 = alpha[16 * i + 8 + g];
#pragma unroll
                    for (int j = 0; j < 8; j++) { acc[i][j][0] *= a0; acc[i][j][1] *= a0; acc[i][j][2] *= a1; acc[i][j][3] *= a1; }
                }
#pragma unroll
                for (int j = 0; j < 8; j++) {
                    uint32_t bf[4];
                    ldsm4t(bf, slot + warp * 4096 + lane * 128 + ((j ^ (lane & 7)) * 16));
#pragma unroll
                    for (int i = 0; i < 2; i++) {
                        mma16816(acc[i][j], pf[i][0], bf[0], bf[1]);
                        mma16816(acc[i][j], pf[i][1], bf[2], bf[3]);
                    }
                }
            }
        }
        __syncthreads();
        if (tid == 0) b_issue(p, BS_PART - 1 + BD, bi, sbase, pol);
        lrun += __shfl_xor_sync(~0u, lrun, 1);
        lrun += __shfl_xor_sync(~0u, lrun, 2);
        lrun += __shfl_xor_sync(~0u, lrun, 4);
        if (kq == 0) g_bml[head * NBCTA + bi] = make_float2(mrun, lrun);
#pragma unroll
        for (int i = 0; i < 2; i++)
#pragma unroll
            for (int j = 0; j < 8; j++) {
                g_bpart[((16 * i + g) * NBCTA + bi) * 256 + warp * 32 + j * 4 + t] = make_float2(acc[i][j][0], acc[i][j][1]);
                g_bpart[((16 * i + 8 + g) * NBCTA + bi) * 256 + warp * 32 + j * 4 + t] = make_float2(acc[i][j][2], acc[i][j][3]);
            }
    }
#pragma unroll 1
    for (int i = tid; i < NH * 36 && !(CLU); i += 256) g_outb[bi * NH * 36 + i] = make_uint4(0u, epoch, 0u, epoch);
    b_exchange(&ctl[C_BBAR + 1][0], BS_PART, &g_bpart[bi * NBCTA * 256], sbase, pol);
    {
        float* omega = reinterpret_cast<float*>(smem + M_OMEGA);
        if (warp == 0) {
            __syncwarp();
            const uint2 ml = ld_relaxed8(&g_bml[bi * NBCTA + lane]);
            const float ms = __uint_as_float(ml.x);
            float m = ms;
            m = fmaxf(m, __shfl_xor_sync(~0u, m, 1));
            m = fmaxf(m, __shfl_xor_sync(~0u, m, 2));
            m = fmaxf(m, __shfl_xor_sync(~0u, m, 4));
            const float w = expsub(ms, m);
            float l = w * __uint_as_float(ml.y);
            l += __shfl_xor_sync(~0u, l, 1);
            l += __shfl_xor_sync(~0u, l, 2);
            l += __shfl_xor_sync(~0u, l, 4);
            omega[lane] = w / l;
        }
        __syncthreads();
        b_wait(BS_PART, sbase);
        b_wait(BS_PART + 1, sbase);
#pragma unroll 1
        for (int b = 0; b < 4; b++) {
            const float2* ps = reinterpret_cast<const float2*>(smem + ((BS_PART + (b >> 1)) % BRING) * SLOT) + (b & 1) * 2048 + tid;
            float c0 = 0.f, c1 = 0.f;
#pragma unroll
            for (int s = 0; s < 8; s++) {
                const float w = omega[b * 8 + s];
                const float2 v = ps[s * 256];
                c0 = fmaf(w, v.x, c0);
                c1 = fmaf(w, v.y, c1);
            }
            const uint32_t hi = pack_bf16(c0, c1);
            *reinterpret_cast<uint32_t*>(smem + M_CH + b * CP + tid * 4) = hi;
            *reinterpret_cast<uint32_t*>(smem + M_CL + b * CP + tid * 4) = pack_bf16(c0 - bf_lo(hi), c1 - bf_hi(hi));
        }
        __syncthreads();
        if (tid == 0) { b_issue(p, BS_PART + BD, bi, sbase, pol); b_issue(p, BS_PART + 1 + BD, bi, sbase, pol); }
    }
    b_gemm(p, sbase, BS_WUV, BS_END, 512, sbase + M_CH, sbase + M_CL, CP, bi, pol);
    TS(12);
    if (CLU) {
        if (tid < 128) {
            const uint32_t xo = sbase + M_QB + ((tid >> 1) & 3) * QP + (tid >> 3) * 16 + (tid & 1) * 8;
            st_tagged2(&g_ctx[bi * 128 + tid], __uint_as_float(lds32(xo)), __uint_as_float(lds32(xo + 4)), epoch + 1);
        }
        return;
    }
    if (tid == 0) {
#pragma unroll 1
        for (int i = 0; i < 4; i++) {
            mbar_expect_tx(sbase + M_BAR + i * 8, 36864);
            tma3d(sbase + i * 36864, &p.tm_wo, 0, bi * 128 + i * 32, 0, sbase + M_BAR + i * 8, pol);
        }
    }
    TS(8);
    {
        float acc[9][4];
#pragma unroll
        for (int j = 0; j < 9; j++) { acc[j][0] = acc[j][1] = acc[j][2] = acc[j][3] = 0.f; }
#pragma unroll 1
        for (int i = 0; i < 4; i++) {
            const uint32_t xo = sbase + M_QB + (g & 3) * QP + i * 64 + t * 4;
            const uint32_t a0[4] = {lds32(xo), 0u, lds32(xo + 16), 0u}, a1[4] = {lds32(xo + 32), 0u, lds32(xo + 48), 0u};
            mbar_wait(sbase + M_BAR + i * 8, 0);
#pragma unroll
            for (int j = 0; j < 9; j++) {
                const int nt = warp * 9 + j;
                uint32_t w[4];
                ldsm4t(w, sbase + i * 36864 + (nt >> 3) * 4096 + lane * 128 + (((nt & 7) ^ (lane & 7)) * 16));
                mma16816(acc[j], a0, w[0], w[1]);
                mma16816(acc[j], a1, w[2], w[3]);
            }
        }
        if (g < 4) {
#pragma unroll
            for (int j = 0; j < 9; j++) {
                const int c2 = (warp * 9 + j) * 4 + t;
                st_tagged2(&g_outb[((c2 / 9) * NH + bi) * 36 + g * 9 + c2 % 9], acc[j][0], acc[j][1], epoch + 1);
            }
        }
    }
    TS(9);
    {
        const uint4* src = g_outb + (bi * NH + (tid >> 3)) * 36 + (tid & 7);
        float2* part = reinterpret_cast<float2*>(red);
        unsigned n = 0;
        while (true) {
            ulonglong2 v[5];
            bool ok = true;
#pragma unroll
            for (int i = 0; i < 5; i++)
                if (i < 4 || (tid & 7) < 4) v[i] = ld_tagged2(src + i * 8);
#pragma unroll
            for (int i = 0; i < 5; i++)
                if (i < 4 || (tid & 7) < 4) {
                    ok = ok && (unsigned)(v[i].x >> 32) == epoch + 1 && (unsigned)(v[i].y >> 32) == epoch + 1;
                    part[(tid >> 3) * 36 + (tid & 7) + i * 8] = make_float2(__uint_as_float((unsigned)v[i].x), __uint_as_float((unsigned)v[i].y));
                }
            if (ok) break;
            __nanosleep(400);
            if (++n > SPIN_LIMIT) __trap();
        }
        __syncthreads();
        if (tid < 36) {
            float s0 = 0.f, s1 = 0.f;
#pragma unroll 8
            for (int h = 0; h < NH; h++) { const float2 v = part[h * 36 + tid]; s0 += v.x; s1 += v.y; }
            *reinterpret_cast<uint32_t*>(p.out + (tid / 9) * 2 * DM + DM + bi * 18 + (tid % 9) * 2) = pack_bf16(s0, s1);
        }
    }
    TS(10);
}

template <bool CLU>
__global__ void __launch_bounds__(256, 1) fused_decode_kernel(const __grid_constant__ First f, const __grid_constant__ Params p) {
    extern __shared__ __align__(1024) char smem_raw[];
    const uint32_t sbase = (smem_u32(smem_raw) + 1023u) & ~1023u;
    char* smem = smem_raw + (sbase - smem_u32(smem_raw));
    const int tid = threadIdx.x, warp = tid >> 5, lane = tid & 31;
    asm volatile("{\n.reg .pred p;\nsetp.ne.u32 p, %1, 0;\n@p prefetch.global.L2 [%0];\n}"
                 ::"l"(f.ptr[tid >> 10] + (blockIdx.x * 8 + warp) * 8192 + lane * 128), "r"((uint32_t)(blockIdx.x < DM / 8 && lane < 16)) : "memory");
    const char* eptr = f.ptr[3 + (tid >> 10)];
    const int blk = CLU ? cluster_role(blockIdx.x) : blockIdx.x;
    const bool isB = CLU ? blk < NBCTA : (blk & 3) == 0 && (blk >> 2) < NBCTA;
    const int bi = CLU ? blk : blk >> 2;
    const int nb = CLU ? blk - NBCTA : blk - min(NBCTA, (blk + 3) >> 2);
    const int nblk = CLU ? 8 * MINCL : gridDim.x, nnb = nblk - NBCTA;
    const int nstatic = nnb * (NW + XW);
    uint64_t pol, poln;
    asm volatile("createpolicy.fractional.L2::evict_first.b64 %0, 1.0;" : "=l"(pol));
    asm volatile("createpolicy.fractional.L2::evict_normal.b64 %0, 1.0;" : "=l"(poln));
    const uint32_t wbar = sbase + M_BAR + warp * 8, wslot = sbase + warp * SLOT;
    const bool hold = blk < 16;
    const uint32_t jbar = sbase + M_BAR + (NSLOT + BRING) * 8, fbar = sbase + M_BAR + 4 * 8;
    if (warp < 4) {
        if (lane == 0) {
            if (warp == 0) {
                mbar_init(jbar, 1);
                asm volatile("fence.mbarrier_init.release.cluster;" ::: "memory");
                mbar_expect_tx(jbar, 36864 + 4 * 1152);
                if (CLU || blk < 128) tma3d(sbase + J0W, &p.tm_j0, blk * 32, 0, 0, jbar, poln);
            } else if (warp & 1) {
                if (warp & 2) {
#pragma unroll
                    for (int i = 0; i < NSLOT + BRING; i++) mbar_init(sbase + M_BAR + i * 8, 1);
                    mbar_expect_tx(fbar, NEARLY * TILE_BYTES);
                } else if (CLU && !isB) {
#pragma unroll
                    for (int i = 0; i < 2; i++) {
                        mbar_init(sbase + F_BAR + i * 8, 1);
                        mbar_expect_tx(sbase + F_BAR + i * 8, 1024);
                    }
                }
                asm volatile("fence.mbarrier_init.release.cluster;" ::: "memory");
            } else {
#pragma unroll
                for (int i = 0; i < 4; i++) asm volatile("st.shared.v4.u32 [%0], {%1,%1,%1,%1};" ::"r"(sbase + M_HELP + i * 16), "r"(0) : "memory");
            }
        }
    } else if (blockIdx.x >= DM / 8) {
        if (tid == 128) {
            asm volatile("prefetch.tensormap [%0];" ::"l"(&p.tm_j0) : "memory");
            asm volatile("prefetch.tensormap [%0];" ::"l"(&p.tm_wq) : "memory");
        } else if (blockIdx.x == DM / 8 + 4 && tid >= 220) {
            asm volatile("prefetch.global.L2 [%0];" ::"l"(f.ptr[2 + (tid >> 10)] + (tid - 220) * 128) : "memory");
        }
    }
    __syncthreads();
    if (tid == 128) {
        if (CLU || blk < 128) bulk_load(sbase + M_XA, f.ptr[2], 4608, jbar, poln);
        if (!isB && !hold) bulk_load(sbase, block_src(f.ptr[1], unit_block(nb * NEARLY)), NEARLY * TILE_BYTES, fbar, pol);
    }
    const int u0 = ((warp / NEARLY) * nnb + nb) * NEARLY + warp % NEARLY;
    unsigned epoch = 0;
    if (lane == 0) epoch = ld_relaxed4(eptr);
    TS(0);
    if (CLU && (unsigned)nb < NFIN) asm volatile("barrier.cluster.arrive.relaxed.aligned;" ::: "memory");
    if ((warp >> 1) == 2 && blk < 128) st_relaxed64(&g_qll[((tid - 128) >> 4) * 2048 + blk * 16 + (tid & 15)], 0ull);
    if (isB || warp >= NW + XW) epoch = __shfl_sync(~0u, epoch, 0);
    if (isB && tid == 96) {
        if (hold) { unsigned n = 0; while (ld_acquire_cta_shared(sbase + M_HELP + 24) < 2) { if (++n > (SPIN_LIMIT << 4)) __trap(); } }
#pragma unroll 1
        for (int b = 0; b < 4; b++) bulk_load(sbase + M_XB + b * XP, p.xb + b * DM, 1152, sbase + M_BAR + NSLOT * 8, pol);
#pragma unroll 1
        for (int n = 0; n < BD; n++) b_issue(p, n, bi, sbase, pol);
    }
    if (warp >= 4 && blk < 128) {
        const int g = lane >> 2, t = lane & 3, j = tid - 128;
#pragma unroll 1
        for (int sl = blk, ph = 0;; sl += 128 - nblk, ph = 1) {
        mbar_wait(jbar, ph);
        TS(13);
        float acc[4][4];
#pragma unroll
        for (int i = 0; i < 16; i++) acc[i >> 2][i & 3] = 0.f;
        const uint32_t wa = sbase + J0W + ((warp - 4) * 144 + (lane & 15)) * 64;
        const uint32_t sw = (lane >> 1) & 3, xa = sbase + M_XA + (g & 3) * 1152 + (warp - 4) * 288 + t * 4;
#pragma unroll 3
        for (int s = 0; s < 9; s++) {
            const uint32_t a[4] = {lds32(xa + s * 32), 0u, lds32(xa + s * 32 + 16), 0u};
            uint32_t w0[4], w1[4];
            ldsm4t(w0, wa + s * 1024 + (((lane >> 4) ^ sw) * 16));
            ldsm4t(w1, wa + s * 1024 + (((2 + (lane >> 4)) ^ sw) * 16));
            mma16816(acc[0], a, w0[0], w0[1]);
            mma16816(acc[1], a, w0[2], w0[3]);
            mma16816(acc[2], a, w1[0], w1[1]);
            mma16816(acc[3], a, w1[2], w1[3]);
        }
        float2* j0 = reinterpret_cast<float2*>(smem + M_J0);
        if (g < 4) {
#pragma unroll
            for (int i = 0; i < 4; i++) j0[(warp - 4) * 64 + g * 16 + i * 4 + t] = make_float2(acc[i][0], acc[i][1]);
        }
        asm volatile("bar.sync 1, 128;" ::: "memory");
        const bool again = sl == blk && blk + 128 - nblk >= nblk;
        if (again && tid == 224) {
            mbar_expect_tx(jbar, 36864);
            tma3d(sbase + J0W, &p.tm_j0, (blk + 128 - nblk) * 32, 0, 0, jbar, pol);
        }
        if (warp < 6) {
            const float2 v0 = j0[j], v1 = j0[64 + j], v2 = j0[128 + j], v3 = j0[192 + j];
            st_relaxed64(&g_qll[(j >> 4) * 2048 + sl * 16 + (j & 15)],
                         (unsigned long long)pack_bf16((v0.x + v1.x) + (v2.x + v3.x), (v0.y + v1.y) + (v2.y + v3.y)) |
                             ((unsigned long long)(epoch + 1) << 32));
            __syncwarp();
            if (lane == 0) asm volatile("red.relaxed.cta.shared::cta.add.u32 [%0], 1;" ::"r"(sbase + M_HELP + 24) : "memory");
        } else if (warp == 7) {
            if (blk < C_LINES) g_ctl[(epoch & 1) ^ 1][blk][lane] = 0;
        }
        TS(1);
        if (!again) break;
        asm volatile("bar.sync 1, 128;" ::: "memory");
        }
    }
    if (isB) {
        b_chain<CLU>(p, smem, sbase, bi, epoch, pol);
        return;
    }
    if (warp < NW + XW) {
        a_worker<CLU>(p, u0, warp >= NW + (((nb * 5) & 7) < (CLU ? X3C : X3) ? 1 : 0), hold, nstatic, wslot, wbar, warp < NEARLY && !hold ? fbar : wbar,
                      sbase + M_HELP, epoch, pol);
        if (CLU && nb < NFIN) {
            if (warp == 3) out_issue_sum(p, sbase, nb >> 3, nb & 7, pol);
            else if (warp == 0) out_late(sbase, nb & 7);
        }
        return;
    } else if (warp == 7) {
#pragma unroll 1
        for (int i = nb; i < 4 * NH; i += nnb) g_oacc[i * 32 + lane] = make_float4(0.f, 0.f, 0.f, 0.f);
        if (nb < NREP * NH) g_vdone[nb][lane] = 0;
        __syncwarp();
        k_helper(sbase + M_HELP, epoch);
        if (nb == 0 && lane == 0) g_epoch = epoch + 1;
        __syncwarp();
        if (CLU && nb < NFIN) out_early(sbase, nb & 7, epoch + 1);
    } else if (CLU) {
    } else if (warp == 6 && nb < NFIN) {
        finisher(p, sbase, nb);
        TS(4);
    } else if (warp >= 6 - NPOLL && nb < NFIN) {
        v_poller(sbase, nb, warp - (6 - NPOLL));
    }
    if (CLU && nb < NFIN) out_project(sbase, nb & 7, warp - 4);
}

}

typedef CUresult (*EncodeFn)(CUtensorMap*, CUtensorMapDataType, cuuint32_t, void*, const cuuint64_t*, const cuuint64_t*,
                             const cuuint32_t*, const cuuint32_t*, CUtensorMapInterleave, CUtensorMapSwizzle,
                             CUtensorMapL2promotion, CUtensorMapFloatOOBfill);

extern "C" void kernel_launch(void* const* d_in, const int* in_sizes, int n_in, void* d_out, int out_size) {
    (void)in_sizes; (void)n_in; (void)out_size;
    static int nsm = 0, ncl = 0;
    static EncodeFn encode = nullptr;
    static const char* epoch_ptr = nullptr;
    cudaLaunchConfig_t cfg = {};
    cudaLaunchAttribute at[1];
    at[0].id = cudaLaunchAttributeClusterDimension;
    at[0].val.clusterDim.x = 8; at[0].val.clusterDim.y = 1; at[0].val.clusterDim.z = 1;
    cfg.blockDim = dim3(256); cfg.dynamicSmemBytes = SMEM_BYTES; cfg.stream = cudaStreamPerThread; cfg.attrs = at; cfg.numAttrs = 1;
    if (nsm == 0) {
        int dev = 0;
        cudaGetDevice(&dev);
        cudaDeviceGetAttribute(&nsm, cudaDevAttrMultiProcessorCount, dev);
        cudaFuncSetAttribute(fused_decode_kernel<false>, cudaFuncAttributeMaxDynamicSharedMemorySize, SMEM_BYTES);
        cudaFuncSetAttribute(fused_decode_kernel<true>, cudaFuncAttributeMaxDynamicSharedMemorySize, SMEM_BYTES);
        cfg.gridDim = dim3(128);
        if (cudaOccupancyMaxActiveClusters(&ncl, fused_decode_kernel<true>, &cfg) != cudaSuccess) { ncl = 0; (void)cudaGetLastError(); }
        if (ncl > MINCL) ncl = MINCL;
        cudaGetSymbolAddress((void**)&epoch_ptr, g_epoch);
        void* fn = nullptr;
        cudaDriverEntryPointQueryResult qr;
        cudaGetDriverEntryPoint("cuTensorMapEncodeTiled", &fn, cudaEnableDefault, &qr);
        encode = (EncodeFn)fn;
    }
    Params p;
    auto panels = [&](CUtensorMap* tm, void* ptr, int rows, int cols, int box_rows, int box_panels) {
        const cuuint64_t gd[3] = {64, (cuuint64_t)rows, (cuuint64_t)(cols / 64)}, gs[2] = {(cuuint64_t)cols * 2, 128};
        const cuuint32_t box[3] = {64, (cuuint32_t)box_rows, (cuuint32_t)box_panels}, es[3] = {1, 1, 1};
        encode(tm, CU_TENSOR_MAP_DATA_TYPE_BFLOAT16, 3, ptr, gd, gs, box, es, CU_TENSOR_MAP_INTERLEAVE_NONE,
               CU_TENSOR_MAP_SWIZZLE_128B, CU_TENSOR_MAP_L2_PROMOTION_L2_256B, CU_TENSOR_MAP_FLOAT_OOB_FILL_NONE);
    };
    panels(&p.tm_wq, d_in[7], DM, 4096, 128, 2);
    panels(&p.tm_wuk, d_in[8], 512, 4096, 128, 2);
    panels(&p.tm_wuv, d_in[9], 512, 4096, 128, 2);
    panels(&p.tm_wo, d_in[10], 4096, DM, 32, 9);
    panels(&p.tm_wf, d_in[10], 4096, DM, 128, 1);
    panels(&p.tm_ckv, d_in[6], 4 * SK, 512, 32, 8);
    {
        const cuuint64_t gd[3] = {4096, 192, 3}, gs[2] = {8192, 192 * 8192};
        const cuuint32_t box[3] = {32, 192, 3}, es[3] = {1, 1, 1};
        encode(&p.tm_j0, CU_TENSOR_MAP_DATA_TYPE_BFLOAT16, 3, d_in[3], gd, gs, box, es, CU_TENSOR_MAP_INTERLEAVE_NONE,
               CU_TENSOR_MAP_SWIZZLE_64B, CU_TENSOR_MAP_L2_PROMOTION_L2_128B, CU_TENSOR_MAP_FLOAT_OOB_FILL_NONE);
    }
    {
        const cuuint64_t gd[3] = {DM, 512, 8}, gs[2] = {8 * DM * 2, DM * 2};
        const cuuint32_t box[3] = {64, 16, 8}, es[3] = {1, 1, 1};
        encode(&p.tm_wl, CU_TENSOR_MAP_DATA_TYPE_BFLOAT16, 3, d_in[4], gd, gs, box, es, CU_TENSOR_MAP_INTERLEAVE_NONE,
               CU_TENSOR_MAP_SWIZZLE_128B, CU_TENSOR_MAP_L2_PROMOTION_L2_256B, CU_TENSOR_MAP_FLOAT_OOB_FILL_NONE);
    }
    p.kc = (const __nv_bfloat16*)d_in[1];
    p.vc = (const __nv_bfloat16*)d_in[2];
    p.wo = (const __nv_bfloat16*)d_in[4];
    p.xb = (const __nv_bfloat16*)d_in[5];
    p.out = (__nv_bfloat16*)d_out;
    const First f = {{(const char*)d_in[3], (const char*)d_in[1], (const char*)d_in[0], epoch_ptr}};
    if (ncl >= MINCL) {
        cfg.gridDim = dim3(8 * ncl);
        cudaLaunchKernelEx(&cfg, fused_decode_kernel<true>, f, p);
    } else {
        fused_decode_kernel<false><<<nsm, 256, SMEM_BYTES, cudaStreamPerThread>>>(f, p);
    }
}
```

```cpp
#include <cuda_runtime.h>
#include <cuda.h>
#include <cuda_bf16.h>
#include <stdint.h>

namespace {

constexpr int NH = 32, SK = 4096, DM = 576;
constexpr int KEYS = 128;
constexpr int UPP = SK / KEYS;
constexpr int NUK = 4 * NH * UPP;
constexpr int TILE_BYTES = KEYS * 256;
#define NWORK 2
constexpr int NW = NWORK;
constexpr int NBCTA = 32;
constexpr int MINCL = 15;
constexpr int NFIN = 72;
constexpr int SLOT = 32768;
constexpr int NSLOT = 6;
constexpr int BRING = 5;
constexpr int J0W = 5 * SLOT;
constexpr int MISC = NSLOT * SLOT + 4096;
constexpr int XP = 1168, CP = 1040, QP = 272;
constexpr int M_XA = MISC;
constexpr int M_XB = M_XA + 4 * XP;
constexpr int M_CH = M_XB + 4 * XP;
constexpr int M_CL = M_CH + 4 * CP;
constexpr int M_QB = M_CL + 4 * CP;
constexpr int M_QA = M_CH;
constexpr int M_J0 = M_QB + 4 * QP;
constexpr int M_P = M_J0 + 2048;
constexpr int M_ALPHA = M_P + 2560;
constexpr int M_OMEGA = M_ALPHA + 128;
constexpr int M_BAR = M_OMEGA + 128;
constexpr int M_HELP = M_BAR + 128;
constexpr int F_W = 3 * SLOT;
constexpr int F_X = NSLOT * SLOT, FXP = 1088;
constexpr int F_RECV = F_X + 12 * FXP;
constexpr int F_BAR = M_P;
constexpr int SMEM_BYTES = M_HELP + 128 + 1024;
static_assert(F_RECV + 2048 <= M_J0, "output phase layout");
static_assert(SMEM_BYTES <= 232448 && M_BAR % 8 == 0 && M_QA % 16 == 0 && M_P % 16 == 0, "smem layout");
#define XW 2
#define X3 2
#define X3C 3
#define NEARLY 2
#define BD 5
#define FPF 3
#define FSLEEP 800
#define FJ 250
#define FP 376
#define FN 32
#define NPOLL 2
#define PGAP 200
static_assert(NW + XW == 4 && 4 % NEARLY == 0 && BD <= BRING, "slots 4 and 5 hold the finisher weights");
constexpr float SCALE = 0.08838834764831845f;
constexpr float LOG2E = 1.4426950408889634f;
constexpr unsigned SPIN_LIMIT = 1u << 24;

#define NREP 2
constexpr int C_QUEUE = 0, C_KDONE = 1, C_BBAR = 3, C_LINES = 5;

struct First { const char* ptr[4]; };
struct Params {
    const __nv_bfloat16 *kc, *vc, *wo, *xb;
    __nv_bfloat16* out;
    CUtensorMap tm_j0;
    CUtensorMap tm_wq, tm_wuk, tm_ckv, tm_wuv, tm_wo;
    CUtensorMap tm_out[3][2];
};

__device__ unsigned g_epoch;
__device__ unsigned g_ctl[2][C_LINES][32];
__device__ uint2 g_qll[4 * 2048];
__device__ uint2 g_scores[128 * SK / 4];
__device__ float2 g_stats[128 * UPP];
__device__ float4 g_oacc[128 * 32];
__device__ unsigned g_vdone[NREP * NH][32];
__device__ uint4 g_qabs[4 * 8 * 4 * 4 * 32];
__device__ float2 g_bpart[NBCTA * NH * 256];
__device__ float2 g_bml[NBCTA * NH];
__device__ uint4 g_ctx[NH * 128];
__device__ uint4 g_outb[NBCTA * NH * 36];

__device__ __forceinline__ int cluster_role(int b) {
    const int i = b - NFIN, q = ((i >> 1) * 43 >> 7) * 2, r = i - 3 * q;
    int x = i - q;
    asm("{\n.reg .pred p;\nsetp.ge.s32 p, %1, 4;\nselp.s32 %0, %2, %0, p;\nsetp.lt.s32 p, %3, 0;\nselp.s32 %0, %4, %0, p;\n}"
        : "+r"(x) : "r"(r), "r"(NBCTA + NFIN - 4 + q + r), "r"(i), "r"(b + NBCTA));
    return x;
}

#define TS(i)
#define TSV(i, v)
#define LAND(i)
#define CLK(x)
#define ACC(a, x, y)

__device__ __forceinline__ uint32_t smem_u32(const void* p) { return (uint32_t)__cvta_generic_to_shared(p); }
__device__ __forceinline__ void mbar_init(uint32_t bar, uint32_t cnt) {
    asm volatile("mbarrier.init.shared::cta.b64 [%0], %1;" ::"r"(bar), "r"(cnt) : "memory");
}
__device__ __forceinline__ void mbar_expect_tx(uint32_t bar, uint32_t bytes) {
    asm volatile("mbarrier.arrive.expect_tx.shared::cta.b64 _, [%0], %1;" ::"r"(bar), "r"(bytes) : "memory");
}
__device__ __forceinline__ bool mbar_try(uint32_t bar, uint32_t parity) {
    uint32_t ok;
    asm volatile("{\n.reg .pred p;\nmbarrier.try_wait.parity.shared::cta.b64 p, [%1], %2;\nselp.u32 %0, 1, 0, p;\n}\n"
                 : "=r"(ok) : "r"(bar), "r"(parity) : "memory");
    return ok;
}
__device__ __forceinline__ void mbar_wait(uint32_t bar, uint32_t parity) {
    unsigned n = 0;
    while (!mbar_try(bar, parity)) { if (++n > SPIN_LIMIT) __trap(); }
}
__device__ __forceinline__ void bulk_load(uint32_t dst, const void* src, uint32_t bytes, uint32_t bar, uint64_t pol) {
    asm volatile("cp.async.bulk.shared::cluster.global.mbarrier::complete_tx::bytes.L2::cache_hint [%0], [%1], %2, [%3], %4;"
                 ::"r"(dst), "l"(src), "r"(bytes), "r"(bar), "l"(pol) : "memory");
}
__device__ __forceinline__ void tma3d(uint32_t dst, const CUtensorMap* tm, int c0, int c1, int c2, uint32_t bar, uint64_t pol) {
    asm volatile("cp.async.bulk.tensor.3d.shared::cluster.global.mbarrier::complete_tx::bytes.L2::cache_hint [%0], [%1, {%3,%4,%5}], [%2], %6;"
                 ::"r"(dst), "l"(tm), "r"(bar), "r"(c0), "r"(c1), "r"(c2), "l"(pol) : "memory");
}
__device__ __forceinline__ void tma4d(uint32_t dst, const CUtensorMap* tm, int c0, int c2, int c3, uint32_t bar, uint64_t pol) {
    asm volatile("cp.async.bulk.tensor.4d.shared::cluster.global.mbarrier::complete_tx::bytes.L2::cache_hint [%0], [%1, {%3,0,%4,%5}], [%2], %6;"
                 ::"r"(dst), "l"(tm), "r"(bar), "r"(c0), "r"(c2), "r"(c3), "l"(pol) : "memory");
}
__device__ __forceinline__ void l2_prefetch(const void* src, uint32_t bytes) {
    asm volatile("cp.async.bulk.prefetch.L2.global [%0], %1;" ::"l"(src), "r"(bytes) : "memory");
}
__device__ __forceinline__ void ldsm4(uint32_t (&r)[4], uint32_t addr) {
    asm volatile("ldmatrix.sync.aligned.m8n8.x4.shared.b16 {%0,%1,%2,%3}, [%4];"
                 : "=r"(r[0]), "=r"(r[1]), "=r"(r[2]), "=r"(r[3]) : "r"(addr));
}
__device__ __forceinline__ void ldsm4t(uint32_t (&r)[4], uint32_t addr) {
    asm volatile("ldmatrix.sync.aligned.m8n8.x4.trans.shared.b16 {%0,%1,%2,%3}, [%4];"
                 : "=r"(r[0]), "=r"(r[1]), "=r"(r[2]), "=r"(r[3]) : "r"(addr));
}
__device__ __forceinline__ void mma16816(float (&d)[4], const uint32_t (&a)[4], uint32_t b0, uint32_t b1) {
    asm("mma.sync.aligned.m16n8k16.row.col.f32.bf16.bf16.f32 {%0,%1,%2,%3}, {%4,%5,%6,%7}, {%8,%9}, {%0,%1,%2,%3};"
        : "+f"(d[0]), "+f"(d[1]), "+f"(d[2]), "+f"(d[3])
        : "r"(a[0]), "r"(a[1]), "r"(a[2]), "r"(a[3]), "r"(b0), "r"(b1));
}
__device__ __forceinline__ void wgmma_k64(float (&d)[4], uint32_t da, uint32_t db, int accumulate) {
    asm volatile("{\n.reg .pred p;\n.reg .b32 x, y;\n.reg .b64 a, b;\nsetp.ne.u32 p, %6, 0;\n"
                 "add.u32 x, %4, 0;\nadd.u32 y, %5, 0;\nmov.b64 a, {x, 0x40000040};\nmov.b64 b, {y, 1};\n"
                 "wgmma.mma_async.sync.aligned.m64n8k16.f32.bf16.bf16 {%0,%1,%2,%3}, a, b, p, 1, 1, 1, 0;\n"
                 "add.u32 x, %4, 128;\nadd.u32 y, %5, 8;\nmov.b64 a, {x, 0x40000040};\nmov.b64 b, {y, 1};\n"
                 "wgmma.mma_async.sync.aligned.m64n8k16.f32.bf16.bf16 {%0,%1,%2,%3}, a, b, 1, 1, 1, 1, 0;\n"
                 "add.u32 x, %4, 256;\nadd.u32 y, %5, 16;\nmov.b64 a, {x, 0x40000040};\nmov.b64 b, {y, 1};\n"
                 "wgmma.mma_async.sync.aligned.m64n8k16.f32.bf16.bf16 {%0,%1,%2,%3}, a, b, 1, 1, 1, 1, 0;\n"
                 "add.u32 x, %4, 384;\nadd.u32 y, %5, 24;\nmov.b64 a, {x, 0x40000040};\nmov.b64 b, {y, 1};\n"
                 "wgmma.mma_async.sync.aligned.m64n8k16.f32.bf16.bf16 {%0,%1,%2,%3}, a, b, 1, 1, 1, 1, 0;\n"
                 "}" : "+f"(d[0]), "+f"(d[1]), "+f"(d[2]), "+f"(d[3]) : "r"(da), "r"(db), "r"(accumulate) : "memory");
}
__device__ __forceinline__ uint32_t lds32(uint32_t a) {
    uint32_t v;
    asm volatile("ld.shared.u32 %0, [%1];" : "=r"(v) : "r"(a));
    return v;
}
__device__ __forceinline__ unsigned ld_acquire(const unsigned* p) {
    unsigned v;
    asm volatile("ld.acquire.gpu.global.u32 %0, [%1];" : "=r"(v) : "l"(p) : "memory");
    return v;
}
__device__ __forceinline__ uint2 ld_relaxed8(const void* p) {
    uint2 v;
    asm volatile("ld.relaxed.gpu.global.v2.u32 {%0,%1}, [%2];" : "=r"(v.x), "=r"(v.y) : "l"(p) : "memory");
    return v;
}
__device__ __forceinline__ unsigned ld_relaxed4(const void* p) {
    unsigned v;
    asm volatile("ld.relaxed.gpu.global.u32 %0, [%1];" : "=r"(v) : "l"(p) : "memory");
    return v;
}
__device__ __forceinline__ unsigned atom_inc(unsigned* p) {
    unsigned v;
    asm volatile("atom.relaxed.gpu.global.inc.u32 %0, [%1], 0x7fffffff;" : "=r"(v) : "l"(p) : "memory");
    return v;
}
__device__ __forceinline__ unsigned long long ld_relaxed64(const void* p) {
    unsigned long long v;
    asm volatile("ld.relaxed.gpu.global.u64 %0, [%1];" : "=l"(v) : "l"(p) : "memory");
    return v;
}
__device__ __forceinline__ void st_relaxed64(void* p, unsigned long long v) {
    asm volatile("st.relaxed.gpu.global.u64 [%0], %1;" ::"l"(p), "l"(v) : "memory");
}
__device__ __forceinline__ float4 ld_relaxed16(const void* p) {
    float4 v;
    asm volatile("ld.relaxed.gpu.global.v4.f32 {%0,%1,%2,%3}, [%4];" : "=f"(v.x), "=f"(v.y), "=f"(v.z), "=f"(v.w) : "l"(p) : "memory");
    return v;
}
__device__ __forceinline__ uint32_t mapa(uint32_t a, uint32_t rank) {
    uint32_t r;
    asm("mapa.shared::cluster.u32 %0, %1, %2;" : "=r"(r) : "r"(a), "r"(rank));
    return r;
}
__device__ __forceinline__ void mbar_first(uint32_t bar) {
    asm volatile("{\n.reg .pred p, q;\n.reg .u32 n;\nmov.u32 n, 0;\n"
                 "SPIN:\nmbarrier.try_wait.parity.shared::cta.b64 p, [%0], 0;\nadd.u32 n, n, 1;\nsetp.gt.u32 q, n, 0x1000000;\n@q trap;\n"
                 "@!p bra.uni SPIN;\n}" ::"r"(bar) : "memory");
}
__device__ __forceinline__ void mbar_first_cluster(uint32_t bar) {
    asm volatile("{\n.reg .pred p, q;\n.reg .u32 n;\nmov.u32 n, 0;\n"
                 "SPIN:\nmbarrier.try_wait.parity.relaxed.cluster.shared::cta.b64 p, [%0], 0;\nadd.u32 n, n, 1;\nsetp.gt.u32 q, n, 0x1000000;\n@q trap;\n"
                 "@!p bra.uni SPIN;\nfence.acquire.sync_restrict::shared::cluster.cluster;\n}" ::"r"(bar) : "memory");
}
__device__ __forceinline__ uint32_t now_ns() {
    unsigned long long t;
    asm volatile("mov.u64 %0, %globaltimer;" : "=l"(t));
    return (uint32_t)t;
}
__device__ __forceinline__ void fence_gpu() { asm volatile("fence.acq_rel.gpu;" ::: "memory"); }
__device__ __forceinline__ void red_add_u32(unsigned* p, unsigned v) {
    asm volatile("red.relaxed.gpu.global.add.u32 [%0], %1;" ::"l"(p), "r"(v) : "memory");
}
__device__ __forceinline__ void st_tagged2(void* p, float a, float b, unsigned tag) {
    const unsigned long long hi = (unsigned long long)tag << 32;
    asm volatile("st.relaxed.gpu.global.v2.b64 [%0], {%1,%2};" ::"l"(p), "l"(hi | __float_as_uint(a)), "l"(hi | __float_as_uint(b)) : "memory");
}
__device__ __forceinline__ ulonglong2 ld_tagged2(const void* p) {
    ulonglong2 v;
    asm volatile("ld.relaxed.gpu.global.v2.b64 {%0,%1}, [%2];" : "=l"(v.x), "=l"(v.y) : "l"(p) : "memory");
    return v;
}
__device__ __forceinline__ float4 atom_add_f4(void* p, float a, float b, float c, float d) {
    float4 r;
    asm volatile("atom.relaxed.gpu.global.add.v4.f32 {%0,%1,%2,%3}, [%4], {%5,%6,%7,%8};"
                 : "=f"(r.x), "=f"(r.y), "=f"(r.z), "=f"(r.w) : "l"(p), "f"(a), "f"(b), "f"(c), "f"(d) : "memory");
    return r;
}
__device__ __forceinline__ void red_release_cta_shared(uint32_t a, unsigned v) {
    asm volatile("red.release.cta.shared::cta.add.u32 [%0], %1;" ::"r"(a), "r"(v) : "memory");
}
__device__ __forceinline__ unsigned ld_acquire_cta_shared(uint32_t a) {
    unsigned v;
    asm volatile("ld.acquire.cta.shared::cta.u32 %0, [%1];" : "=r"(v) : "r"(a) : "memory");
    return v;
}
__device__ __forceinline__ void st_release_cta_shared(uint32_t a, unsigned v) {
    asm volatile("st.release.cta.shared::cta.u32 [%0], %1;" ::"r"(a), "r"(v) : "memory");
}
__device__ __forceinline__ void wait_count(const unsigned* p, unsigned target) {
    unsigned n = 0;
    while (ld_acquire(p) < target) { if (++n > SPIN_LIMIT) __trap(); }
}
__device__ __forceinline__ uint32_t pack_bf16(float lo, float hi) {
    uint32_t r;
    asm("cvt.rn.bf16x2.f32 %0, %1, %2;" : "=r"(r) : "f"(hi), "f"(lo));
    return r;
}
__device__ __forceinline__ float bf_lo(uint32_t v) { return __uint_as_float(v << 16); }
__device__ __forceinline__ float bf_hi(uint32_t v) { return __uint_as_float(v & 0xffff0000u); }
__device__ __forceinline__ float ex2(float x) { float y; asm("ex2.approx.ftz.f32 %0, %1;" : "=f"(y) : "f"(x)); return y; }
__device__ __forceinline__ float expsub(float a, float b) { return ex2((a - b) * LOG2E); }
__device__ __forceinline__ float warp_max(float v) {
#pragma unroll
    for (int m = 16; m; m >>= 1) v = fmaxf(v, __shfl_xor_sync(~0u, v, m));
    return v;
}
__device__ __forceinline__ float warp_sum(float v) {
#pragma unroll
    for (int m = 16; m; m >>= 1) v += __shfl_xor_sync(~0u, v, m);
    return v;
}
__device__ __forceinline__ unsigned unit_block(int u) {
    const unsigned v = u & (NUK - 1);
    return u < NUK ? (v & ~0x78u) | (v & 0x18u) << 2 | (v & 0x60u) >> 2 : v;
}
__device__ __forceinline__ const char* block_src(const void* base, unsigned blk) {
    const unsigned po = blk / UPP;
    return reinterpret_cast<const char*>(base) + (size_t)(((po & 3) * NH + (po >> 2)) * UPP + blk % UPP) * TILE_BYTES;
}

template <bool CLU>
__device__ __forceinline__ void a_worker(const Params& p, int un, bool once, bool hold, int nstatic, uint32_t slot, uint32_t bar, uint32_t wb,
                                         uint32_t help, unsigned epoch, uint64_t pol) {
    constexpr int NU = 2 * NUK;
    const int lane = threadIdx.x & 31, g = lane >> 2, t = lane & 3;
    const int li = lane & 7;
    uint32_t kaddr[4], vaddr[8];
    {
        const int e = (lane >> 3) & 1, kk = lane >> 4;
#pragma unroll
        for (int s = 0; s < 4; s++) kaddr[s] = slot + (16 * li + e) * 256 + ((2 * s + kk + li) & 7) * 16;
        const int vrow = 4 * (li >> 1) + (li & 1) + 2 * kk;
#pragma unroll
        for (int c = 0; c < 8; c++) vaddr[c] = slot + vrow * 256 + e * 128 + ((c + li) & 7) * 16;
#pragma unroll
        for (int c = 0; c < 8; c++) asm volatile("" : "+r"(vaddr[c]));
    }
    const uint32_t vmask = (g >> 1) != t ? 0u : ((g & 1) ? 0xffff0000u : 0xffffu);
    int kseen = -1;
    unsigned long long H0 = 0, H1 = 0;
    auto header = [&](int v, unsigned vb) {
        if (v >= NU) return;
        const void *a0, *a1;
        if (v < NUK) {
            const unsigned po = vb / UPP;
            a0 = g_qll + (po & 3) * 2048 + (po >> 2) * 64 + lane;
            a1 = reinterpret_cast<const uint2*>(a0) + 32;
        } else {
            const int half = vb / (NUK / 2);
            if (half > kseen) {
                unsigned n = 0;
                while (ld_acquire_cta_shared(help + 12 + 4 * half) == 0) { if (++n > (SPIN_LIMIT << 4)) __trap(); }
                kseen = half;
            }
            a0 = &g_scores[vb * (KEYS / 4) + lane];
            a1 = &g_stats[(vb / UPP) * UPP + lane];
        }
        H0 = ld_relaxed64(a0);
        H1 = ld_relaxed64(a1);
    };
    epoch = __shfl_sync(~0u, epoch, 0);
    if (hold) { unsigned n = 0; while (ld_acquire_cta_shared(help + 24) < 2) { if (++n > (SPIN_LIMIT << 4)) __trap(); } }
    unsigned (*ctl)[32] = g_ctl[epoch & 1];
    const unsigned tag = epoch + 1;
    unsigned nxt = once ? NU : 0;
    int u = -1;
    unsigned bu = 0, bn = unit_block(un);
    bool have = false;
    uint32_t phase = 0;
    unsigned kpend = 0;
    const unsigned zero = gridDim.x >> 24;
    uint32_t Q[16];
    float4 oret = make_float4(0.f, 0.f, 0.f, 0.f);
    while (true) {
        const char* nsrc = block_src(un < NUK ? p.kc : p.vc, bn);
        float4* odst = &g_oacc[(bu / UPP) * 32 + lane];
        unsigned* vdst = &g_vdone[(lane & (NREP - 1)) * NH + bu / (4 * UPP)][0];
        float d[8][4];
        CLK(c1);
        asm volatile("" : "+l"(odst));
        if (u >= NUK) {
#pragma unroll
            for (int j = 0; j < 8; j++) { d[j][0] = d[j][1] = d[j][2] = d[j][3] = 0.f; }
            mbar_wait(wb, phase);
            LAND(NUK + bu);
            uint32_t a[2][8][4];
#pragma unroll
            for (int c = 0; c < 8; c++) ldsm4t(a[0][c], vaddr[c]);
#pragma unroll
            for (int j = 0; j < 8; j++) {
                if (j < 7) {
#pragma unroll
                    for (int c = 0; c < 8; c++) ldsm4t(a[(j + 1) & 1][c], vaddr[c] + (j + 1) * 4096);
                }
#pragma unroll
                for (int c = 0; c < 8; c++) mma16816(d[c], a[j & 1][c], Q[2 * j], Q[2 * j + 1]);
            }
            float o[4];
#pragma unroll
            for (int r = 0; r < 2; r++) {
                o[2 * r] = d[0][2 * r] + d[7][2 * r + 1];
                o[2 * r + 1] = d[0][2 * r + 1] + d[1][2 * r];
#pragma unroll
                for (int k = 1; k < 4; k++) {
                    const int src = (lane & 28) | ((t - k) & 3);
                    o[2 * r] += __shfl_sync(~0u, d[2 * k][2 * r] + d[2 * k - 1][2 * r + 1], src);
                    o[2 * r + 1] += __shfl_sync(~0u, d[2 * k][2 * r + 1] + d[2 * k + 1][2 * r], src);
                }
            }
            oret = atom_add_f4(odst, o[0], o[1], o[2], o[3]);
        } else if (u >= 0) {
#pragma unroll
            for (int j = 0; j < 8; j++) { d[j][0] = d[j][1] = d[j][2] = d[j][3] = 0.f; }
            mbar_wait(wb, phase);
            LAND(bu);
            uint32_t a[2][8][4];
#pragma unroll
            for (int j = 0; j < 8; j++) ldsm4(a[0][j], kaddr[0] + (4 * (j & 3) + 2 * (j >> 2)) * 256);
#pragma unroll
            for (int s = 0; s < 8; s++) {
                if (s < 7) {
#pragma unroll
                    for (int j = 0; j < 8; j++)
                        ldsm4(a[(s + 1) & 1][j], kaddr[(s + 1) & 3] + (4 * (j & 3) + 2 * (j >> 2)) * 256 + ((s + 1) >> 2) * 128);
                }
#pragma unroll
                for (int j = 0; j < 8; j++)
                    mma16816(d[j], a[s & 1][j], Q[(s & 4) * 2 + ((2 * s - 2 * j) & 7)], Q[(s & 4) * 2 + ((2 * s + 1 - 2 * j) & 7)]);
            }
        }
        const bool pre = wb != bar;
        if (u >= 0) { phase = pre ? 0 : phase ^ 1; wb = bar; }
        CLK(c2b);
        if (un < NU && lane == 0) {
            if (!once) nxt = atom_inc(&ctl[C_QUEUE][0]);
            if (u >= 0 || !pre) {
                mbar_expect_tx(bar, TILE_BYTES);
                bulk_load(slot, nsrc, TILE_BYTES, bar, pol);
            }
        }
        const uint32_t tiss = now_ns();
        CLK(c3);
        if ((unsigned)u < (unsigned)NUK) {
            const int j0 = (t - (g >> 1)) & 3;
            float v[4];
#pragma unroll
            for (int q = 0; q < 4; q++) {
                const int jq = (q >> 1) * 4, e = (q & 1) * 2;
                const float x0 = (g & 1) ? d[jq + 0][e + 1] : d[jq + 0][e];
                const float x1 = (g & 1) ? d[jq + 1][e + 1] : d[jq + 1][e];
                const float x2 = (g & 1) ? d[jq + 2][e + 1] : d[jq + 2][e];
                const float x3 = (g & 1) ? d[jq + 3][e + 1] : d[jq + 3][e];
                const float y0 = (j0 & 1) ? x1 : x0, y1 = (j0 & 1) ? x3 : x2;
                v[q] = (j0 & 2) ? y1 : y0;
            }
            const uint32_t r0 = pack_bf16(v[0], v[1]), r1 = pack_bf16(v[2], v[3]);
            const uint32_t s0 = pack_bf16(bf_lo(r0) * SCALE, bf_hi(r0) * SCALE);
            const uint32_t s1 = pack_bf16(bf_lo(r1) * SCALE, bf_hi(r1) * SCALE);
            g_scores[bu * (KEYS / 4) + 4 * g + j0] = make_uint2(s0, s1);
            const float f0 = bf_lo(s0), f1 = bf_hi(s0), f2 = bf_lo(s1), f3 = bf_hi(s1);
            const float m = warp_max(fmaxf(fmaxf(f0, f1), fmaxf(f2, f3)));
            const float l = warp_sum((expsub(f0, m) + expsub(f1, m)) + (expsub(f2, m) + expsub(f3, m)));
            if (lane == 0) g_stats[bu] = make_float2(m, l);
            kpend++;
            if (un / (NUK / 2) != u / (NUK / 2)) {
                __syncwarp();
                if (lane == 0) {
                    red_release_cta_shared(help + 4 * (u / (NUK / 2)), kpend);
                    if (un >= NUK) red_release_cta_shared(help + 8, 1u);
                }
                kpend = 0;
            }
        }
        CLK(c4);
        int unn = NU;
        if (un < NU) {
            unsigned n = 0;
            while (true) {
                if (!have) header(un, bn);
                if (un >= NUK || __all_sync(~0u, (uint32_t)(H0 >> 32) == tag && (uint32_t)(H1 >> 32) == tag)) break;
                if (++n > SPIN_LIMIT) __trap();
                have = false;
            }
            if (un >= NUK) {
                const uint32_t s0 = (uint32_t)H0, s1 = (uint32_t)(H0 >> 32);
                const float mu = __uint_as_float((uint32_t)H1);
                const float m = warp_max(mu);
                const float l = warp_sum(__uint_as_float((uint32_t)(H1 >> 32)) * expsub(mu, m));
                const float inv = 1.0f / l;
                const uint32_t w0 = pack_bf16(expsub(bf_lo(s0), m) * inv, expsub(bf_hi(s0), m) * inv);
                const uint32_t w1 = pack_bf16(expsub(bf_lo(s1), m) * inv, expsub(bf_hi(s1), m) * inv);
#pragma unroll
                for (int j = 0; j < 8; j++) {
                    Q[2 * j] = __shfl_sync(~0u, w0, 4 * j + t) & vmask;
                    Q[2 * j + 1] = __shfl_sync(~0u, w1, 4 * j + t) & vmask;
                }
            } else {
#pragma unroll
                for (int j = 0; j < 8; j++) {
                    const int src = (((j + g) & 7) << 2) + t;
                    Q[j] = __shfl_sync(~0u, (uint32_t)H0, src);
                    Q[8 + j] = __shfl_sync(~0u, (uint32_t)H1, src);
                }
            }
            if (u < 0) TS(2);
            unn = nstatic + (int)__shfl_sync(~0u, nxt, 0);
            if (CLU && !once && unn >= NU && lane == 0)
                asm volatile("st.relaxed.cta.shared::cta.u32 [%0], %1;" ::"r"(help + 28), "r"((tiss + (FJ - (unn - NU)) * 10) | 1u) : "memory");
        }
        if (u >= NUK && lane < (CLU ? 1 : NREP))
            red_add_u32(vdst,
                        1u + ((__float_as_uint(oret.x) | __float_as_uint(oret.y) | __float_as_uint(oret.z) | __float_as_uint(oret.w)) & zero));
        if (un >= NU) break;
        bu = bn;
        have = !(un < NUK && unn >= NUK && !(un >= NUK / 2 && unn < NUK + NUK / 2));
        bn = unit_block(unn);
        if (have) header(unn, bn);
        u = un;
        un = unn;
    }
    TS(4);
}

__device__ __forceinline__ void k_helper(uint32_t help, unsigned epoch) {
    if ((threadIdx.x & 31) != 0) return;
    unsigned (*ctl)[32] = g_ctl[epoch & 1];
    unsigned sent0 = 0, sent1 = 0, n = 0;
    int seen = 0;
    bool fin = false;
    while (!fin || seen < 2) {
        if (!fin) {
            fin = ld_acquire_cta_shared(help + 8) == NW + XW;
            const unsigned c0 = ld_acquire_cta_shared(help), c1 = ld_acquire_cta_shared(help + 4);
            if (c0 != sent0 || c1 != sent1) {
                fence_gpu();
                if (c0 != sent0) red_add_u32(&ctl[C_KDONE][0], c0 - sent0);
                if (c1 != sent1) red_add_u32(&ctl[C_KDONE + 1][0], c1 - sent1);
                sent0 = c0; sent1 = c1;
            }
        }
        if (seen < 2 && ld_acquire(&ctl[C_KDONE + seen][0]) >= NUK / 2) {
            st_release_cta_shared(help + 12 + 4 * seen, 1u);
            seen++;
        } else {
            __nanosleep(300);
        }
        if (++n > SPIN_LIMIT) __trap();
    }
}

__device__ __forceinline__ void v_poller(uint32_t sbase, int f, int w) {
    const int lane = threadIdx.x & 31;
    const unsigned (*cp)[32] = &g_vdone[((f * NPOLL + w) % NREP) * NH];
    unsigned n = 0;
    while (ld_acquire_cta_shared(sbase + M_HELP + 12) == 0) { __nanosleep(1000); if (++n > SPIN_LIMIT) __trap(); }
    int h = 0;
    bool fast = false;
    while (h < NH) {
        const unsigned r = __ballot_sync(~0u, ld_acquire(&cp[min(h + (lane & 3), NH - 1)][0]) >= 4 * UPP) & 15u;
        if (r & 1) {
            h = min(NH, h + __ffs(~r) - 1);
            __syncwarp();
            if (lane == 0) asm volatile("red.release.cta.shared::cta.max.u32 [%0], %1;" ::"r"(sbase + M_HELP + 20), "r"(h) : "memory");
        }
        if (h < NH - 4) {
            __nanosleep(h ? 300 : 1000);
        } else if (!fast) {
            fast = true;
            const long long t0 = clock64();
            while (clock64() - t0 < w * PGAP) {}
        }
        if (++n > SPIN_LIMIT) __trap();
    }
}
__device__ __forceinline__ void finisher(const Params& p, uint32_t sbase, int f) {
    const int lane = threadIdx.x & 31;
    {
        const char* wg = reinterpret_cast<const char*>(p.wo);
        const uint32_t dst = sbase + 4 * SLOT + (16 * (lane & 7) + (lane >> 3)) * 16;
#pragma unroll 1
        for (int h = -FPF - 4; h < NH; h++) {
            if (lane == 0 && (unsigned)(h + FPF) < (unsigned)NH) l2_prefetch(wg + (size_t)(h + FPF) * 147456 + f * 2048, 2048);
            if (h >= 0) {
#pragma unroll
                for (int r = 0; r < 4; r++)
                    asm volatile("cp.async.cg.shared.global [%0], [%1], 16;" ::"r"(dst + h * 2048 + ((r & 1) * 4 + (r >> 1) * 8) * 16),
                                 "l"(wg + (size_t)(h * 128 + r * 32 + lane) * (DM * 2) + f * 16) : "memory");
            }
            __nanosleep(FSLEEP);
        }
        asm volatile("cp.async.wait_all;" ::: "memory");
        __syncwarp();
    }
    TS(11);
    const float4* vec = g_oacc + ((lane >> 2) & 3) * 32 + (lane >> 4) * 16 + (lane & 3);
    float acc[2][2][4];
#pragma unroll
    for (int i = 0; i < 16; i++) acc[i >> 3][(i >> 2) & 1][i & 3] = 0.f;
    uint32_t* outp = reinterpret_cast<uint32_t*>(p.out + (lane >> 2) * (2 * DM) + f * 8 + (lane & 3) * 2);
    uint32_t wa = sbase + 4 * SLOT + lane * 16;
    auto project = [&](const float4 (&x)[4], const uint32_t (&w)[4][4]) {
#pragma unroll
        for (int s = 0; s < 4; s++) {
            const uint32_t a[4] = {pack_bf16(x[s].x, x[s].y), 0u, pack_bf16(x[s].z, x[s].w), 0u};
            mma16816(acc[0][s & 1], a, w[s >> 1][(s & 1) * 2], w[s >> 1][(s & 1) * 2 + 1]);
            mma16816(acc[1][s & 1], a, w[2 + (s >> 1)][(s & 1) * 2], w[2 + (s >> 1)][(s & 1) * 2 + 1]);
        }
    };
    int h = 0;
    unsigned n = 0;
    while (h < NH) {
        uint32_t w[4][4];
#pragma unroll
        for (int q = 0; q < 4; q++) ldsm4t(w[q], wa + q * 512);
        int ready;
        while ((ready = ld_acquire_cta_shared(sbase + M_HELP + 20)) <= h) {
            if (h < NH - 3) __nanosleep(100);
            if (++n > (SPIN_LIMIT << 4)) __trap();
        }
        float4 x[4], y[4];
#pragma unroll
        for (int s = 0; s < 4; s++) x[s] = ld_relaxed16(vec + s * 4);
        const bool two = ready > h + 1;
        if (two) {
#pragma unroll
            for (int s = 0; s < 4; s++) y[s] = ld_relaxed16(vec + 128 + s * 4);
        }
        project(x, w);
        if (two) {
#pragma unroll
            for (int q = 0; q < 4; q++) ldsm4t(w[q], wa + 2048 + q * 512);
            project(y, w);
        }
        const int nr = two ? 2 : 1;
        h += nr;
        vec += nr * 128;
        wa += nr * 2048;
        const float o0 = acc[0][0][0] + acc[0][1][0] + __shfl_down_sync(~0u, acc[1][0][0] + acc[1][1][0], 16);
        const float o1 = acc[0][0][1] + acc[0][1][1] + __shfl_down_sync(~0u, acc[1][0][1] + acc[1][1][1], 16);
        asm volatile("{\n.reg .pred p;\nsetp.ne.u32 p, %2, 0;\n@p st.global.u32 [%0], %1;\n}" ::"l"(outp), "r"(pack_bf16(o0, o1)),
                     "r"((uint32_t)(lane < 16 && h == NH)) : "memory");
    }
}

__device__ __forceinline__ void out_fetch(uint32_t sbase, int j, int h) {
    const int lane = threadIdx.x & 31, g = lane >> 2;
    float4 x[4];
#pragma unroll
    for (int b = 0; b < 4; b++) x[b] = ld_relaxed16(&g_oacc[(h * 4 + ((b + g) & 3)) * 32 + lane]);
#pragma unroll
    for (int b = 0; b < 4; b++) {
        const uint32_t a = sbase + F_X + j * FXP + g * 128 + ((b + g) & 3) * 16 + (lane & 3) * 4;
        asm volatile("st.shared.u32 [%0], %1;\nst.shared.u32 [%0 + 64], %2;" ::"r"(a), "r"(pack_bf16(x[b].x, x[b].y)), "r"(pack_bf16(x[b].z, x[b].w)) : "memory");
    }
    asm volatile("fence.proxy.async.shared::cta;" ::: "memory");
}
__device__ __forceinline__ void out_early(uint32_t sbase, int rank, unsigned tag) {
    const int lane = threadIdx.x & 31;
    if (lane < 10) {
        mbar_init(sbase + F_BAR + 16 + lane * 8, lane >= 8 ? 4 : lane == 6 ? 2 : 1);
        if (lane < 8) mbar_expect_tx(sbase + F_BAR + 16 + lane * 8, 16384);
    }
    asm volatile("fence.mbarrier_init.release.cluster;" ::: "memory");
    unsigned n = 0;
#pragma unroll 1
    for (int k = 7; k < 18; k++) {
        const int j = k < 12 ? k : k - 12;
        const int h = j >= 8 ? j - 8 : j % 7 == 0 ? 4 + (rank >> 1) : ((j - 1) % 3 + 1) * 8 + rank;
        if (j >= 8 ? rank >= 4 : j >= 4) {
            while (ld_acquire(&g_vdone[h][0]) < 4 * UPP) { __nanosleep(500); if (++n > SPIN_LIMIT) __trap(); }
            out_fetch(sbase, j, h);
        } else {
            while (true) {
                ulonglong2 v[4];
                bool ok = true;
#pragma unroll
                for (int i = 0; i < 4; i++) v[i] = ld_tagged2(&g_ctx[h * 128 + i * 32 + lane]);
#pragma unroll
                for (int i = 0; i < 4; i++) {
                    ok = ok && (unsigned)(v[i].x >> 32) == tag && (unsigned)(v[i].y >> 32) == tag;
                    asm volatile("st.shared.v2.u32 [%0], {%1,%2};" ::"r"(sbase + F_X + j * FXP + (i * 32 + lane) * 8), "r"((uint32_t)v[i].x), "r"((uint32_t)v[i].y) : "memory");
                }
                if (__all_sync(~0u, ok)) break;
                __nanosleep(500);
                if (++n > SPIN_LIMIT) __trap();
            }
        }
    }
    __syncwarp();
    if (lane == 0) st_release_cta_shared(sbase + M_HELP + 32, 1u);
}
__device__ __forceinline__ void out_late(uint32_t sbase, int rank) {
    unsigned n = 0;
    while (ld_acquire_cta_shared(sbase + M_HELP + 32) == 0) { if (++n > (SPIN_LIMIT << 4)) __trap(); }
    while (ld_acquire(&g_vdone[24 + rank][0]) < 4 * UPP) { if (++n > SPIN_LIMIT) __trap(); }
    TS(12);
    out_fetch(sbase, 6, 24 + rank);
    __syncwarp();
    if ((threadIdx.x & 31) == 0) asm volatile("mbarrier.arrive.shared::cta.b64 _, [%0];" ::"r"(sbase + F_BAR + 16 + 6 * 8) : "memory");
    TS(13);
}
__device__ __forceinline__ void out_project(uint32_t sbase, int rank, int w) {
    const int lane = threadIdx.x & 31, g = lane >> 2, t = lane & 3;
    unsigned n = 0;
    while (ld_acquire_cta_shared(sbase + M_HELP + 32) == 0) { __nanosleep(500); if (++n > SPIN_LIMIT) __trap(); }
    asm volatile("barrier.cluster.wait.acquire.aligned;" ::: "memory");
    uint32_t rdst[2], rbar[2];
#pragma unroll
    for (int e = 0; e < 2; e++) {
        rdst[e] = mapa(sbase + F_RECV + rank * 256 + g * 32 + t * 16, 4 * e + w);
        rbar[e] = mapa(sbase + F_BAR, 4 * e + w);
    }
    while (ld_acquire_cta_shared(sbase + M_HELP + 28) == 0) { __nanosleep(200); if (++n > SPIN_LIMIT) __trap(); }
    const uint32_t da = (1u << 16) | (((sbase + F_W) & 0x3ffff) >> 4), db = (4u << 16) | (((sbase + F_X) & 0x3ffff) >> 4);
    float d[2][4] = {0.f, 0.f, 0.f, 0.f, 0.f, 0.f, 0.f, 0.f};
#pragma unroll
    for (int i = 0; i < 7; i++) {
        const int e = i >> 2;
        mbar_first(sbase + F_BAR + 16 + i * 8);
        asm volatile("wgmma.fence.sync.aligned;" ::: "memory");
        if (i == 0) {
            wgmma_k64(d[0], da, db + (rank & 1) * 32, 0);
            wgmma_k64(d[1], da + 512, db + 7 * (FXP / 16) + (rank & 1) * 32, 0);
        } else {
            wgmma_k64(d[e], da + (i % 6) * 1024, db + i * (FXP / 16), 1);
            wgmma_k64(d[e], da + (i % 6) * 1024 + 512, db + i * (FXP / 16) + 32, 1);
        }
        asm volatile("wgmma.commit_group.sync.aligned;" ::: "memory");
        if (i < 2 || i % 3 == 0)
            asm volatile("wgmma.wait_group.sync.aligned 0;" : "+f"(d[e][0]), "+f"(d[e][1]), "+f"(d[e][2]), "+f"(d[e][3])::"memory");
        if (i < 2) {
            asm volatile("{\n.reg .pred p;\nsetp.eq.u32 p, %1, 0;\n@p mbarrier.arrive.shared::cta.b64 _, [%0];\n}"
                         ::"r"(sbase + F_BAR + 80 + i * 8), "r"(lane) : "memory");
        } else if (i % 3 == 0) {
            if (t < 2)
                asm volatile("st.async.weak.shared::cluster.mbarrier::complete_tx::bytes.v4.f32 [%0], {%1,%2,%3,%4}, [%5];"
                             ::"r"(rdst[e]), "f"(d[e][0]), "f"(d[e][1]), "f"(d[e][2]), "f"(d[e][3]), "r"(rbar[e]) : "memory");
            __syncwarp();
        }
    }
}
__device__ __forceinline__ void out_issue(const Params& p, uint32_t sbase, int c, int rank, uint64_t pol) {
    unsigned n = 0;
    while (ld_acquire_cta_shared(sbase + M_HELP + 32) == 0) { __nanosleep(500); if (++n > SPIN_LIMIT) __trap(); }
#pragma unroll
    for (int i = 0; i < 6; i++) asm volatile("prefetch.tensormap [%0];" ::"l"(&p.tm_out[i >> 1][i & 1]) : "memory");
    uint32_t t0;
    while ((t0 = ld_acquire_cta_shared(sbase + M_HELP + 28)) == 0) { __nanosleep(100); if (++n > SPIN_LIMIT) __trap(); }
#pragma unroll
    for (int i = 0; i < 8; i++) {
        const uint32_t dst = sbase + F_W + (i % 6) * 16384, bar = sbase + F_BAR + 16 + i * 8;
        if (i >= 6) mbar_wait(sbase + F_BAR + 32 + i * 8, 0);
        for (int k = 0; k < 4096 && (int)(now_ns() - t0) < 0; k++) {}
        if (i == 0) {
            TS(16);
            tma4d(dst, &p.tm_out[0][0], c * 64, (rank & 1) * 4, 4 + (rank >> 1), bar, pol);
            tma4d(dst + 8192, &p.tm_out[0][1], c * 64, (rank & 1) * 4, 4 + (rank >> 1), bar, pol);
        } else if (i < 7) {
            tma4d(dst, &p.tm_out[1][i >> 2], c * 64, 0, ((i - 1) % 3 + 1) * 8 + rank, bar, pol);
        } else {
#pragma unroll
            for (int q = 0; q < 2; q++) {
                const int h = ((q + rank) & 1) * 2;
                tma4d(dst + h * 4096, &p.tm_out[2][rank >> 2], c * 64 + (rank & 3) * 16, 0, h, bar, pol);
            }
        }
        t0 += i == 6 ? FP - FN : FP;
    }
    TS(17);
}
__device__ __forceinline__ void out_final(const Params& p, uint32_t sbase, int c, int rank, int hf) {
    const int lane = threadIdx.x & 31, g = lane >> 2, t = lane & 3;
    unsigned n = 0;
    while (ld_acquire_cta_shared(sbase + M_HELP + 32) == 0) { if (++n > (SPIN_LIMIT << 4)) __trap(); }
    uint32_t bf[16][2];
#pragma unroll
    for (int s = 0; s < 16; s++) {
        const uint32_t a = sbase + F_X + (8 + 2 * (g >> 2) + (s >> 3)) * FXP + (s & 7) * 128 + (g & 3) * 16 + t * 4;
        bf[s][0] = lds32(a);
        bf[s][1] = lds32(a + 64);
    }
    __nv_bfloat16* dst = p.out + (2 * (t & 1) + (t >> 1)) * (2 * DM) + (rank < 4 ? DM : 0) + c * 64 + (rank & 3) * 16 + hf * 8 + g;
    uint32_t src = sbase + F_RECV + g * 32 + (t & 1) * 16 + hf * 8 + (t >> 1) * 4;
    uint32_t wa = sbase + F_W + 16384 + ((lane >> 3) & 1) * 8192 + ((lane & 7) + (lane >> 4) * 8) * 32 + ((hf ^ (lane >> 2)) & 1) * 16;
    wa += bf[15][1] & (gridDim.x >> 24);
    asm volatile("" : "+l"(dst), "+r"(src), "+r"(wa));
    float x[8];
    auto partials = [&]() {
        mbar_first_cluster(sbase + F_BAR);
#pragma unroll
        for (int i = 0; i < 8; i++) asm volatile("ld.shared.f32 %0, [%1];" : "=f"(x[i]) : "r"(src + i * 256) : "memory");
    };
    const bool pre = rank < 4;
    if (pre) partials();
    mbar_first(sbase + F_BAR + 16 + 7 * 8);
    uint32_t a[16][4];
    float acc[4][4];
#pragma unroll
    for (int i = 0; i < 16; i++) acc[i >> 2][i & 3] = 0.f;
#pragma unroll
    for (int s = 0; s < 16; s++) ldsm4t(a[s], wa + s * 512);
#pragma unroll
    for (int s = 0; s < 16; s++) mma16816(acc[s & 3], a[s], bf[s][0], bf[s][1]);
    float y[4];
#pragma unroll
    for (int i = 0; i < 4; i++) y[i] = (acc[0][i] + acc[1][i]) + (acc[2][i] + acc[3][i]);
    float v = __shfl_xor_sync(~0u, (t & 2) ? y[2] : y[1], 2);
    if (!pre) partials();
    v = (v + ((t & 2) ? y[3] : y[0])) + (((x[0] + x[1]) + (x[2] + x[3])) + ((x[4] + x[5]) + (x[6] + x[7])));
    asm volatile("{\n.reg .b16 h;\ncvt.rn.bf16.f32 h, %1;\nst.global.b16 [%0], h;\n}" ::"l"(dst), "f"(v) : "memory");
}

constexpr int BS_WUK = 5, BS_Q = 9, BS_CKV = 11, BS_PART = 27, BS_WUV = 29, BS_END = 33;

__device__ __noinline__ void b_issue(const Params& p, int n, int bi, uint32_t sbase, uint64_t pol) {
    if (n >= BS_END || (n >= BS_Q && n < BS_CKV) || (n >= BS_PART && n < BS_WUV)) return;
    const uint32_t bar = sbase + M_BAR + (NSLOT + n % BRING) * 8;
    const CUtensorMap* tm;
    int row, panel = 2 * bi;
    if (n < BS_WUK) { tm = &p.tm_wq; row = n * 128; }
    else if (n < BS_Q) { tm = &p.tm_wuk; row = (n - BS_WUK) * 128; }
    else if (n < BS_PART) {
        tm = &p.tm_ckv; panel = 0;
        row = (bi >> 3) * SK + ((n - BS_CKV) * 8 + (bi & 7)) * 32;
    }
    else { tm = &p.tm_wuv; row = (n - BS_WUV) * 128; }
    mbar_expect_tx(bar, n == 0 ? 32768 + 4 * 1152 : 32768);
    tma3d(sbase + (n % BRING) * SLOT, tm, 0, row, panel, bar, pol);
}
__device__ __forceinline__ void b_issue_xchg(int n, const void* src, uint32_t sbase, uint64_t pol) {
    asm volatile("fence.proxy.async;" ::: "memory");
#pragma unroll
    for (int i = 0; i < 2; i++) {
        const uint32_t bar = sbase + M_BAR + (NSLOT + (n + i) % BRING) * 8;
        mbar_expect_tx(bar, 32768);
        bulk_load(sbase + ((n + i) % BRING) * SLOT, reinterpret_cast<const char*>(src) + i * 32768, 32768, bar, pol);
    }
}
__device__ __forceinline__ void b_wait(int n, uint32_t sbase) {
    mbar_wait(sbase + M_BAR + (NSLOT + n % BRING) * 8, (n / BRING) & 1);
}

__device__ __noinline__ void b_gemm(const Params& p, uint32_t sbase, int n0, int n1, int ktot, uint32_t xh, uint32_t xl, int pitch,
                                    int bi, uint64_t pol) {
    const int tid = threadIdx.x, warp = tid >> 5, lane = tid & 31, g = lane >> 2, t = lane & 3;
    const uint32_t woff = (warp >> 2) * 16384 + (lane & 15) * 128 + ((((warp & 3) * 2 + (lane >> 4)) ^ (lane & 7)) * 16);
    const uint32_t xoff = (g & 3) * pitch + t * 4;
    float acc[2][4];
#pragma unroll
    for (int i = 0; i < 8; i++) acc[i >> 2][i & 3] = 0.f;
#pragma unroll 1
    for (int n = n0; n < n1; n++) {
        b_wait(n, sbase);
        const uint32_t slot = sbase + (n % BRING) * SLOT + woff;
        const int k0 = (n - n0) * 128;
        const int ns = min(8, (ktot - k0) >> 4);
#pragma unroll 2
        for (int s = 0; s < ns; s++) {
            uint32_t a[4], w[4];
            const uint32_t xo = xoff + (k0 + 16 * s) * 2;
            a[0] = lds32(xh + xo); a[2] = lds32(xh + xo + 16);
            a[1] = xl ? lds32(xl + xo) : 0u; a[3] = xl ? lds32(xl + xo + 16) : 0u;
            ldsm4t(w, slot + s * 2048);
            mma16816(acc[0], a, w[0], w[1]);
            mma16816(acc[1], a, w[2], w[3]);
        }
        __syncthreads();
        if (tid == 0) b_issue(p, n + BD, bi, sbase, pol);
    }
    if (g < 4) {
#pragma unroll
        for (int j = 0; j < 2; j++)
            asm volatile("st.shared.u32 [%0], %1;" ::"r"(sbase + M_QB + g * QP + (warp * 16 + j * 8 + t * 2) * 2),
                         "r"(pack_bf16(acc[j][0] + acc[j][2], acc[j][1] + acc[j][3])) : "memory");
    }
    __syncthreads();
}

__device__ __forceinline__ void b_exchange(unsigned* c, int n, const void* src, uint32_t sbase, uint64_t pol) {
    TS(n == BS_Q ? 24 : 28);
    __syncthreads();
    if (threadIdx.x == 0) {
        TS(n == BS_Q ? 25 : 29);
        fence_gpu();
        TS(n == BS_Q ? 26 : 30);
        red_add_u32(c, 1u);
        wait_count(c, NBCTA);
        TS(n == BS_Q ? 27 : 31);
        b_issue_xchg(n, src, sbase, pol);
    }
}

template <bool CLU>
__device__ __noinline__ void b_chain(const Params& p, char* smem, uint32_t sbase, int bi, unsigned epoch, uint64_t pol) {
    const int tid = threadIdx.x, warp = tid >> 5, lane = tid & 31, g = lane >> 2, t = lane & 3;
    unsigned (*ctl)[32] = g_ctl[epoch & 1];
    float* red = reinterpret_cast<float*>(smem + 5 * SLOT);
    b_gemm(p, sbase, 0, BS_WUK, DM, sbase + M_XB, 0, XP, bi, pol);
    TS(6);
    {
        uint32_t Q[16];
#pragma unroll
        for (int c = 0; c < 16; c++) Q[c] = lds32(sbase + M_QB + (g & 3) * QP + c * 16 + t * 4);
        float* qa = reinterpret_cast<float*>(smem + M_QA);
#pragma unroll 1
        for (int n = BS_WUK; n < BS_Q; n++) {
            b_wait(n, sbase);
            const uint32_t base = sbase + (n % BRING) * SLOT + (warp * 16 + (lane & 15)) * 128;
            float d[2][4];
#pragma unroll
            for (int i = 0; i < 8; i++) d[i >> 2][i & 3] = 0.f;
#pragma unroll
            for (int s = 0; s < 8; s++) {
                uint32_t a[4];
                ldsm4(a, base + (s >> 2) * 16384 + (((2 * (s & 3) + (lane >> 4)) ^ (lane & 7)) * 16));
                mma16816(d[s & 1], a, Q[2 * s], Q[2 * s + 1]);
            }
            const int c = (n - BS_WUK) * 128 + warp * 16 + g + 8 * (t >> 1);
            qa[(2 * (t & 1)) * 512 + c] = (t & 2) ? d[0][2] + d[1][2] : d[0][0] + d[1][0];
            qa[(2 * (t & 1) + 1) * 512 + c] = (t & 2) ? d[0][3] + d[1][3] : d[0][1] + d[1][1];
            __syncthreads();
            if (tid == 0) b_issue(p, n + BD, bi, sbase, pol);
        }
#pragma unroll 1
        for (int r = 0; r < 2; r++) {
            const int id = tid + r * 256;
            const int b = id >> 7, c0 = ((id >> 2) & 31) * 16 + (id & 3) * 2;
            const float2 u0 = *reinterpret_cast<const float2*>(qa + b * 512 + c0);
            const float2 u1 = *reinterpret_cast<const float2*>(qa + b * 512 + c0 + 8);
            const uint32_t h0 = pack_bf16(u0.x, u0.y), h1 = pack_bf16(u1.x, u1.y);
            const uint32_t l0 = pack_bf16(u0.x - bf_lo(h0), u0.y - bf_hi(h0)), l1 = pack_bf16(u1.x - bf_lo(h1), u1.y - bf_hi(h1));
            g_qabs[((id >> 2) * 4 + (bi >> 3)) * 32 + (bi & 7) * 4 + (id & 3)] = make_uint4(h0, l0, h1, l1);
        }
    }
    b_exchange(&ctl[C_BBAR][0], BS_Q, &g_qabs[(bi >> 3) * 4096], sbase, pol);
    {
        uint32_t qf[4][4][4];
        b_wait(BS_Q + (warp >> 2), sbase);
        TS(7);
        {
            const uint4* qs = reinterpret_cast<const uint4*>(smem + ((BS_Q + (warp >> 2)) % BRING) * SLOT) + (warp & 3) * 512 + lane;
#pragma unroll
            for (int s = 0; s < 4; s++)
#pragma unroll
                for (int i = 0; i < 4; i++) {
                    const uint4 v = qs[(s * 4 + i) * 32];
                    qf[i][s][0] = v.x; qf[i][s][1] = v.y; qf[i][s][2] = v.z; qf[i][s][3] = v.w;
                }
        }
        __syncthreads();
        if (tid == 0) { b_issue(p, BS_Q + BD, bi, sbase, pol); b_issue(p, BS_Q + 1 + BD, bi, sbase, pol); }
        float acc[2][8][4];
#pragma unroll
        for (int i = 0; i < 2; i++)
#pragma unroll
            for (int j = 0; j < 8; j++) { acc[i][j][0] = acc[i][j][1] = acc[i][j][2] = acc[i][j][3] = 0.f; }
        float mrun = -INFINITY, lrun = 0.f;
        const int head = tid >> 3, kq = tid & 7;
        float* alpha = reinterpret_cast<float*>(smem + M_ALPHA);
        for (int n = BS_CKV; n < BS_PART; n++) {
            b_wait(n, sbase);
            const uint32_t slot = sbase + (n % BRING) * SLOT;
            float sc[4][4][4];
#pragma unroll
            for (int i = 0; i < 4; i++)
#pragma unroll
                for (int j = 0; j < 4; j++) { sc[i][j][0] = sc[i][j][1] = sc[i][j][2] = sc[i][j][3] = 0.f; }
#pragma unroll
            for (int j = 0; j < 4; j++)
#pragma unroll
                for (int sp = 0; sp < 2; sp++) {
                    uint32_t bf[4];
                    ldsm4(bf, slot + warp * 4096 + (8 * j + (lane & 7)) * 128 + (((4 * sp + (lane >> 3)) ^ (lane & 7)) * 16));
#pragma unroll
                    for (int i = 0; i < 4; i++) {
                        mma16816(sc[i][j], qf[i][2 * sp], bf[0], bf[1]);
                        mma16816(sc[i][j], qf[i][2 * sp + 1], bf[2], bf[3]);
                    }
                }
#pragma unroll
            for (int i = 0; i < 4; i++)
#pragma unroll
                for (int j = 0; j < 4; j++)
                    *reinterpret_cast<float2*>(red + warp * 1024 + (8 * i + g) * 32 + ((8 * j) ^ (8 * (g & 3))) + 2 * t) =
                        make_float2(sc[i][j][0] + sc[i][j][2], sc[i][j][1] + sc[i][j][3]);
            __syncthreads();
            if (tid == 0 && n > BS_CKV) b_issue(p, n - 1 + BD, bi, sbase, pol);
            {
                float4 s = make_float4(0.f, 0.f, 0.f, 0.f);
#pragma unroll
                for (int w = 0; w < 8; w++) {
                    const float4 v = *reinterpret_cast<const float4*>(red + w * 1024 + head * 32 + ((4 * kq) ^ (8 * (head & 3))));
                    s.x += v.x; s.y += v.y; s.z += v.z; s.w += v.w;
                }
                const uint32_t r0 = pack_bf16(s.x, s.y), r1 = pack_bf16(s.z, s.w);
                const uint32_t s0 = pack_bf16(bf_lo(r0) * SCALE, bf_hi(r0) * SCALE);
                const uint32_t s1 = pack_bf16(bf_lo(r1) * SCALE, bf_hi(r1) * SCALE);
                const float f0 = bf_lo(s0), f1 = bf_hi(s0), f2 = bf_lo(s1), f3 = bf_hi(s1);
                float mx = fmaxf(fmaxf(f0, f1), fmaxf(f2, f3));
                mx = fmaxf(mx, __shfl_xor_sync(~0u, mx, 1));
                mx = fmaxf(mx, __shfl_xor_sync(~0u, mx, 2));
                mx = fmaxf(mx, __shfl_xor_sync(~0u, mx, 4));
                const float mnew = fmaxf(mrun, mx);
                const float al = expsub(mrun, mnew);
                const float p0 = expsub(f0, mnew), p1 = expsub(f1, mnew), p2 = expsub(f2, mnew), p3 = expsub(f3, mnew);
                lrun = lrun * al + ((p0 + p1) + (p2 + p3));
                mrun = mnew;
                *reinterpret_cast<uint2*>(smem + M_P + head * 80 + kq * 8) = make_uint2(pack_bf16(p0, p1), pack_bf16(p2, p3));
                if (kq == 0) alpha[head] = al;
            }
            __syncthreads();
            {
                uint32_t pf[2][2][4];
#pragma unroll
                for (int i = 0; i < 2; i++)
#pragma unroll
                    for (int ks = 0; ks < 2; ks++)
                        ldsm4(pf[i][ks], sbase + M_P + (16 * i + (lane & 15)) * 80 + (16 * ks + 8 * (lane >> 4)) * 2);
#pragma unroll
                for (int i = 0; i < 2; i++) {
                    const float a0 = alpha[16 * i + g], a1 = alpha[16 * i + 8 + g];
#pragma unroll
                    for (int j = 0; j < 8; j++) { acc[i][j][0] *= a0; acc[i][j][1] *= a0; acc[i][j][2] *= a1; acc[i][j][3] *= a1; }
                }
#pragma unroll
                for (int j = 0; j < 8; j++) {
                    uint32_t bf[4];
                    ldsm4t(bf, slot + warp * 4096 + lane * 128 + ((j ^ (lane & 7)) * 16));
#pragma unroll
                    for (int i = 0; i < 2; i++) {
                        mma16816(acc[i][j], pf[i][0], bf[0], bf[1]);
                        mma16816(acc[i][j], pf[i][1], bf[2], bf[3]);
                    }
                }
            }
        }
        __syncthreads();
        if (tid == 0) b_issue(p, BS_PART - 1 + BD, bi, sbase, pol);
        lrun += __shfl_xor_sync(~0u, lrun, 1);
        lrun += __shfl_xor_sync(~0u, lrun, 2);
        lrun += __shfl_xor_sync(~0u, lrun, 4);
        if (kq == 0) g_bml[head * NBCTA + bi] = make_float2(mrun, lrun);
#pragma unroll
        for (int i = 0; i < 2; i++)
#pragma unroll
            for (int j = 0; j < 8; j++) {
                g_bpart[((16 * i + g) * NBCTA + bi) * 256 + warp * 32 + j * 4 + t] = make_float2(acc[i][j][0], acc[i][j][1]);
                g_bpart[((16 * i + 8 + g) * NBCTA + bi) * 256 + warp * 32 + j * 4 + t] = make_float2(acc[i][j][2], acc[i][j][3]);
            }
    }
#pragma unroll 1
    for (int i = tid; i < NH * 36 && !(CLU); i += 256) g_outb[bi * NH * 36 + i] = make_uint4(0u, epoch, 0u, epoch);
    b_exchange(&ctl[C_BBAR + 1][0], BS_PART, &g_bpart[bi * NBCTA * 256], sbase, pol);
    {
        float* omega = reinterpret_cast<float*>(smem + M_OMEGA);
        if (warp == 0) {
            __syncwarp();
            const uint2 ml = ld_relaxed8(&g_bml[bi * NBCTA + lane]);
            const float ms = __uint_as_float(ml.x);
            float m = ms;
            m = fmaxf(m, __shfl_xor_sync(~0u, m, 1));
            m = fmaxf(m, __shfl_xor_sync(~0u, m, 2));
            m = fmaxf(m, __shfl_xor_sync(~0u, m, 4));
            const float w = expsub(ms, m);
            float l = w * __uint_as_float(ml.y);
            l += __shfl_xor_sync(~0u, l, 1);
            l += __shfl_xor_sync(~0u, l, 2);
            l += __shfl_xor_sync(~0u, l, 4);
            omega[lane] = w / l;
        }
        __syncthreads();
        b_wait(BS_PART, sbase);
        b_wait(BS_PART + 1, sbase);
#pragma unroll 1
        for (int b = 0; b < 4; b++) {
            const float2* ps = reinterpret_cast<const float2*>(smem + ((BS_PART + (b >> 1)) % BRING) * SLOT) + (b & 1) * 2048 + tid;
            float c0 = 0.f, c1 = 0.f;
#pragma unroll
            for (int s = 0; s < 8; s++) {
                const float w = omega[b * 8 + s];
                const float2 v = ps[s * 256];
                c0 = fmaf(w, v.x, c0);
                c1 = fmaf(w, v.y, c1);
            }
            const uint32_t hi = pack_bf16(c0, c1);
            *reinterpret_cast<uint32_t*>(smem + M_CH + b * CP + tid * 4) = hi;
            *reinterpret_cast<uint32_t*>(smem + M_CL + b * CP + tid * 4) = pack_bf16(c0 - bf_lo(hi), c1 - bf_hi(hi));
        }
        __syncthreads();
        if (tid == 0) { b_issue(p, BS_PART + BD, bi, sbase, pol); b_issue(p, BS_PART + 1 + BD, bi, sbase, pol); }
    }
    b_gemm(p, sbase, BS_WUV, BS_END, 512, sbase + M_CH, sbase + M_CL, CP, bi, pol);
    TS(12);
    if (CLU) {
        if (tid < 128) {
            const uint32_t xo = sbase + M_QB + ((tid >> 1) & 3) * QP + (tid >> 3) * 16 + (tid & 1) * 8;
            st_tagged2(&g_ctx[bi * 128 + tid], __uint_as_float(lds32(xo)), __uint_as_float(lds32(xo + 4)), epoch + 1);
        }
        return;
    }
    if (tid == 0) {
#pragma unroll 1
        for (int i = 0; i < 4; i++) {
            mbar_expect_tx(sbase + M_BAR + i * 8, 36864);
            tma3d(sbase + i * 36864, &p.tm_wo, 0, bi * 128 + i * 32, 0, sbase + M_BAR + i * 8, pol);
        }
    }
    TS(8);
    {
        float acc[9][4];
#pragma unroll
        for (int j = 0; j < 9; j++) { acc[j][0] = acc[j][1] = acc[j][2] = acc[j][3] = 0.f; }
#pragma unroll 1
        for (int i = 0; i < 4; i++) {
            const uint32_t xo = sbase + M_QB + (g & 3) * QP + i * 64 + t * 4;
            const uint32_t a0[4] = {lds32(xo), 0u, lds32(xo + 16), 0u}, a1[4] = {lds32(xo + 32), 0u, lds32(xo + 48), 0u};
            mbar_wait(sbase + M_BAR + i * 8, 0);
#pragma unroll
            for (int j = 0; j < 9; j++) {
                const int nt = warp * 9 + j;
                uint32_t w[4];
                ldsm4t(w, sbase + i * 36864 + (nt >> 3) * 4096 + lane * 128 + (((nt & 7) ^ (lane & 7)) * 16));
                mma16816(acc[j], a0, w[0], w[1]);
                mma16816(acc[j], a1, w[2], w[3]);
            }
        }
        if (g < 4) {
#pragma unroll
            for (int j = 0; j < 9; j++) {
                const int c2 = (warp * 9 + j) * 4 + t;
                st_tagged2(&g_outb[((c2 / 9) * NH + bi) * 36 + g * 9 + c2 % 9], acc[j][0], acc[j][1], epoch + 1);
            }
        }
    }
    TS(9);
    {
        const uint4* src = g_outb + (bi * NH + (tid >> 3)) * 36 + (tid & 7);
        float2* part = reinterpret_cast<float2*>(red);
        unsigned n = 0;
        while (true) {
            ulonglong2 v[5];
            bool ok = true;
#pragma unroll
            for (int i = 0; i < 5; i++)
                if (i < 4 || (tid & 7) < 4) v[i] = ld_tagged2(src + i * 8);
#pragma unroll
            for (int i = 0; i < 5; i++)
                if (i < 4 || (tid & 7) < 4) {
                    ok = ok && (unsigned)(v[i].x >> 32) == epoch + 1 && (unsigned)(v[i].y >> 32) == epoch + 1;
                    part[(tid >> 3) * 36 + (tid & 7) + i * 8] = make_float2(__uint_as_float((unsigned)v[i].x), __uint_as_float((unsigned)v[i].y));
                }
            if (ok) break;
            __nanosleep(400);
            if (++n > SPIN_LIMIT) __trap();
        }
        __syncthreads();
        if (tid < 36) {
            float s0 = 0.f, s1 = 0.f;
#pragma unroll 8
            for (int h = 0; h < NH; h++) { const float2 v = part[h * 36 + tid]; s0 += v.x; s1 += v.y; }
            *reinterpret_cast<uint32_t*>(p.out + (tid / 9) * 2 * DM + DM + bi * 18 + (tid % 9) * 2) = pack_bf16(s0, s1);
        }
    }
    TS(10);
}

template <bool CLU>
__global__ void __launch_bounds__(256, 1) fused_decode_kernel(const __grid_constant__ First f, const __grid_constant__ Params p) {
    extern __shared__ __align__(1024) char smem_raw[];
    const uint32_t sbase = (smem_u32(smem_raw) + 1023u) & ~1023u;
    char* smem = smem_raw + (sbase - smem_u32(smem_raw));
    const int tid = threadIdx.x, warp = tid >> 5, lane = tid & 31;
    asm volatile("{\n.reg .pred p;\nsetp.ne.u32 p, %1, 0;\n@p prefetch.global.L2 [%0];\n}"
                 ::"l"(f.ptr[tid >> 10] + (blockIdx.x * 8 + warp) * 8192 + lane * 128), "r"((uint32_t)(blockIdx.x < DM / 8 && lane < 16)) : "memory");
    const char* eptr = f.ptr[3 + (tid >> 10)];
    const int blk = CLU ? cluster_role(blockIdx.x) : blockIdx.x;
    const bool isB = CLU ? blk < NBCTA : (blk & 3) == 0 && (blk >> 2) < NBCTA;
    const int bi = CLU ? blk : blk >> 2;
    const int nb = CLU ? blk - NBCTA : blk - min(NBCTA, (blk + 3) >> 2);
    const int nblk = CLU ? 8 * MINCL : gridDim.x, nnb = nblk - NBCTA;
    const int nstatic = nnb * (NW + XW);
    uint64_t pol, poln;
    asm volatile("createpolicy.fractional.L2::evict_first.b64 %0, 1.0;" : "=l"(pol));
    asm volatile("createpolicy.fractional.L2::evict_normal.b64 %0, 1.0;" : "=l"(poln));
    const uint32_t wbar = sbase + M_BAR + warp * 8, wslot = sbase + warp * SLOT;
    const bool hold = blk < 16;
    const uint32_t jbar = sbase + M_BAR + (NSLOT + BRING) * 8, fbar = sbase + M_BAR + 4 * 8;
    if (warp < 4) {
        if (lane == 0) {
            if (warp == 0) {
                mbar_init(jbar, 1);
                asm volatile("fence.mbarrier_init.release.cluster;" ::: "memory");
                mbar_expect_tx(jbar, 36864 + 4 * 1152);
                if (CLU || blk < 128) tma3d(sbase + J0W, &p.tm_j0, blk * 32, 0, 0, jbar, poln);
            } else if (warp & 1) {
                if (warp & 2) {
#pragma unroll
                    for (int i = 0; i < NSLOT + BRING; i++) mbar_init(sbase + M_BAR + i * 8, 1);
                    mbar_expect_tx(fbar, NEARLY * TILE_BYTES);
                } else if (CLU && !isB) {
                    mbar_init(sbase + F_BAR, 1);
                    mbar_expect_tx(sbase + F_BAR, 2048);
                }
                asm volatile("fence.mbarrier_init.release.cluster;" ::: "memory");
            } else {
#pragma unroll
                for (int i = 0; i < 4; i++) asm volatile("st.shared.v4.u32 [%0], {%1,%1,%1,%1};" ::"r"(sbase + M_HELP + i * 16), "r"(0) : "memory");
            }
        }
    } else if (blockIdx.x >= DM / 8) {
        if (tid == 128) {
            asm volatile("prefetch.tensormap [%0];" ::"l"(&p.tm_j0) : "memory");
            asm volatile("prefetch.tensormap [%0];" ::"l"(&p.tm_wq) : "memory");
        } else if (blockIdx.x == DM / 8 + 4 && tid >= 220) {
            asm volatile("prefetch.global.L2 [%0];" ::"l"(f.ptr[2 + (tid >> 10)] + (tid - 220) * 128) : "memory");
        }
    }
    __syncthreads();
    if (tid == 128) {
        if (CLU || blk < 128) bulk_load(sbase + M_XA, f.ptr[2], 4608, jbar, poln);
        if (!isB && !hold) bulk_load(sbase, block_src(f.ptr[1], unit_block(nb * NEARLY)), NEARLY * TILE_BYTES, fbar, pol);
    }
    const int u0 = ((warp / NEARLY) * nnb + nb) * NEARLY + warp % NEARLY;
    unsigned epoch = 0;
    if (lane == 0) epoch = ld_relaxed4(eptr);
    TS(0);
    if (CLU && (unsigned)nb < NFIN) asm volatile("barrier.cluster.arrive.relaxed.aligned;" ::: "memory");
    if ((warp >> 1) == 2 && blk < 128) st_relaxed64(&g_qll[((tid - 128) >> 4) * 2048 + blk * 16 + (tid & 15)], 0ull);
    if (isB || warp >= NW + XW) epoch = __shfl_sync(~0u, epoch, 0);
    if (isB && tid == 96) {
        if (hold) { unsigned n = 0; while (ld_acquire_cta_shared(sbase + M_HELP + 24) < 2) { if (++n > (SPIN_LIMIT << 4)) __trap(); } }
#pragma unroll 1
        for (int b = 0; b < 4; b++) bulk_load(sbase + M_XB + b * XP, p.xb + b * DM, 1152, sbase + M_BAR + NSLOT * 8, pol);
#pragma unroll 1
        for (int n = 0; n < BD; n++) b_issue(p, n, bi, sbase, pol);
    }
    if (warp >= 4 && blk < 128) {
        const int g = lane >> 2, t = lane & 3, j = tid - 128;
#pragma unroll 1
        for (int sl = blk, ph = 0;; sl += 128 - nblk, ph = 1) {
        mbar_wait(jbar, ph);
        TS(13);
        float acc[4][4];
#pragma unroll
        for (int i = 0; i < 16; i++) acc[i >> 2][i & 3] = 0.f;
        const uint32_t wa = sbase + J0W + ((warp - 4) * 144 + (lane & 15)) * 64;
        const uint32_t sw = (lane >> 1) & 3, xa = sbase + M_XA + (g & 3) * 1152 + (warp - 4) * 288 + t * 4;
#pragma unroll 3
        for (int s = 0; s < 9; s++) {
            const uint32_t a[4] = {lds32(xa + s * 32), 0u, lds32(xa + s * 32 + 16), 0u};
            uint32_t w0[4], w1[4];
            ldsm4t(w0, wa + s * 1024 + (((lane >> 4) ^ sw) * 16));
            ldsm4t(w1, wa + s * 1024 + (((2 + (lane >> 4)) ^ sw) * 16));
            mma16816(acc[0], a, w0[0], w0[1]);
            mma16816(acc[1], a, w0[2], w0[3]);
            mma16816(acc[2], a, w1[0], w1[1]);
            mma16816(acc[3], a, w1[2], w1[3]);
        }
        float2* j0 = reinterpret_cast<float2*>(smem + M_J0);
        if (g < 4) {
#pragma unroll
            for (int i = 0; i < 4; i++) j0[(warp - 4) * 64 + g * 16 + i * 4 + t] = make_float2(acc[i][0], acc[i][1]);
        }
        asm volatile("bar.sync 1, 128;" ::: "memory");
        const bool again = sl == blk && blk + 128 - nblk >= nblk;
        if (again && tid == 224) {
            mbar_expect_tx(jbar, 36864);
            tma3d(sbase + J0W, &p.tm_j0, (blk + 128 - nblk) * 32, 0, 0, jbar, pol);
        }
        if (warp < 6) {
            const float2 v0 = j0[j], v1 = j0[64 + j], v2 = j0[128 + j], v3 = j0[192 + j];
            st_relaxed64(&g_qll[(j >> 4) * 2048 + sl * 16 + (j & 15)],
                         (unsigned long long)pack_bf16((v0.x + v1.x) + (v2.x + v3.x), (v0.y + v1.y) + (v2.y + v3.y)) |
                             ((unsigned long long)(epoch + 1) << 32));
            __syncwarp();
            if (lane == 0) asm volatile("red.relaxed.cta.shared::cta.add.u32 [%0], 1;" ::"r"(sbase + M_HELP + 24) : "memory");
        } else if (warp == 7) {
            if (blk < C_LINES) g_ctl[(epoch & 1) ^ 1][blk][lane] = 0;
        }
        TS(1);
        if (!again) break;
        asm volatile("bar.sync 1, 128;" ::: "memory");
        }
    }
    if (isB) {
        b_chain<CLU>(p, smem, sbase, bi, epoch, pol);
        return;
    }
    if (warp < NW + XW) {
        a_worker<CLU>(p, u0, warp >= NW + (((nb * 5) & 7) < (CLU ? X3C : X3) ? 1 : 0), hold, nstatic, wslot, wbar, warp < NEARLY && !hold ? fbar : wbar,
                      sbase + M_HELP, epoch, pol);
        if (CLU && nb < NFIN) {
            if (tid == 96) out_issue(p, sbase, nb >> 3, nb & 7, pol);
            __syncwarp();
            if (warp & 1) out_final(p, sbase, nb >> 3, nb & 7, warp >> 1);
            else if (warp == 0) out_late(sbase, nb & 7);
        }
        return;
    } else if (warp == 7) {
#pragma unroll 1
        for (int i = nb; i < 4 * NH; i += nnb) g_oacc[i * 32 + lane] = make_float4(0.f, 0.f, 0.f, 0.f);
        if (nb < NREP * NH) g_vdone[nb][lane] = 0;
        __syncwarp();
        k_helper(sbase + M_HELP, epoch);
        if (nb == 0 && lane == 0) g_epoch = epoch + 1;
        __syncwarp();
        if (CLU && nb < NFIN) out_early(sbase, nb & 7, epoch + 1);
    } else if (CLU) {
    } else if (warp == 6 && nb < NFIN) {
        finisher(p, sbase, nb);
        TS(4);
    } else if (warp >= 6 - NPOLL && nb < NFIN) {
        v_poller(sbase, nb, warp - (6 - NPOLL));
    }
    if (CLU && nb < NFIN) out_project(sbase, nb & 7, warp - 4);
}

}

typedef CUresult (*EncodeFn)(CUtensorMap*, CUtensorMapDataType, cuuint32_t, void*, const cuuint64_t*, const cuuint64_t*,
                             const cuuint32_t*, const cuuint32_t*, CUtensorMapInterleave, CUtensorMapSwizzle,
                             CUtensorMapL2promotion, CUtensorMapFloatOOBfill);

extern "C" void kernel_launch(void* const* d_in, const int* in_sizes, int n_in, void* d_out, int out_size) {
    (void)in_sizes; (void)n_in; (void)out_size;
    static int nsm = 0, ncl = 0;
    static EncodeFn encode = nullptr;
    static const char* epoch_ptr = nullptr;
    cudaLaunchConfig_t cfg = {};
    cudaLaunchAttribute at[1];
    at[0].id = cudaLaunchAttributeClusterDimension;
    at[0].val.clusterDim.x = 8; at[0].val.clusterDim.y = 1; at[0].val.clusterDim.z = 1;
    cfg.blockDim = dim3(256); cfg.dynamicSmemBytes = SMEM_BYTES; cfg.stream = cudaStreamPerThread; cfg.attrs = at; cfg.numAttrs = 1;
    if (nsm == 0) {
        int dev = 0;
        cudaGetDevice(&dev);
        cudaDeviceGetAttribute(&nsm, cudaDevAttrMultiProcessorCount, dev);
        cudaFuncSetAttribute(fused_decode_kernel<false>, cudaFuncAttributeMaxDynamicSharedMemorySize, SMEM_BYTES);
        cudaFuncSetAttribute(fused_decode_kernel<true>, cudaFuncAttributeMaxDynamicSharedMemorySize, SMEM_BYTES);
        cfg.gridDim = dim3(128);
        if (cudaOccupancyMaxActiveClusters(&ncl, fused_decode_kernel<true>, &cfg) != cudaSuccess) { ncl = 0; (void)cudaGetLastError(); }
        if (ncl > MINCL) ncl = MINCL;
        cudaGetSymbolAddress((void**)&epoch_ptr, g_epoch);
        void* fn = nullptr;
        cudaDriverEntryPointQueryResult qr;
        cudaGetDriverEntryPoint("cuTensorMapEncodeTiled", &fn, cudaEnableDefault, &qr);
        encode = (EncodeFn)fn;
    }
    Params p;
    auto panels = [&](CUtensorMap* tm, void* ptr, int rows, int cols, int box_rows, int box_panels) {
        const cuuint64_t gd[3] = {64, (cuuint64_t)rows, (cuuint64_t)(cols / 64)}, gs[2] = {(cuuint64_t)cols * 2, 128};
        const cuuint32_t box[3] = {64, (cuuint32_t)box_rows, (cuuint32_t)box_panels}, es[3] = {1, 1, 1};
        encode(tm, CU_TENSOR_MAP_DATA_TYPE_BFLOAT16, 3, ptr, gd, gs, box, es, CU_TENSOR_MAP_INTERLEAVE_NONE,
               CU_TENSOR_MAP_SWIZZLE_128B, CU_TENSOR_MAP_L2_PROMOTION_L2_256B, CU_TENSOR_MAP_FLOAT_OOB_FILL_NONE);
    };
    panels(&p.tm_wq, d_in[7], DM, 4096, 128, 2);
    panels(&p.tm_wuk, d_in[8], 512, 4096, 128, 2);
    panels(&p.tm_wuv, d_in[9], 512, 4096, 128, 2);
    panels(&p.tm_wo, d_in[10], 4096, DM, 32, 9);
    panels(&p.tm_ckv, d_in[6], 4 * SK, 512, 32, 8);
    {
        const cuuint64_t gd[3] = {4096, 192, 3}, gs[2] = {8192, 192 * 8192};
        const cuuint32_t box[3] = {32, 192, 3}, es[3] = {1, 1, 1};
        encode(&p.tm_j0, CU_TENSOR_MAP_DATA_TYPE_BFLOAT16, 3, d_in[3], gd, gs, box, es, CU_TENSOR_MAP_INTERLEAVE_NONE,
               CU_TENSOR_MAP_SWIZZLE_64B, CU_TENSOR_MAP_L2_PROMOTION_L2_128B, CU_TENSOR_MAP_FLOAT_OOB_FILL_NONE);
    }
    for (int i = 0; i < 6; i++) {
        const int k = i >> 1, a = i & 1;
        const cuuint64_t gd[4] = {DM, 16, 8, NH}, gs[3] = {(cuuint64_t)(a ? 8 : 1) * DM * 2, (cuuint64_t)(a ? 1 : 16) * DM * 2, 128 * DM * 2};
        const cuuint32_t box[4] = {k < 2 ? 64u : 16u, 16, k ? 8u : 4u, k < 2 ? 1u : 2u}, es[4] = {1, 1, 1, 1};
        encode(&p.tm_out[k][a], CU_TENSOR_MAP_DATA_TYPE_BFLOAT16, 4, d_in[a ? 4 : 10], gd, gs, box, es, CU_TENSOR_MAP_INTERLEAVE_NONE,
               k < 2 ? CU_TENSOR_MAP_SWIZZLE_128B : CU_TENSOR_MAP_SWIZZLE_32B,
               k < 2 ? CU_TENSOR_MAP_L2_PROMOTION_L2_256B : CU_TENSOR_MAP_L2_PROMOTION_L2_128B, CU_TENSOR_MAP_FLOAT_OOB_FILL_NONE);
    }
    p.kc = (const __nv_bfloat16*)d_in[1];
    p.vc = (const __nv_bfloat16*)d_in[2];
    p.wo = (const __nv_bfloat16*)d_in[4];
    p.xb = (const __nv_bfloat16*)d_in[5];
    p.out = (__nv_bfloat16*)d_out;
    const First f = {{(const char*)d_in[3], (const char*)d_in[1], (const char*)d_in[0], epoch_ptr}};
    if (ncl >= MINCL) {
        cfg.gridDim = dim3(8 * ncl);
        cudaLaunchKernelEx(&cfg, fused_decode_kernel<true>, f, p);
    } else {
        fused_decode_kernel<false><<<nsm, 256, SMEM_BYTES, cudaStreamPerThread>>>(f, p);
    }
}
```

```cpp
#include <cuda_runtime.h>
#include <cuda.h>
#include <cuda_bf16.h>
#include <stdint.h>

namespace {

constexpr int NH = 32, SK = 4096, DM = 576;
constexpr int KEYS = 128;
constexpr int UPP = SK / KEYS;
constexpr int NUK = 4 * NH * UPP;
constexpr int TILE_BYTES = KEYS * 256;
#define NWORK 2
constexpr int NW = NWORK;
constexpr int NBCTA = 32;
constexpr int MINCL = 15;
constexpr int NFIN = 72;
constexpr int SLOT = 32768;
constexpr int NSLOT = 6;
constexpr int BRING = 5;
constexpr int J0W = 5 * SLOT;
constexpr int MISC = NSLOT * SLOT + 4096;
constexpr int XP = 1168, CP = 1040, QP = 272;
constexpr int M_XA = MISC;
constexpr int M_XB = M_XA + 4 * XP;
constexpr int M_CH = M_XB + 4 * XP;
constexpr int M_CL = M_CH + 4 * CP;
constexpr int M_QB = M_CL + 4 * CP;
constexpr int M_QA = M_CH;
constexpr int M_J0 = M_QB + 4 * QP;
constexpr int M_P = M_J0 + 2048;
constexpr int M_ALPHA = M_P + 2560;
constexpr int M_OMEGA = M_ALPHA + 128;
constexpr int M_BAR = M_OMEGA + 128;
constexpr int M_HELP = M_BAR + 128;
constexpr int F_W = 3 * SLOT;
constexpr int F_X = NSLOT * SLOT, FXP = 1088;
constexpr int F_RECV = F_X + 12 * FXP;
constexpr int F_BAR = M_P;
constexpr int SMEM_BYTES = M_HELP + 128 + 1024;
static_assert(F_RECV + 2048 <= M_J0, "output phase layout");
static_assert(SMEM_BYTES <= 232448 && M_BAR % 8 == 0 && M_QA % 16 == 0 && M_P % 16 == 0, "smem layout");
#define XW 2
#define X3 2
#define X3C 3
#define NEARLY 2
#define BD 5
#define FPF 3
#define FSLEEP 800
#define FJ 250
#define FP 376
#define FN 32
#define NPOLL 2
#define PGAP 200
static_assert(NW + XW == 4 && 4 % NEARLY == 0 && BD <= BRING, "slots 4 and 5 hold the finisher weights");
constexpr float SCALE = 0.08838834764831845f;
constexpr float LOG2E = 1.4426950408889634f;
constexpr unsigned SPIN_LIMIT = 1u << 24;

#define NREP 2
constexpr int C_QUEUE = 0, C_KDONE = 1, C_BBAR = 3, C_LINES = 5;

struct First { const char* ptr[4]; };
struct Params {
    const __nv_bfloat16 *kc, *vc, *wo, *xb;
    __nv_bfloat16* out;
    CUtensorMap tm_j0;
    CUtensorMap tm_wq, tm_wuk, tm_ckv, tm_wuv, tm_wo;
    CUtensorMap tm_out[3][2];
};

__device__ unsigned g_epoch;
__device__ unsigned g_ctl[2][C_LINES][32];
__device__ uint2 g_qll[4 * 2048];
__device__ uint2 g_scores[128 * SK / 4];
__device__ float2 g_stats[128 * UPP];
__device__ float4 g_oacc[128 * 32];
__device__ unsigned g_vdone[NREP * NH][32];
__device__ uint4 g_qabs[4 * 8 * 4 * 4 * 32];
__device__ float2 g_bpart[NBCTA * NH * 256];
__device__ float2 g_bml[NBCTA * NH];
__device__ uint4 g_ctx[NH * 128];
__device__ uint4 g_outb[NBCTA * NH * 36];

__device__ __forceinline__ int cluster_role(int b) {
    const int i = b - NFIN, q = ((i >> 1) * 43 >> 7) * 2, r = i - 3 * q;
    int x = i - q;
    asm("{\n.reg .pred p;\nsetp.ge.s32 p, %1, 4;\nselp.s32 %0, %2, %0, p;\nsetp.lt.s32 p, %3, 0;\nselp.s32 %0, %4, %0, p;\n}"
        : "+r"(x) : "r"(r), "r"(NBCTA + NFIN - 4 + q + r), "r"(i), "r"(b + NBCTA));
    return x;
}

#define TS(i)
#define TSV(i, v)
#define LAND(i)
#define CLK(x)
#define ACC(a, x, y)

__device__ __forceinline__ uint32_t smem_u32(const void* p) { return (uint32_t)__cvta_generic_to_shared(p); }
__device__ __forceinline__ void mbar_init(uint32_t bar, uint32_t cnt) {
    asm volatile("mbarrier.init.shared::cta.b64 [%0], %1;" ::"r"(bar), "r"(cnt) : "memory");
}
__device__ __forceinline__ void mbar_expect_tx(uint32_t bar, uint32_t bytes) {
    asm volatile("mbarrier.arrive.expect_tx.shared::cta.b64 _, [%0], %1;" ::"r"(bar), "r"(bytes) : "memory");
}
__device__ __forceinline__ bool mbar_try(uint32_t bar, uint32_t parity) {
    uint32_t ok;
    asm volatile("{\n.reg .pred p;\nmbarrier.try_wait.parity.shared::cta.b64 p, [%1], %2;\nselp.u32 %0, 1, 0, p;\n}\n"
                 : "=r"(ok) : "r"(bar), "r"(parity) : "memory");
    return ok;
}
__device__ __forceinline__ void mbar_wait(uint32_t bar, uint32_t parity) {
    unsigned n = 0;
    while (!mbar_try(bar, parity)) { if (++n > SPIN_LIMIT) __trap(); }
}
__device__ __forceinline__ void bulk_load(uint32_t dst, const void* src, uint32_t bytes, uint32_t bar, uint64_t pol) {
    asm volatile("cp.async.bulk.shared::cluster.global.mbarrier::complete_tx::bytes.L2::cache_hint [%0], [%1], %2, [%3], %4;"
                 ::"r"(dst), "l"(src), "r"(bytes), "r"(bar), "l"(pol) : "memory");
}
__device__ __forceinline__ void tma3d(uint32_t dst, const CUtensorMap* tm, int c0, int c1, int c2, uint32_t bar, uint64_t pol) {
    asm volatile("cp.async.bulk.tensor.3d.shared::cluster.global.mbarrier::complete_tx::bytes.L2::cache_hint [%0], [%1, {%3,%4,%5}], [%2], %6;"
                 ::"r"(dst), "l"(tm), "r"(bar), "r"(c0), "r"(c1), "r"(c2), "l"(pol) : "memory");
}
__device__ __forceinline__ void tma4d(uint32_t dst, const CUtensorMap* tm, int c0, int c2, int c3, uint32_t bar, uint64_t pol) {
    asm volatile("cp.async.bulk.tensor.4d.shared::cluster.global.mbarrier::complete_tx::bytes.L2::cache_hint [%0], [%1, {%3,0,%4,%5}], [%2], %6;"
                 ::"r"(dst), "l"(tm), "r"(bar), "r"(c0), "r"(c2), "r"(c3), "l"(pol) : "memory");
}
__device__ __forceinline__ void l2_prefetch(const void* src, uint32_t bytes) {
    asm volatile("cp.async.bulk.prefetch.L2.global [%0], %1;" ::"l"(src), "r"(bytes) : "memory");
}
__device__ __forceinline__ void ldsm4(uint32_t (&r)[4], uint32_t addr) {
    asm volatile("ldmatrix.sync.aligned.m8n8.x4.shared.b16 {%0,%1,%2,%3}, [%4];"
                 : "=r"(r[0]), "=r"(r[1]), "=r"(r[2]), "=r"(r[3]) : "r"(addr));
}
__device__ __forceinline__ void ldsm4t(uint32_t (&r)[4], uint32_t addr) {
    asm volatile("ldmatrix.sync.aligned.m8n8.x4.trans.shared.b16 {%0,%1,%2,%3}, [%4];"
                 : "=r"(r[0]), "=r"(r[1]), "=r"(r[2]), "=r"(r[3]) : "r"(addr));
}
__device__ __forceinline__ void mma16816(float (&d)[4], const uint32_t (&a)[4], uint32_t b0, uint32_t b1) {
    asm("mma.sync.aligned.m16n8k16.row.col.f32.bf16.bf16.f32 {%0,%1,%2,%3}, {%4,%5,%6,%7}, {%8,%9}, {%0,%1,%2,%3};"
        : "+f"(d[0]), "+f"(d[1]), "+f"(d[2]), "+f"(d[3])
        : "r"(a[0]), "r"(a[1]), "r"(a[2]), "r"(a[3]), "r"(b0), "r"(b1));
}
__device__ __forceinline__ void wgmma_k64(float (&d)[4], uint32_t da, uint32_t db, int accumulate) {
    asm volatile("{\n.reg .pred p;\n.reg .b32 x, y;\n.reg .b64 a, b;\nsetp.ne.u32 p, %6, 0;\n"
                 "add.u32 x, %4, 0;\nadd.u32 y, %5, 0;\nmov.b64 a, {x, 0x40000040};\nmov.b64 b, {y, 1};\n"
                 "wgmma.mma_async.sync.aligned.m64n8k16.f32.bf16.bf16 {%0,%1,%2,%3}, a, b, p, 1, 1, 1, 0;\n"
                 "add.u32 x, %4, 128;\nadd.u32 y, %5, 8;\nmov.b64 a, {x, 0x40000040};\nmov.b64 b, {y, 1};\n"
                 "wgmma.mma_async.sync.aligned.m64n8k16.f32.bf16.bf16 {%0,%1,%2,%3}, a, b, 1, 1, 1, 1, 0;\n"
                 "add.u32 x, %4, 256;\nadd.u32 y, %5, 16;\nmov.b64 a, {x, 0x40000040};\nmov.b64 b, {y, 1};\n"
                 "wgmma.mma_async.sync.aligned.m64n8k16.f32.bf16.bf16 {%0,%1,%2,%3}, a, b, 1, 1, 1, 1, 0;\n"
                 "add.u32 x, %4, 384;\nadd.u32 y, %5, 24;\nmov.b64 a, {x, 0x40000040};\nmov.b64 b, {y, 1};\n"
                 "wgmma.mma_async.sync.aligned.m64n8k16.f32.bf16.bf16 {%0,%1,%2,%3}, a, b, 1, 1, 1, 1, 0;\n"
                 "}" : "+f"(d[0]), "+f"(d[1]), "+f"(d[2]), "+f"(d[3]) : "r"(da), "r"(db), "r"(accumulate) : "memory");
}
__device__ __forceinline__ uint32_t lds32(uint32_t a) {
    uint32_t v;
    asm volatile("ld.shared.u32 %0, [%1];" : "=r"(v) : "r"(a));
    return v;
}
__device__ __forceinline__ unsigned ld_acquire(const unsigned* p) {
    unsigned v;
    asm volatile("ld.acquire.gpu.global.u32 %0, [%1];" : "=r"(v) : "l"(p) : "memory");
    return v;
}
__device__ __forceinline__ uint2 ld_relaxed8(const void* p) {
    uint2 v;
    asm volatile("ld.relaxed.gpu.global.v2.u32 {%0,%1}, [%2];" : "=r"(v.x), "=r"(v.y) : "l"(p) : "memory");
    return v;
}
__device__ __forceinline__ unsigned ld_relaxed4(const void* p) {
    unsigned v;
    asm volatile("ld.relaxed.gpu.global.u32 %0, [%1];" : "=r"(v) : "l"(p) : "memory");
    return v;
}
__device__ __forceinline__ unsigned atom_inc(unsigned* p) {
    unsigned v;
    asm volatile("atom.relaxed.gpu.global.inc.u32 %0, [%1], 0x7fffffff;" : "=r"(v) : "l"(p) : "memory");
    return v;
}
__device__ __forceinline__ unsigned long long ld_relaxed64(const void* p) {
    unsigned long long v;
    asm volatile("ld.relaxed.gpu.global.u64 %0, [%1];" : "=l"(v) : "l"(p) : "memory");
    return v;
}
__device__ __forceinline__ void st_relaxed64(void* p, unsigned long long v) {
    asm volatile("st.relaxed.gpu.global.u64 [%0], %1;" ::"l"(p), "l"(v) : "memory");
}
__device__ __forceinline__ float4 ld_relaxed16(const void* p) {
    float4 v;
    asm volatile("ld.relaxed.gpu.global.v4.f32 {%0,%1,%2,%3}, [%4];" : "=f"(v.x), "=f"(v.y), "=f"(v.z), "=f"(v.w) : "l"(p) : "memory");
    return v;
}
__device__ __forceinline__ uint32_t mapa(uint32_t a, uint32_t rank) {
    uint32_t r;
    asm("mapa.shared::cluster.u32 %0, %1, %2;" : "=r"(r) : "r"(a), "r"(rank));
    return r;
}
__device__ __forceinline__ void mbar_first(uint32_t bar) {
    asm volatile("{\n.reg .pred p, q;\n.reg .u32 n;\nmov.u32 n, 0;\n"
                 "SPIN:\nmbarrier.try_wait.parity.shared::cta.b64 p, [%0], 0;\nadd.u32 n, n, 1;\nsetp.gt.u32 q, n, 0x1000000;\n@q trap;\n"
                 "@!p bra.uni SPIN;\n}" ::"r"(bar) : "memory");
}
__device__ __forceinline__ void mbar_first_cluster(uint32_t bar) {
    asm volatile("{\n.reg .pred p, q;\n.reg .u32 n;\nmov.u32 n, 0;\n"
                 "SPIN:\nmbarrier.try_wait.parity.relaxed.cluster.shared::cta.b64 p, [%0], 0;\nadd.u32 n, n, 1;\nsetp.gt.u32 q, n, 0x1000000;\n@q trap;\n"
                 "@!p bra.uni SPIN;\nfence.acquire.sync_restrict::shared::cluster.cluster;\n}" ::"r"(bar) : "memory");
}
__device__ __forceinline__ uint32_t now_ns() {
    unsigned long long t;
    asm volatile("mov.u64 %0, %globaltimer;" : "=l"(t));
    return (uint32_t)t;
}
__device__ __forceinline__ void fence_gpu() { asm volatile("fence.acq_rel.gpu;" ::: "memory"); }
__device__ __forceinline__ void red_add_u32(unsigned* p, unsigned v) {
    asm volatile("red.relaxed.gpu.global.add.u32 [%0], %1;" ::"l"(p), "r"(v) : "memory");
}
__device__ __forceinline__ void st_tagged2(void* p, float a, float b, unsigned tag) {
    const unsigned long long hi = (unsigned long long)tag << 32;
    asm volatile("st.relaxed.gpu.global.v2.b64 [%0], {%1,%2};" ::"l"(p), "l"(hi | __float_as_uint(a)), "l"(hi | __float_as_uint(b)) : "memory");
}
__device__ __forceinline__ ulonglong2 ld_tagged2(const void* p) {
    ulonglong2 v;
    asm volatile("ld.relaxed.gpu.global.v2.b64 {%0,%1}, [%2];" : "=l"(v.x), "=l"(v.y) : "l"(p) : "memory");
    return v;
}
__device__ __forceinline__ float4 atom_add_f4(void* p, float a, float b, float c, float d) {
    float4 r;
    asm volatile("atom.relaxed.gpu.global.add.v4.f32 {%0,%1,%2,%3}, [%4], {%5,%6,%7,%8};"
                 : "=f"(r.x), "=f"(r.y), "=f"(r.z), "=f"(r.w) : "l"(p), "f"(a), "f"(b), "f"(c), "f"(d) : "memory");
    return r;
}
__device__ __forceinline__ void red_release_cta_shared(uint32_t a, unsigned v) {
    asm volatile("red.release.cta.shared::cta.add.u32 [%0], %1;" ::"r"(a), "r"(v) : "memory");
}
__device__ __forceinline__ unsigned ld_acquire_cta_shared(uint32_t a) {
    unsigned v;
    asm volatile("ld.acquire.cta.shared::cta.u32 %0, [%1];" : "=r"(v) : "r"(a) : "memory");
    return v;
}
__device__ __forceinline__ void st_release_cta_shared(uint32_t a, unsigned v) {
    asm volatile("st.release.cta.shared::cta.u32 [%0], %1;" ::"r"(a), "r"(v) : "memory");
}
__device__ __forceinline__ void wait_count(const unsigned* p, unsigned target) {
    unsigned n = 0;
    while (ld_acquire(p) < target) { if (++n > SPIN_LIMIT) __trap(); }
}
__device__ __forceinline__ uint32_t pack_bf16(float lo, float hi) {
    uint32_t r;
    asm("cvt.rn.bf16x2.f32 %0, %1, %2;" : "=r"(r) : "f"(hi), "f"(lo));
    return r;
}
__device__ __forceinline__ float bf_lo(uint32_t v) { return __uint_as_float(v << 16); }
__device__ __forceinline__ float bf_hi(uint32_t v) { return __uint_as_float(v & 0xffff0000u); }
__device__ __forceinline__ float ex2(float x) { float y; asm("ex2.approx.ftz.f32 %0, %1;" : "=f"(y) : "f"(x)); return y; }
__device__ __forceinline__ float expsub(float a, float b) { return ex2((a - b) * LOG2E); }
__device__ __forceinline__ float warp_max(float v) {
#pragma unroll
    for (int m = 16; m; m >>= 1) v = fmaxf(v, __shfl_xor_sync(~0u, v, m));
    return v;
}
__device__ __forceinline__ float warp_sum(float v) {
#pragma unroll
    for (int m = 16; m; m >>= 1) v += __shfl_xor_sync(~0u, v, m);
    return v;
}
__device__ __forceinline__ unsigned unit_block(int u) {
    const unsigned v = u & (NUK - 1);
    return u < NUK ? (v & ~0x78u) | (v & 0x18u) << 2 | (v & 0x60u) >> 2 : v;
}
__device__ __forceinline__ const char* block_src(const void* base, unsigned blk) {
    const unsigned po = blk / UPP;
    return reinterpret_cast<const char*>(base) + (size_t)(((po & 3) * NH + (po >> 2)) * UPP + blk % UPP) * TILE_BYTES;
}

template <bool CLU>
__device__ __forceinline__ void a_worker(const Params& p, int un, bool once, bool hold, int nstatic, uint32_t slot, uint32_t bar, uint32_t wb,
                                         uint32_t help, unsigned epoch, uint64_t pol) {
    constexpr int NU = 2 * NUK;
    const int lane = threadIdx.x & 31, g = lane >> 2, t = lane & 3;
    const int li = lane & 7;
    uint32_t kaddr[4], vaddr[8];
    {
        const int e = (lane >> 3) & 1, kk = lane >> 4;
#pragma unroll
        for (int s = 0; s < 4; s++) kaddr[s] = slot + (16 * li + e) * 256 + ((2 * s + kk + li) & 7) * 16;
        const int vrow = 4 * (li >> 1) + (li & 1) + 2 * kk;
#pragma unroll
        for (int c = 0; c < 8; c++) vaddr[c] = slot + vrow * 256 + e * 128 + ((c + li) & 7) * 16;
#pragma unroll
        for (int c = 0; c < 8; c++) asm volatile("" : "+r"(vaddr[c]));
    }
    const uint32_t vmask = (g >> 1) != t ? 0u : ((g & 1) ? 0xffff0000u : 0xffffu);
    int kseen = -1;
    unsigned long long H0 = 0, H1 = 0;
    auto header = [&](int v, unsigned vb) {
        if (v >= NU) return;
        const void *a0, *a1;
        if (v < NUK) {
            const unsigned po = vb / UPP;
            a0 = g_qll + (po & 3) * 2048 + (po >> 2) * 64 + lane;
            a1 = reinterpret_cast<const uint2*>(a0) + 32;
        } else {
            const int half = vb / (NUK / 2);
            if (half > kseen) {
                unsigned n = 0;
                while (ld_acquire_cta_shared(help + 12 + 4 * half) == 0) { if (++n > (SPIN_LIMIT << 4)) __trap(); }
                kseen = half;
            }
            a0 = &g_scores[vb * (KEYS / 4) + lane];
            a1 = &g_stats[(vb / UPP) * UPP + lane];
        }
        H0 = ld_relaxed64(a0);
        H1 = ld_relaxed64(a1);
    };
    epoch = __shfl_sync(~0u, epoch, 0);
    if (hold) { unsigned n = 0; while (ld_acquire_cta_shared(help + 24) < 2) { if (++n > (SPIN_LIMIT << 4)) __trap(); } }
    unsigned (*ctl)[32] = g_ctl[epoch & 1];
    const unsigned tag = epoch + 1;
    unsigned nxt = once ? NU : 0;
    int u = -1;
    unsigned bu = 0, bn = unit_block(un);
    bool have = false;
    uint32_t phase = 0;
    unsigned kpend = 0;
    const unsigned zero = gridDim.x >> 24;
    uint32_t Q[16];
    float4 oret = make_float4(0.f, 0.f, 0.f, 0.f);
    while (true) {
        const char* nsrc = block_src(un < NUK ? p.kc : p.vc, bn);
        float4* odst = &g_oacc[(bu / UPP) * 32 + lane];
        unsigned* vdst = &g_vdone[(lane & (NREP - 1)) * NH + bu / (4 * UPP)][0];
        float d[8][4];
        CLK(c1);
        asm volatile("" : "+l"(odst));
        if (u >= NUK) {
#pragma unroll
            for (int j = 0; j < 8; j++) { d[j][0] = d[j][1] = d[j][2] = d[j][3] = 0.f; }
            mbar_wait(wb, phase);
            LAND(NUK + bu);
            uint32_t a[2][8][4];
#pragma unroll
            for (int c = 0; c < 8; c++) ldsm4t(a[0][c], vaddr[c]);
#pragma unroll
            for (int j = 0; j < 8; j++) {
                if (j < 7) {
#pragma unroll
                    for (int c = 0; c < 8; c++) ldsm4t(a[(j + 1) & 1][c], vaddr[c] + (j + 1) * 4096);
                }
#pragma unroll
                for (int c = 0; c < 8; c++) mma16816(d[c], a[j & 1][c], Q[2 * j], Q[2 * j + 1]);
            }
            float o[4];
#pragma unroll
            for (int r = 0; r < 2; r++) {
                o[2 * r] = d[0][2 * r] + d[7][2 * r + 1];
                o[2 * r + 1] = d[0][2 * r + 1] + d[1][2 * r];
#pragma unroll
                for (int k = 1; k < 4; k++) {
                    const int src = (lane & 28) | ((t - k) & 3);
                    o[2 * r] += __shfl_sync(~0u, d[2 * k][2 * r] + d[2 * k - 1][2 * r + 1], src);
                    o[2 * r + 1] += __shfl_sync(~0u, d[2 * k][2 * r + 1] + d[2 * k + 1][2 * r], src);
                }
            }
            oret = atom_add_f4(odst, o[0], o[1], o[2], o[3]);
        } else if (u >= 0) {
#pragma unroll
            for (int j = 0; j < 8; j++) { d[j][0] = d[j][1] = d[j][2] = d[j][3] = 0.f; }
            mbar_wait(wb, phase);
            LAND(bu);
            uint32_t a[2][8][4];
#pragma unroll
            for (int j = 0; j < 8; j++) ldsm4(a[0][j], kaddr[0] + (4 * (j & 3) + 2 * (j >> 2)) * 256);
#pragma unroll
            for (int s = 0; s < 8; s++) {
                if (s < 7) {
#pragma unroll
                    for (int j = 0; j < 8; j++)
                        ldsm4(a[(s + 1) & 1][j], kaddr[(s + 1) & 3] + (4 * (j & 3) + 2 * (j >> 2)) * 256 + ((s + 1) >> 2) * 128);
                }
#pragma unroll
                for (int j = 0; j < 8; j++)
                    mma16816(d[j], a[s & 1][j], Q[(s & 4) * 2 + ((2 * s - 2 * j) & 7)], Q[(s & 4) * 2 + ((2 * s + 1 - 2 * j) & 7)]);
            }
        }
        const bool pre = wb != bar;
        if (u >= 0) { phase = pre ? 0 : phase ^ 1; wb = bar; }
        CLK(c2b);
        if (un < NU && lane == 0) {
            if (!once) nxt = atom_inc(&ctl[C_QUEUE][0]);
            if (u >= 0 || !pre) {
                mbar_expect_tx(bar, TILE_BYTES);
                bulk_load(slot, nsrc, TILE_BYTES, bar, pol);
            }
        }
        const uint32_t tiss = now_ns();
        CLK(c3);
        if ((unsigned)u < (unsigned)NUK) {
            const int j0 = (t - (g >> 1)) & 3;
            float v[4];
#pragma unroll
            for (int q = 0; q < 4; q++) {
                const int jq = (q >> 1) * 4, e = (q & 1) * 2;
                const float x0 = (g & 1) ? d[jq + 0][e + 1] : d[jq + 0][e];
                const float x1 = (g & 1) ? d[jq + 1][e + 1] : d[jq + 1][e];
                const float x2 = (g & 1) ? d[jq + 2][e + 1] : d[jq + 2][e];
                const float x3 = (g & 1) ? d[jq + 3][e + 1] : d[jq + 3][e];
                const float y0 = (j0 & 1) ? x1 : x0, y1 = (j0 & 1) ? x3 : x2;
                v[q] = (j0 & 2) ? y1 : y0;
            }
            const uint32_t r0 = pack_bf16(v[0], v[1]), r1 = pack_bf16(v[2], v[3]);
            const uint32_t s0 = pack_bf16(bf_lo(r0) * SCALE, bf_hi(r0) * SCALE);
            const uint32_t s1 = pack_bf16(bf_lo(r1) * SCALE, bf_hi(r1) * SCALE);
            g_scores[bu * (KEYS / 4) + 4 * g + j0] = make_uint2(s0, s1);
            const float f0 = bf_lo(s0), f1 = bf_hi(s0), f2 = bf_lo(s1), f3 = bf_hi(s1);
            const float m = warp_max(fmaxf(fmaxf(f0, f1), fmaxf(f2, f3)));
            const float l = warp_sum((expsub(f0, m) + expsub(f1, m)) + (expsub(f2, m) + expsub(f3, m)));
            if (lane == 0) g_stats[bu] = make_float2(m, l);
            kpend++;
            if (un / (NUK / 2) != u / (NUK / 2)) {
                __syncwarp();
                if (lane == 0) {
                    red_release_cta_shared(help + 4 * (u / (NUK / 2)), kpend);
                    if (un >= NUK) red_release_cta_shared(help + 8, 1u);
                }
                kpend = 0;
            }
        }
        CLK(c4);
        int unn = NU;
        if (un < NU) {
            unsigned n = 0;
            while (true) {
                if (!have) header(un, bn);
                if (un >= NUK || __all_sync(~0u, (uint32_t)(H0 >> 32) == tag && (uint32_t)(H1 >> 32) == tag)) break;
                if (++n > SPIN_LIMIT) __trap();
                have = false;
            }
            if (un >= NUK) {
                const uint32_t s0 = (uint32_t)H0, s1 = (uint32_t)(H0 >> 32);
                const float mu = __uint_as_float((uint32_t)H1);
                const float m = warp_max(mu);
                const float l = warp_sum(__uint_as_float((uint32_t)(H1 >> 32)) * expsub(mu, m));
                const float inv = 1.0f / l;
                const uint32_t w0 = pack_bf16(expsub(bf_lo(s0), m) * inv, expsub(bf_hi(s0), m) * inv);
                const uint32_t w1 = pack_bf16(expsub(bf_lo(s1), m) * inv, expsub(bf_hi(s1), m) * inv);
#pragma unroll
                for (int j = 0; j < 8; j++) {
                    Q[2 * j] = __shfl_sync(~0u, w0, 4 * j + t) & vmask;
                    Q[2 * j + 1] = __shfl_sync(~0u, w1, 4 * j + t) & vmask;
                }
            } else {
#pragma unroll
                for (int j = 0; j < 8; j++) {
                    const int src = (((j + g) & 7) << 2) + t;
                    Q[j] = __shfl_sync(~0u, (uint32_t)H0, src);
                    Q[8 + j] = __shfl_sync(~0u, (uint32_t)H1, src);
                }
            }
            if (u < 0) TS(2);
            unn = nstatic + (int)__shfl_sync(~0u, nxt, 0);
            if (CLU && !once && unn >= NU && lane == 0)
                asm volatile("st.relaxed.cta.shared::cta.u32 [%0], %1;" ::"r"(help + 28), "r"((tiss + (FJ - (unn - NU)) * 10) | 1u) : "memory");
        }
        if (u >= NUK && lane < (CLU ? 1 : NREP))
            red_add_u32(vdst,
                        1u + ((__float_as_uint(oret.x) | __float_as_uint(oret.y) | __float_as_uint(oret.z) | __float_as_uint(oret.w)) & zero));
        if (un >= NU) break;
        bu = bn;
        have = !(un < NUK && unn >= NUK && !(un >= NUK / 2 && unn < NUK + NUK / 2));
        bn = unit_block(unn);
        if (have) header(unn, bn);
        u = un;
        un = unn;
    }
    TS(4);
}

__device__ __forceinline__ void k_helper(uint32_t help, unsigned epoch, unsigned nwork) {
    if ((threadIdx.x & 31) != 0) return;
    unsigned (*ctl)[32] = g_ctl[epoch & 1];
    unsigned sent0 = 0, sent1 = 0, n = 0;
    int seen = 0;
    bool fin = false;
    while (!fin || seen < 2) {
        if (!fin) {
            fin = ld_acquire_cta_shared(help + 8) == nwork;
            const unsigned c0 = ld_acquire_cta_shared(help), c1 = ld_acquire_cta_shared(help + 4);
            if (c0 != sent0 || c1 != sent1) {
                fence_gpu();
                if (c0 != sent0) red_add_u32(&ctl[C_KDONE][0], c0 - sent0);
                if (c1 != sent1) red_add_u32(&ctl[C_KDONE + 1][0], c1 - sent1);
                sent0 = c0; sent1 = c1;
            }
        }
        if (seen < 2 && ld_acquire(&ctl[C_KDONE + seen][0]) >= NUK / 2) {
            st_release_cta_shared(help + 12 + 4 * seen, 1u);
            seen++;
        } else {
            __nanosleep(300);
        }
        if (++n > SPIN_LIMIT) __trap();
    }
}

__device__ __forceinline__ void v_poller(uint32_t sbase, int f, int w) {
    const int lane = threadIdx.x & 31;
    const unsigned (*cp)[32] = &g_vdone[((f * NPOLL + w) % NREP) * NH];
    unsigned n = 0;
    while (ld_acquire_cta_shared(sbase + M_HELP + 12) == 0) { __nanosleep(1000); if (++n > SPIN_LIMIT) __trap(); }
    int h = 0;
    bool fast = false;
    while (h < NH) {
        const unsigned r = __ballot_sync(~0u, ld_acquire(&cp[min(h + (lane & 3), NH - 1)][0]) >= 4 * UPP) & 15u;
        if (r & 1) {
            h = min(NH, h + __ffs(~r) - 1);
            __syncwarp();
            if (lane == 0) asm volatile("red.release.cta.shared::cta.max.u32 [%0], %1;" ::"r"(sbase + M_HELP + 20), "r"(h) : "memory");
        }
        if (h < NH - 4) {
            __nanosleep(h ? 300 : 1000);
        } else if (!fast) {
            fast = true;
            const long long t0 = clock64();
            while (clock64() - t0 < w * PGAP) {}
        }
        if (++n > SPIN_LIMIT) __trap();
    }
}
__device__ __forceinline__ void finisher(const Params& p, uint32_t sbase, int f) {
    const int lane = threadIdx.x & 31;
    {
        const char* wg = reinterpret_cast<const char*>(p.wo);
        const uint32_t dst = sbase + 4 * SLOT + (16 * (lane & 7) + (lane >> 3)) * 16;
#pragma unroll 1
        for (int h = -FPF - 4; h < NH; h++) {
            if (lane == 0 && (unsigned)(h + FPF) < (unsigned)NH) l2_prefetch(wg + (size_t)(h + FPF) * 147456 + f * 2048, 2048);
            if (h >= 0) {
#pragma unroll
                for (int r = 0; r < 4; r++)
                    asm volatile("cp.async.cg.shared.global [%0], [%1], 16;" ::"r"(dst + h * 2048 + ((r & 1) * 4 + (r >> 1) * 8) * 16),
                                 "l"(wg + (size_t)(h * 128 + r * 32 + lane) * (DM * 2) + f * 16) : "memory");
            }
            __nanosleep(FSLEEP);
        }
        asm volatile("cp.async.wait_all;" ::: "memory");
        __syncwarp();
    }
    TS(11);
    const float4* vec = g_oacc + ((lane >> 2) & 3) * 32 + (lane >> 4) * 16 + (lane & 3);
    float acc[2][2][4];
#pragma unroll
    for (int i = 0; i < 16; i++) acc[i >> 3][(i >> 2) & 1][i & 3] = 0.f;
    uint32_t* outp = reinterpret_cast<uint32_t*>(p.out + (lane >> 2) * (2 * DM) + f * 8 + (lane & 3) * 2);
    uint32_t wa = sbase + 4 * SLOT + lane * 16;
    auto project = [&](const float4 (&x)[4], const uint32_t (&w)[4][4]) {
#pragma unroll
        for (int s = 0; s < 4; s++) {
            const uint32_t a[4] = {pack_bf16(x[s].x, x[s].y), 0u, pack_bf16(x[s].z, x[s].w), 0u};
            mma16816(acc[0][s & 1], a, w[s >> 1][(s & 1) * 2], w[s >> 1][(s & 1) * 2 + 1]);
            mma16816(acc[1][s & 1], a, w[2 + (s >> 1)][(s & 1) * 2], w[2 + (s >> 1)][(s & 1) * 2 + 1]);
        }
    };
    int h = 0;
    unsigned n = 0;
    while (h < NH) {
        uint32_t w[4][4];
#pragma unroll
        for (int q = 0; q < 4; q++) ldsm4t(w[q], wa + q * 512);
        int ready;
        while ((ready = ld_acquire_cta_shared(sbase + M_HELP + 20)) <= h) {
            if (h < NH - 3) __nanosleep(100);
            if (++n > (SPIN_LIMIT << 4)) __trap();
        }
        float4 x[4], y[4];
#pragma unroll
        for (int s = 0; s < 4; s++) x[s] = ld_relaxed16(vec + s * 4);
        const bool two = ready > h + 1;
        if (two) {
#pragma unroll
            for (int s = 0; s < 4; s++) y[s] = ld_relaxed16(vec + 128 + s * 4);
        }
        project(x, w);
        if (two) {
#pragma unroll
            for (int q = 0; q < 4; q++) ldsm4t(w[q], wa + 2048 + q * 512);
            project(y, w);
        }
        const int nr = two ? 2 : 1;
        h += nr;
        vec += nr * 128;
        wa += nr * 2048;
        const float o0 = acc[0][0][0] + acc[0][1][0] + __shfl_down_sync(~0u, acc[1][0][0] + acc[1][1][0], 16);
        const float o1 = acc[0][0][1] + acc[0][1][1] + __shfl_down_sync(~0u, acc[1][0][1] + acc[1][1][1], 16);
        asm volatile("{\n.reg .pred p;\nsetp.ne.u32 p, %2, 0;\n@p st.global.u32 [%0], %1;\n}" ::"l"(outp), "r"(pack_bf16(o0, o1)),
                     "r"((uint32_t)(lane < 16 && h == NH)) : "memory");
    }
}

__device__ __forceinline__ void out_fetch(uint32_t sbase, int j, int h) {
    const int lane = threadIdx.x & 31, g = lane >> 2;
    float4 x[4];
#pragma unroll
    for (int b = 0; b < 4; b++) x[b] = ld_relaxed16(&g_oacc[(h * 4 + ((b + g) & 3)) * 32 + lane]);
#pragma unroll
    for (int b = 0; b < 4; b++) {
        const uint32_t a = sbase + F_X + j * FXP + g * 128 + ((b + g) & 3) * 16 + (lane & 3) * 4;
        asm volatile("st.shared.u32 [%0], %1;\nst.shared.u32 [%0 + 64], %2;" ::"r"(a), "r"(pack_bf16(x[b].x, x[b].y)), "r"(pack_bf16(x[b].z, x[b].w)) : "memory");
    }
    asm volatile("fence.proxy.async.shared::cta;" ::: "memory");
}
__device__ __forceinline__ void out_early(uint32_t sbase, int rank, unsigned tag) {
    const int lane = threadIdx.x & 31;
    if (lane < 10) {
        mbar_init(sbase + F_BAR + 16 + lane * 8, lane >= 8 ? 4 : lane == 6 ? 2 : 1);
        if (lane < 8) mbar_expect_tx(sbase + F_BAR + 16 + lane * 8, 16384);
    }
    asm volatile("fence.mbarrier_init.release.cluster;" ::: "memory");
    unsigned n = 0;
#pragma unroll 1
    for (int k = 7; k < 18; k++) {
        const int j = k < 12 ? k : k - 12;
        const int h = j >= 8 ? j - 8 : j % 7 == 0 ? 4 + (rank >> 1) : ((j - 1) % 3 + 1) * 8 + rank;
        if (j >= 8 ? rank >= 4 : j >= 4) {
            while (ld_acquire(&g_vdone[h][0]) < 4 * UPP) { __nanosleep(500); if (++n > SPIN_LIMIT) __trap(); }
            out_fetch(sbase, j, h);
        } else {
            while (true) {
                ulonglong2 v[4];
                bool ok = true;
#pragma unroll
                for (int i = 0; i < 4; i++) v[i] = ld_tagged2(&g_ctx[h * 128 + i * 32 + lane]);
#pragma unroll
                for (int i = 0; i < 4; i++) {
                    ok = ok && (unsigned)(v[i].x >> 32) == tag && (unsigned)(v[i].y >> 32) == tag;
                    asm volatile("st.shared.v2.u32 [%0], {%1,%2};" ::"r"(sbase + F_X + j * FXP + (i * 32 + lane) * 8), "r"((uint32_t)v[i].x), "r"((uint32_t)v[i].y) : "memory");
                }
                if (__all_sync(~0u, ok)) break;
                __nanosleep(500);
                if (++n > SPIN_LIMIT) __trap();
            }
        }
    }
    __syncwarp();
    if (lane == 0) st_release_cta_shared(sbase + M_HELP + 32, 1u);
}
__device__ __forceinline__ void out_late(uint32_t sbase, int rank) {
    unsigned n = 0;
    while (ld_acquire_cta_shared(sbase + M_HELP + 32) == 0) { if (++n > (SPIN_LIMIT << 4)) __trap(); }
    while (ld_acquire(&g_vdone[24 + rank][0]) < 4 * UPP) { if (++n > SPIN_LIMIT) __trap(); }
    TS(12);
    out_fetch(sbase, 6, 24 + rank);
    __syncwarp();
    if ((threadIdx.x & 31) == 0) asm volatile("mbarrier.arrive.shared::cta.b64 _, [%0];" ::"r"(sbase + F_BAR + 16 + 6 * 8) : "memory");
    TS(13);
}
__device__ __forceinline__ void out_project(uint32_t sbase, int rank, int w) {
    const int lane = threadIdx.x & 31, g = lane >> 2, t = lane & 3;
    unsigned n = 0;
    while (ld_acquire_cta_shared(sbase + M_HELP + 32) == 0) { __nanosleep(500); if (++n > SPIN_LIMIT) __trap(); }
    asm volatile("barrier.cluster.wait.acquire.aligned;" ::: "memory");
    uint32_t rdst[2], rbar[2];
#pragma unroll
    for (int e = 0; e < 2; e++) {
        rdst[e] = mapa(sbase + F_RECV + rank * 256 + g * 32 + t * 16, 4 * e + w);
        rbar[e] = mapa(sbase + F_BAR, 4 * e + w);
    }
    while (ld_acquire_cta_shared(sbase + M_HELP + 28) == 0) { __nanosleep(200); if (++n > SPIN_LIMIT) __trap(); }
    const uint32_t da = (1u << 16) | (((sbase + F_W) & 0x3ffff) >> 4), db = (4u << 16) | (((sbase + F_X) & 0x3ffff) >> 4);
    float d[2][4] = {0.f, 0.f, 0.f, 0.f, 0.f, 0.f, 0.f, 0.f};
#pragma unroll
    for (int i = 0; i < 7; i++) {
        const int e = i >> 2;
        mbar_first(sbase + F_BAR + 16 + i * 8);
        asm volatile("wgmma.fence.sync.aligned;" ::: "memory");
        if (i == 0) {
            wgmma_k64(d[0], da, db + (rank & 1) * 32, 0);
            wgmma_k64(d[1], da + 512, db + 7 * (FXP / 16) + (rank & 1) * 32, 0);
        } else {
            wgmma_k64(d[e], da + (i % 6) * 1024, db + i * (FXP / 16), 1);
            wgmma_k64(d[e], da + (i % 6) * 1024 + 512, db + i * (FXP / 16) + 32, 1);
        }
        asm volatile("wgmma.commit_group.sync.aligned;" ::: "memory");
        if (i < 2 || i % 3 == 0)
            asm volatile("wgmma.wait_group.sync.aligned 0;" : "+f"(d[e][0]), "+f"(d[e][1]), "+f"(d[e][2]), "+f"(d[e][3])::"memory");
        if (i < 2) {
            asm volatile("{\n.reg .pred p;\nsetp.eq.u32 p, %1, 0;\n@p mbarrier.arrive.shared::cta.b64 _, [%0];\n}"
                         ::"r"(sbase + F_BAR + 80 + i * 8), "r"(lane) : "memory");
        } else if (i % 3 == 0) {
            if (t < 2)
                asm volatile("st.async.weak.shared::cluster.mbarrier::complete_tx::bytes.v4.f32 [%0], {%1,%2,%3,%4}, [%5];"
                             ::"r"(rdst[e]), "f"(d[e][0]), "f"(d[e][1]), "f"(d[e][2]), "f"(d[e][3]), "r"(rbar[e]) : "memory");
            __syncwarp();
        }
    }
}
__device__ __forceinline__ void out_issue(const Params& p, uint32_t sbase, int c, int rank, uint64_t pol) {
    unsigned n = 0;
    while (ld_acquire_cta_shared(sbase + M_HELP + 32) == 0) { __nanosleep(500); if (++n > SPIN_LIMIT) __trap(); }
#pragma unroll
    for (int i = 0; i < 6; i++) asm volatile("prefetch.tensormap [%0];" ::"l"(&p.tm_out[i >> 1][i & 1]) : "memory");
    uint32_t t0;
    while ((t0 = ld_acquire_cta_shared(sbase + M_HELP + 28)) == 0) { __nanosleep(100); if (++n > SPIN_LIMIT) __trap(); }
#pragma unroll
    for (int i = 0; i < 8; i++) {
        const uint32_t dst = sbase + F_W + (i % 6) * 16384, bar = sbase + F_BAR + 16 + i * 8;
        if (i >= 6) mbar_wait(sbase + F_BAR + 32 + i * 8, 0);
        for (int k = 0; k < 4096 && (int)(now_ns() - t0) < 0; k++) {}
        if (i == 0) {
            TS(16);
            tma4d(dst, &p.tm_out[0][0], c * 64, (rank & 1) * 4, 4 + (rank >> 1), bar, pol);
            tma4d(dst + 8192, &p.tm_out[0][1], c * 64, (rank & 1) * 4, 4 + (rank >> 1), bar, pol);
        } else if (i < 7) {
            tma4d(dst, &p.tm_out[1][i >> 2], c * 64, 0, ((i - 1) % 3 + 1) * 8 + rank, bar, pol);
        } else {
#pragma unroll
            for (int q = 0; q < 2; q++) {
                const int h = ((q + rank) & 1) * 2;
                tma4d(dst + h * 4096, &p.tm_out[2][rank >> 2], c * 64 + (rank & 3) * 16, 0, h, bar, pol);
            }
        }
        t0 += i == 6 ? FP - FN : FP;
    }
    TS(17);
}
__device__ __forceinline__ void out_final(const Params& p, uint32_t sbase, int c, int rank, int hf) {
    const int lane = threadIdx.x & 31, g = lane >> 2, t = lane & 3;
    unsigned n = 0;
    while (ld_acquire_cta_shared(sbase + M_HELP + 32) == 0) { if (++n > (SPIN_LIMIT << 4)) __trap(); }
    uint32_t bf[16][2];
#pragma unroll
    for (int s = 0; s < 16; s++) {
        const uint32_t a = sbase + F_X + (8 + 2 * (g >> 2) + (s >> 3)) * FXP + (s & 7) * 128 + (g & 3) * 16 + t * 4;
        bf[s][0] = lds32(a);
        bf[s][1] = lds32(a + 64);
    }
    __nv_bfloat16* dst = p.out + (2 * (t & 1) + (t >> 1)) * (2 * DM) + (rank < 4 ? DM : 0) + c * 64 + (rank & 3) * 16 + hf * 8 + g;
    uint32_t src = sbase + F_RECV + g * 32 + (t & 1) * 16 + hf * 8 + (t >> 1) * 4;
    uint32_t wa = sbase + F_W + 16384 + ((lane >> 3) & 1) * 8192 + ((lane & 7) + (lane >> 4) * 8) * 32 + ((hf ^ (lane >> 2)) & 1) * 16;
    wa += bf[15][1] & (gridDim.x >> 24);
    asm volatile("" : "+l"(dst), "+r"(src), "+r"(wa));
    float x[8];
    auto partials = [&]() {
        mbar_first_cluster(sbase + F_BAR);
#pragma unroll
        for (int i = 0; i < 8; i++) asm volatile("ld.shared.f32 %0, [%1];" : "=f"(x[i]) : "r"(src + i * 256) : "memory");
    };
    const bool pre = rank < 4;
    if (pre) partials();
    mbar_first(sbase + F_BAR + 16 + 7 * 8);
    uint32_t a[16][4];
    float acc[4][4];
#pragma unroll
    for (int i = 0; i < 16; i++) acc[i >> 2][i & 3] = 0.f;
#pragma unroll
    for (int s = 0; s < 16; s++) ldsm4t(a[s], wa + s * 512);
#pragma unroll
    for (int s = 0; s < 16; s++) mma16816(acc[s & 3], a[s], bf[s][0], bf[s][1]);
    float y[4];
#pragma unroll
    for (int i = 0; i < 4; i++) y[i] = (acc[0][i] + acc[1][i]) + (acc[2][i] + acc[3][i]);
    float v = __shfl_xor_sync(~0u, (t & 2) ? y[2] : y[1], 2);
    if (!pre) partials();
    v = (v + ((t & 2) ? y[3] : y[0])) + (((x[0] + x[1]) + (x[2] + x[3])) + ((x[4] + x[5]) + (x[6] + x[7])));
    asm volatile("{\n.reg .b16 h;\ncvt.rn.bf16.f32 h, %1;\nst.global.b16 [%0], h;\n}" ::"l"(dst), "f"(v) : "memory");
}

constexpr int BS_WUK = 5, BS_Q = 9, BS_CKV = 11, BS_PART = 27, BS_WUV = 29, BS_END = 33;

__device__ __noinline__ void b_issue(const Params& p, int n, int bi, uint32_t sbase, uint64_t pol) {
    if (n >= BS_END || (n >= BS_Q && n < BS_CKV) || (n >= BS_PART && n < BS_WUV)) return;
    const uint32_t bar = sbase + M_BAR + (NSLOT + n % BRING) * 8;
    const CUtensorMap* tm;
    int row, panel = 2 * bi;
    if (n < BS_WUK) { tm = &p.tm_wq; row = n * 128; }
    else if (n < BS_Q) { tm = &p.tm_wuk; row = (n - BS_WUK) * 128; }
    else if (n < BS_PART) {
        tm = &p.tm_ckv; panel = 0;
        row = (bi >> 3) * SK + ((n - BS_CKV) * 8 + (bi & 7)) * 32;
    }
    else { tm = &p.tm_wuv; row = (n - BS_WUV) * 128; }
    mbar_expect_tx(bar, n == 0 ? 32768 + 4 * 1152 : 32768);
    tma3d(sbase + (n % BRING) * SLOT, tm, 0, row, panel, bar, pol);
}
__device__ __forceinline__ void b_issue_xchg(int n, const void* src, uint32_t sbase, uint64_t pol) {
    asm volatile("fence.proxy.async;" ::: "memory");
#pragma unroll
    for (int i = 0; i < 2; i++) {
        const uint32_t bar = sbase + M_BAR + (NSLOT + (n + i) % BRING) * 8;
        mbar_expect_tx(bar, 32768);
        bulk_load(sbase + ((n + i) % BRING) * SLOT, reinterpret_cast<const char*>(src) + i * 32768, 32768, bar, pol);
    }
}
__device__ __forceinline__ void b_wait(int n, uint32_t sbase) {
    mbar_wait(sbase + M_BAR + (NSLOT + n % BRING) * 8, (n / BRING) & 1);
}

__device__ __noinline__ void b_gemm(const Params& p, uint32_t sbase, int n0, int n1, int ktot, uint32_t xh, uint32_t xl, int pitch,
                                    int bi, uint64_t pol) {
    const int tid = threadIdx.x, warp = tid >> 5, lane = tid & 31, g = lane >> 2, t = lane & 3;
    const uint32_t woff = (warp >> 2) * 16384 + (lane & 15) * 128 + ((((warp & 3) * 2 + (lane >> 4)) ^ (lane & 7)) * 16);
    const uint32_t xoff = (g & 3) * pitch + t * 4;
    float acc[2][4];
#pragma unroll
    for (int i = 0; i < 8; i++) acc[i >> 2][i & 3] = 0.f;
#pragma unroll 1
    for (int n = n0; n < n1; n++) {
        b_wait(n, sbase);
        const uint32_t slot = sbase + (n % BRING) * SLOT + woff;
        const int k0 = (n - n0) * 128;
        const int ns = min(8, (ktot - k0) >> 4);
#pragma unroll 2
        for (int s = 0; s < ns; s++) {
            uint32_t a[4], w[4];
            const uint32_t xo = xoff + (k0 + 16 * s) * 2;
            a[0] = lds32(xh + xo); a[2] = lds32(xh + xo + 16);
            a[1] = xl ? lds32(xl + xo) : 0u; a[3] = xl ? lds32(xl + xo + 16) : 0u;
            ldsm4t(w, slot + s * 2048);
            mma16816(acc[0], a, w[0], w[1]);
            mma16816(acc[1], a, w[2], w[3]);
        }
        __syncthreads();
        if (tid == 0) b_issue(p, n + BD, bi, sbase, pol);
    }
    if (g < 4) {
#pragma unroll
        for (int j = 0; j < 2; j++)
            asm volatile("st.shared.u32 [%0], %1;" ::"r"(sbase + M_QB + g * QP + (warp * 16 + j * 8 + t * 2) * 2),
                         "r"(pack_bf16(acc[j][0] + acc[j][2], acc[j][1] + acc[j][3])) : "memory");
    }
    __syncthreads();
}

__device__ __forceinline__ void b_exchange(unsigned* c, int n, const void* src, uint32_t sbase, uint64_t pol) {
    TS(n == BS_Q ? 24 : 28);
    __syncthreads();
    if (threadIdx.x == 0) {
        TS(n == BS_Q ? 25 : 29);
        fence_gpu();
        TS(n == BS_Q ? 26 : 30);
        red_add_u32(c, 1u);
        wait_count(c, NBCTA);
        TS(n == BS_Q ? 27 : 31);
        b_issue_xchg(n, src, sbase, pol);
    }
}

template <bool CLU>
__device__ __noinline__ void b_chain(const Params& p, char* smem, uint32_t sbase, int bi, unsigned epoch, uint64_t pol) {
    const int tid = threadIdx.x, warp = tid >> 5, lane = tid & 31, g = lane >> 2, t = lane & 3;
    unsigned (*ctl)[32] = g_ctl[epoch & 1];
    float* red = reinterpret_cast<float*>(smem + 5 * SLOT);
    b_gemm(p, sbase, 0, BS_WUK, DM, sbase + M_XB, 0, XP, bi, pol);
    TS(6);
    {
        uint32_t Q[16];
#pragma unroll
        for (int c = 0; c < 16; c++) Q[c] = lds32(sbase + M_QB + (g & 3) * QP + c * 16 + t * 4);
        float* qa = reinterpret_cast<float*>(smem + M_QA);
#pragma unroll 1
        for (int n = BS_WUK; n < BS_Q; n++) {
            b_wait(n, sbase);
            const uint32_t base = sbase + (n % BRING) * SLOT + (warp * 16 + (lane & 15)) * 128;
            float d[2][4];
#pragma unroll
            for (int i = 0; i < 8; i++) d[i >> 2][i & 3] = 0.f;
#pragma unroll
            for (int s = 0; s < 8; s++) {
                uint32_t a[4];
                ldsm4(a, base + (s >> 2) * 16384 + (((2 * (s & 3) + (lane >> 4)) ^ (lane & 7)) * 16));
                mma16816(d[s & 1], a, Q[2 * s], Q[2 * s + 1]);
            }
            const int c = (n - BS_WUK) * 128 + warp * 16 + g + 8 * (t >> 1);
            qa[(2 * (t & 1)) * 512 + c] = (t & 2) ? d[0][2] + d[1][2] : d[0][0] + d[1][0];
            qa[(2 * (t & 1) + 1) * 512 + c] = (t & 2) ? d[0][3] + d[1][3] : d[0][1] + d[1][1];
            __syncthreads();
            if (tid == 0) b_issue(p, n + BD, bi, sbase, pol);
        }
#pragma unroll 1
        for (int r = 0; r < 2; r++) {
            const int id = tid + r * 256;
            const int b = id >> 7, c0 = ((id >> 2) & 31) * 16 + (id & 3) * 2;
            const float2 u0 = *reinterpret_cast<const float2*>(qa + b * 512 + c0);
            const float2 u1 = *reinterpret_cast<const float2*>(qa + b * 512 + c0 + 8);
            const uint32_t h0 = pack_bf16(u0.x, u0.y), h1 = pack_bf16(u1.x, u1.y);
            const uint32_t l0 = pack_bf16(u0.x - bf_lo(h0), u0.y - bf_hi(h0)), l1 = pack_bf16(u1.x - bf_lo(h1), u1.y - bf_hi(h1));
            g_qabs[((id >> 2) * 4 + (bi >> 3)) * 32 + (bi & 7) * 4 + (id & 3)] = make_uint4(h0, l0, h1, l1);
        }
    }
    b_exchange(&ctl[C_BBAR][0], BS_Q, &g_qabs[(bi >> 3) * 4096], sbase, pol);
    {
        uint32_t qf[4][4][4];
        b_wait(BS_Q + (warp >> 2), sbase);
        TS(7);
        {
            const uint4* qs = reinterpret_cast<const uint4*>(smem + ((BS_Q + (warp >> 2)) % BRING) * SLOT) + (warp & 3) * 512 + lane;
#pragma unroll
            for (int s = 0; s < 4; s++)
#pragma unroll
                for (int i = 0; i < 4; i++) {
                    const uint4 v = qs[(s * 4 + i) * 32];
                    qf[i][s][0] = v.x; qf[i][s][1] = v.y; qf[i][s][2] = v.z; qf[i][s][3] = v.w;
                }
        }
        __syncthreads();
        if (tid == 0) { b_issue(p, BS_Q + BD, bi, sbase, pol); b_issue(p, BS_Q + 1 + BD, bi, sbase, pol); }
        float acc[2][8][4];
#pragma unroll
        for (int i = 0; i < 2; i++)
#pragma unroll
            for (int j = 0; j < 8; j++) { acc[i][j][0] = acc[i][j][1] = acc[i][j][2] = acc[i][j][3] = 0.f; }
        float mrun = -INFINITY, lrun = 0.f;
        const int head = tid >> 3, kq = tid & 7;
        float* alpha = reinterpret_cast<float*>(smem + M_ALPHA);
        for (int n = BS_CKV; n < BS_PART; n++) {
            b_wait(n, sbase);
            const uint32_t slot = sbase + (n % BRING) * SLOT;
            float sc[4][4][4];
#pragma unroll
            for (int i = 0; i < 4; i++)
#pragma unroll
                for (int j = 0; j < 4; j++) { sc[i][j][0] = sc[i][j][1] = sc[i][j][2] = sc[i][j][3] = 0.f; }
#pragma unroll
            for (int j = 0; j < 4; j++)
#pragma unroll
                for (int sp = 0; sp < 2; sp++) {
                    uint32_t bf[4];
                    ldsm4(bf, slot + warp * 4096 + (8 * j + (lane & 7)) * 128 + (((4 * sp + (lane >> 3)) ^ (lane & 7)) * 16));
#pragma unroll
                    for (int i = 0; i < 4; i++) {
                        mma16816(sc[i][j], qf[i][2 * sp], bf[0], bf[1]);
                        mma16816(sc[i][j], qf[i][2 * sp + 1], bf[2], bf[3]);
                    }
                }
#pragma unroll
            for (int i = 0; i < 4; i++)
#pragma unroll
                for (int j = 0; j < 4; j++)
                    *reinterpret_cast<float2*>(red + warp * 1024 + (8 * i + g) * 32 + ((8 * j) ^ (8 * (g & 3))) + 2 * t) =
                        make_float2(sc[i][j][0] + sc[i][j][2], sc[i][j][1] + sc[i][j][3]);
            __syncthreads();
            if (tid == 0 && n > BS_CKV) b_issue(p, n - 1 + BD, bi, sbase, pol);
            {
                float4 s = make_float4(0.f, 0.f, 0.f, 0.f);
#pragma unroll
                for (int w = 0; w < 8; w++) {
                    const float4 v = *reinterpret_cast<const float4*>(red + w * 1024 + head * 32 + ((4 * kq) ^ (8 * (head & 3))));
                    s.x += v.x; s.y += v.y; s.z += v.z; s.w += v.w;
                }
                const uint32_t r0 = pack_bf16(s.x, s.y), r1 = pack_bf16(s.z, s.w);
                const uint32_t s0 = pack_bf16(bf_lo(r0) * SCALE, bf_hi(r0) * SCALE);
                const uint32_t s1 = pack_bf16(bf_lo(r1) * SCALE, bf_hi(r1) * SCALE);
                const float f0 = bf_lo(s0), f1 = bf_hi(s0), f2 = bf_lo(s1), f3 = bf_hi(s1);
                float mx = fmaxf(fmaxf(f0, f1), fmaxf(f2, f3));
                mx = fmaxf(mx, __shfl_xor_sync(~0u, mx, 1));
                mx = fmaxf(mx, __shfl_xor_sync(~0u, mx, 2));
                mx = fmaxf(mx, __shfl_xor_sync(~0u, mx, 4));
                const float mnew = fmaxf(mrun, mx);
                const float al = expsub(mrun, mnew);
                const float p0 = expsub(f0, mnew), p1 = expsub(f1, mnew), p2 = expsub(f2, mnew), p3 = expsub(f3, mnew);
                lrun = lrun * al + ((p0 + p1) + (p2 + p3));
                mrun = mnew;
                *reinterpret_cast<uint2*>(smem + M_P + head * 80 + kq * 8) = make_uint2(pack_bf16(p0, p1), pack_bf16(p2, p3));
                if (kq == 0) alpha[head] = al;
            }
            __syncthreads();
            {
                uint32_t pf[2][2][4];
#pragma unroll
                for (int i = 0; i < 2; i++)
#pragma unroll
                    for (int ks = 0; ks < 2; ks++)
                        ldsm4(pf[i][ks], sbase + M_P + (16 * i + (lane & 15)) * 80 + (16 * ks + 8 * (lane >> 4)) * 2);
#pragma unroll
                for (int i = 0; i < 2; i++) {
                    const float a0 = alpha[16 * i + g], a1 = alpha[16 * i + 8 + g];
#pragma unroll
                    for (int j = 0; j < 8; j++) { acc[i][j][0] *= a0; acc[i][j][1] *= a0; acc[i][j][2] *= a1; acc[i][j][3] *= a1; }
                }
#pragma unroll
                for (int j = 0; j < 8; j++) {
                    uint32_t bf[4];
                    ldsm4t(bf, slot + warp * 4096 + lane * 128 + ((j ^ (lane & 7)) * 16));
#pragma unroll
                    for (int i = 0; i < 2; i++) {
                        mma16816(acc[i][j], pf[i][0], bf[0], bf[1]);
                        mma16816(acc[i][j], pf[i][1], bf[2], bf[3]);
                    }
                }
            }
        }
        __syncthreads();
        if (tid == 0) b_issue(p, BS_PART - 1 + BD, bi, sbase, pol);
        lrun += __shfl_xor_sync(~0u, lrun, 1);
        lrun += __shfl_xor_sync(~0u, lrun, 2);
        lrun += __shfl_xor_sync(~0u, lrun, 4);
        if (kq == 0) g_bml[head * NBCTA + bi] = make_float2(mrun, lrun);
#pragma unroll
        for (int i = 0; i < 2; i++)
#pragma unroll
            for (int j = 0; j < 8; j++) {
                g_bpart[((16 * i + g) * NBCTA + bi) * 256 + warp * 32 + j * 4 + t] = make_float2(acc[i][j][0], acc[i][j][1]);
                g_bpart[((16 * i + 8 + g) * NBCTA + bi) * 256 + warp * 32 + j * 4 + t] = make_float2(acc[i][j][2], acc[i][j][3]);
            }
    }
#pragma unroll 1
    for (int i = tid; i < NH * 36 && !(CLU); i += 256) g_outb[bi * NH * 36 + i] = make_uint4(0u, epoch, 0u, epoch);
    b_exchange(&ctl[C_BBAR + 1][0], BS_PART, &g_bpart[bi * NBCTA * 256], sbase, pol);
    {
        float* omega = reinterpret_cast<float*>(smem + M_OMEGA);
        if (warp == 0) {
            __syncwarp();
            const uint2 ml = ld_relaxed8(&g_bml[bi * NBCTA + lane]);
            const float ms = __uint_as_float(ml.x);
            float m = ms;
            m = fmaxf(m, __shfl_xor_sync(~0u, m, 1));
            m = fmaxf(m, __shfl_xor_sync(~0u, m, 2));
            m = fmaxf(m, __shfl_xor_sync(~0u, m, 4));
            const float w = expsub(ms, m);
            float l = w * __uint_as_float(ml.y);
            l += __shfl_xor_sync(~0u, l, 1);
            l += __shfl_xor_sync(~0u, l, 2);
            l += __shfl_xor_sync(~0u, l, 4);
            omega[lane] = w / l;
        }
        __syncthreads();
        b_wait(BS_PART, sbase);
        b_wait(BS_PART + 1, sbase);
#pragma unroll 1
        for (int b = 0; b < 4; b++) {
            const float2* ps = reinterpret_cast<const float2*>(smem + ((BS_PART + (b >> 1)) % BRING) * SLOT) + (b & 1) * 2048 + tid;
            float c0 = 0.f, c1 = 0.f;
#pragma unroll
            for (int s = 0; s < 8; s++) {
                const float w = omega[b * 8 + s];
                const float2 v = ps[s * 256];
                c0 = fmaf(w, v.x, c0);
                c1 = fmaf(w, v.y, c1);
            }
            const uint32_t hi = pack_bf16(c0, c1);
            *reinterpret_cast<uint32_t*>(smem + M_CH + b * CP + tid * 4) = hi;
            *reinterpret_cast<uint32_t*>(smem + M_CL + b * CP + tid * 4) = pack_bf16(c0 - bf_lo(hi), c1 - bf_hi(hi));
        }
        __syncthreads();
        if (tid == 0) { b_issue(p, BS_PART + BD, bi, sbase, pol); b_issue(p, BS_PART + 1 + BD, bi, sbase, pol); }
    }
    b_gemm(p, sbase, BS_WUV, BS_END, 512, sbase + M_CH, sbase + M_CL, CP, bi, pol);
    TS(12);
    if (CLU) {
        if (tid < 128) {
            const uint32_t xo = sbase + M_QB + ((tid >> 1) & 3) * QP + (tid >> 3) * 16 + (tid & 1) * 8;
            st_tagged2(&g_ctx[bi * 128 + tid], __uint_as_float(lds32(xo)), __uint_as_float(lds32(xo + 4)), epoch + 1);
        }
        return;
    }
    if (tid == 0) {
#pragma unroll 1
        for (int i = 0; i < 4; i++) {
            mbar_expect_tx(sbase + M_BAR + i * 8, 36864);
            tma3d(sbase + i * 36864, &p.tm_wo, 0, bi * 128 + i * 32, 0, sbase + M_BAR + i * 8, pol);
        }
    }
    TS(8);
    {
        float acc[9][4];
#pragma unroll
        for (int j = 0; j < 9; j++) { acc[j][0] = acc[j][1] = acc[j][2] = acc[j][3] = 0.f; }
#pragma unroll 1
        for (int i = 0; i < 4; i++) {
            const uint32_t xo = sbase + M_QB + (g & 3) * QP + i * 64 + t * 4;
            const uint32_t a0[4] = {lds32(xo), 0u, lds32(xo + 16), 0u}, a1[4] = {lds32(xo + 32), 0u, lds32(xo + 48), 0u};
            mbar_wait(sbase + M_BAR + i * 8, 0);
#pragma unroll
            for (int j = 0; j < 9; j++) {
                const int nt = warp * 9 + j;
                uint32_t w[4];
                ldsm4t(w, sbase + i * 36864 + (nt >> 3) * 4096 + lane * 128 + (((nt & 7) ^ (lane & 7)) * 16));
                mma16816(acc[j], a0, w[0], w[1]);
                mma16816(acc[j], a1, w[2], w[3]);
            }
        }
        if (g < 4) {
#pragma unroll
            for (int j = 0; j < 9; j++) {
                const int c2 = (warp * 9 + j) * 4 + t;
                st_tagged2(&g_outb[((c2 / 9) * NH + bi) * 36 + g * 9 + c2 % 9], acc[j][0], acc[j][1], epoch + 1);
            }
        }
    }
    TS(9);
    {
        const uint4* src = g_outb + (bi * NH + (tid >> 3)) * 36 + (tid & 7);
        float2* part = reinterpret_cast<float2*>(red);
        unsigned n = 0;
        while (true) {
            ulonglong2 v[5];
            bool ok = true;
#pragma unroll
            for (int i = 0; i < 5; i++)
                if (i < 4 || (tid & 7) < 4) v[i] = ld_tagged2(src + i * 8);
#pragma unroll
            for (int i = 0; i < 5; i++)
                if (i < 4 || (tid & 7) < 4) {
                    ok = ok && (unsigned)(v[i].x >> 32) == epoch + 1 && (unsigned)(v[i].y >> 32) == epoch + 1;
                    part[(tid >> 3) * 36 + (tid & 7) + i * 8] = make_float2(__uint_as_float((unsigned)v[i].x), __uint_as_float((unsigned)v[i].y));
                }
            if (ok) break;
            __nanosleep(400);
            if (++n > SPIN_LIMIT) __trap();
        }
        __syncthreads();
        if (tid < 36) {
            float s0 = 0.f, s1 = 0.f;
#pragma unroll 8
            for (int h = 0; h < NH; h++) { const float2 v = part[h * 36 + tid]; s0 += v.x; s1 += v.y; }
            *reinterpret_cast<uint32_t*>(p.out + (tid / 9) * 2 * DM + DM + bi * 18 + (tid % 9) * 2) = pack_bf16(s0, s1);
        }
    }
    TS(10);
}

template <bool CLU>
__global__ void __launch_bounds__(256, 1) fused_decode_kernel(const __grid_constant__ First f, const __grid_constant__ Params p) {
    extern __shared__ __align__(1024) char smem_raw[];
    const uint32_t sbase = (smem_u32(smem_raw) + 1023u) & ~1023u;
    char* smem = smem_raw + (sbase - smem_u32(smem_raw));
    const int tid = threadIdx.x, warp = tid >> 5, lane = tid & 31;
    asm volatile("{\n.reg .pred p;\nsetp.ne.u32 p, %1, 0;\n@p prefetch.global.L2 [%0];\n}"
                 ::"l"(f.ptr[tid >> 10] + (blockIdx.x * 8 + warp) * 8192 + lane * 128), "r"((uint32_t)(blockIdx.x < DM / 8 && lane < 16)) : "memory");
    const char* eptr = f.ptr[3 + (tid >> 10)];
    const int blk = CLU ? cluster_role(blockIdx.x) : blockIdx.x;
    const bool isB = CLU ? blk < NBCTA : (blk & 3) == 0 && (blk >> 2) < NBCTA;
    const int bi = CLU ? blk : blk >> 2;
    const int nb = CLU ? blk - NBCTA : blk - min(NBCTA, (blk + 3) >> 2);
    const int nblk = CLU ? 8 * MINCL : gridDim.x, nnb = nblk - NBCTA;
    constexpr int NFIRST = NW + XW + CLU;
    const int nstatic = nnb * NFIRST;
    uint64_t pol, poln;
    asm volatile("createpolicy.fractional.L2::evict_first.b64 %0, 1.0;" : "=l"(pol));
    asm volatile("createpolicy.fractional.L2::evict_normal.b64 %0, 1.0;" : "=l"(poln));
    const uint32_t wbar = sbase + M_BAR + warp * 8, wslot = sbase + warp * SLOT;
    const bool hold = blk < 16;
    const uint32_t jbar = sbase + M_BAR + (NSLOT + BRING) * 8, fbar = sbase + M_BAR + 4 * 8;
    if (warp < 4) {
        if (lane == 0) {
            if (warp == 0) {
                mbar_init(jbar, 1);
                asm volatile("fence.mbarrier_init.release.cluster;" ::: "memory");
                mbar_expect_tx(jbar, 36864 + 4 * 1152);
                if (CLU || blk < 128) tma3d(sbase + J0W, &p.tm_j0, blk * 32, 0, 0, jbar, poln);
            } else if (warp & 1) {
                if (warp & 2) {
#pragma unroll
                    for (int i = 0; i < NSLOT + BRING; i++) mbar_init(sbase + M_BAR + i * 8, 1);
                    mbar_expect_tx(fbar, NEARLY * TILE_BYTES);
                } else if (CLU && !isB) {
                    mbar_init(sbase + F_BAR, 1);
                    mbar_expect_tx(sbase + F_BAR, 2048);
                }
                asm volatile("fence.mbarrier_init.release.cluster;" ::: "memory");
            } else {
#pragma unroll
                for (int i = 0; i < 4; i++) asm volatile("st.shared.v4.u32 [%0], {%1,%1,%1,%1};" ::"r"(sbase + M_HELP + i * 16), "r"(0) : "memory");
            }
        }
    } else if (blockIdx.x >= DM / 8) {
        if (tid == 128) {
            asm volatile("prefetch.tensormap [%0];" ::"l"(&p.tm_j0) : "memory");
            asm volatile("prefetch.tensormap [%0];" ::"l"(&p.tm_wq) : "memory");
        } else if (blockIdx.x == DM / 8 + 4 && tid >= 220) {
            asm volatile("prefetch.global.L2 [%0];" ::"l"(f.ptr[2 + (tid >> 10)] + (tid - 220) * 128) : "memory");
        }
    }
    __syncthreads();
    if (tid == 128) {
        if (CLU || blk < 128) bulk_load(sbase + M_XA, f.ptr[2], 4608, jbar, poln);
        if (!isB && !hold) bulk_load(sbase, block_src(f.ptr[1], unit_block(nb * NEARLY)), NEARLY * TILE_BYTES, fbar, pol);
    }
    const int u0 = ((warp / NEARLY) * nnb + nb) * NEARLY + warp % NEARLY;
    unsigned epoch = 0;
    if (lane == 0) epoch = ld_relaxed4(eptr);
    TS(0);
    if (CLU && (unsigned)nb < NFIN) asm volatile("barrier.cluster.arrive.relaxed.aligned;" ::: "memory");
    if ((warp >> 1) == 2 && blk < 128) st_relaxed64(&g_qll[((tid - 128) >> 4) * 2048 + blk * 16 + (tid & 15)], 0ull);
    if (isB || warp >= NW + XW) epoch = __shfl_sync(~0u, epoch, 0);
    if (isB && tid == 96) {
        if (hold) { unsigned n = 0; while (ld_acquire_cta_shared(sbase + M_HELP + 24) < 2) { if (++n > (SPIN_LIMIT << 4)) __trap(); } }
#pragma unroll 1
        for (int b = 0; b < 4; b++) bulk_load(sbase + M_XB + b * XP, p.xb + b * DM, 1152, sbase + M_BAR + NSLOT * 8, pol);
#pragma unroll 1
        for (int n = 0; n < BD; n++) b_issue(p, n, bi, sbase, pol);
    }
    if (warp >= 4 && blk < 128) {
        const int g = lane >> 2, t = lane & 3, j = tid - 128;
#pragma unroll 1
        for (int sl = blk, ph = 0;; sl += 128 - nblk, ph = 1) {
        mbar_wait(jbar, ph);
        TS(13);
        float acc[4][4];
#pragma unroll
        for (int i = 0; i < 16; i++) acc[i >> 2][i & 3] = 0.f;
        const uint32_t wa = sbase + J0W + ((warp - 4) * 144 + (lane & 15)) * 64;
        const uint32_t sw = (lane >> 1) & 3, xa = sbase + M_XA + (g & 3) * 1152 + (warp - 4) * 288 + t * 4;
#pragma unroll 3
        for (int s = 0; s < 9; s++) {
            const uint32_t a[4] = {lds32(xa + s * 32), 0u, lds32(xa + s * 32 + 16), 0u};
            uint32_t w0[4], w1[4];
            ldsm4t(w0, wa + s * 1024 + (((lane >> 4) ^ sw) * 16));
            ldsm4t(w1, wa + s * 1024 + (((2 + (lane >> 4)) ^ sw) * 16));
            mma16816(acc[0], a, w0[0], w0[1]);
            mma16816(acc[1], a, w0[2], w0[3]);
            mma16816(acc[2], a, w1[0], w1[1]);
            mma16816(acc[3], a, w1[2], w1[3]);
        }
        float2* j0 = reinterpret_cast<float2*>(smem + M_J0);
        if (g < 4) {
#pragma unroll
            for (int i = 0; i < 4; i++) j0[(warp - 4) * 64 + g * 16 + i * 4 + t] = make_float2(acc[i][0], acc[i][1]);
        }
        asm volatile("bar.sync 1, 128;" ::: "memory");
        const bool again = sl == blk && blk + 128 - nblk >= nblk;
        if (again && tid == 224) {
            mbar_expect_tx(jbar, 36864);
            tma3d(sbase + J0W, &p.tm_j0, (blk + 128 - nblk) * 32, 0, 0, jbar, pol);
        }
        if (warp < 6) {
            const float2 v0 = j0[j], v1 = j0[64 + j], v2 = j0[128 + j], v3 = j0[192 + j];
            st_relaxed64(&g_qll[(j >> 4) * 2048 + sl * 16 + (j & 15)],
                         (unsigned long long)pack_bf16((v0.x + v1.x) + (v2.x + v3.x), (v0.y + v1.y) + (v2.y + v3.y)) |
                             ((unsigned long long)(epoch + 1) << 32));
            __syncwarp();
            if (lane == 0) asm volatile("red.relaxed.cta.shared::cta.add.u32 [%0], 1;" ::"r"(sbase + M_HELP + 24) : "memory");
        } else if (warp == 7) {
            if (blk < C_LINES) g_ctl[(epoch & 1) ^ 1][blk][lane] = 0;
        }
        TS(1);
        if (!again) break;
        asm volatile("bar.sync 1, 128;" ::: "memory");
        }
    }
    if (isB) {
        b_chain<CLU>(p, smem, sbase, bi, epoch, pol);
        return;
    }
    if (warp < NW + XW) {
        const bool twice = CLU && warp == 3;
        if (twice) {
            epoch = __shfl_sync(~0u, epoch, 0);
            if (lane == 0) {
                mbar_expect_tx(fbar + 8, TILE_BYTES);
                bulk_load(wslot + SLOT, block_src(p.kc, unit_block(4 * nnb + nb)), TILE_BYTES, fbar + 8, pol);
            }
        }
#pragma unroll 1
        for (int r = 0; r <= twice; r++)
            a_worker<CLU>(p, r ? 4 * nnb + nb : u0, warp >= NW + (((nb * 5) & 7) < (CLU ? X3C : X3) ? 1 : 0), hold, nstatic, wslot + r * SLOT, wbar,
                          r ? fbar + 8 : warp < NEARLY && !hold ? fbar : wbar, sbase + M_HELP, epoch, pol);
        if (CLU && nb < NFIN) {
            if (tid == 96) out_issue(p, sbase, nb >> 3, nb & 7, pol);
            __syncwarp();
            if (warp & 1) out_final(p, sbase, nb >> 3, nb & 7, warp >> 1);
            else if (warp == 0) out_late(sbase, nb & 7);
        }
        return;
    } else if (warp == 7) {
#pragma unroll 1
        for (int i = nb; i < 4 * NH; i += nnb) g_oacc[i * 32 + lane] = make_float4(0.f, 0.f, 0.f, 0.f);
        if (nb < NREP * NH) g_vdone[nb][lane] = 0;
        __syncwarp();
        k_helper(sbase + M_HELP, epoch, NFIRST);
        if (nb == 0 && lane == 0) g_epoch = epoch + 1;
        __syncwarp();
        if (CLU && nb < NFIN) out_early(sbase, nb & 7, epoch + 1);
    } else if (CLU) {
    } else if (warp == 6 && nb < NFIN) {
        finisher(p, sbase, nb);
        TS(4);
    } else if (warp >= 6 - NPOLL && nb < NFIN) {
        v_poller(sbase, nb, warp - (6 - NPOLL));
    }
    if (CLU && nb < NFIN) out_project(sbase, nb & 7, warp - 4);
}

}

typedef CUresult (*EncodeFn)(CUtensorMap*, CUtensorMapDataType, cuuint32_t, void*, const cuuint64_t*, const cuuint64_t*,
                             const cuuint32_t*, const cuuint32_t*, CUtensorMapInterleave, CUtensorMapSwizzle,
                             CUtensorMapL2promotion, CUtensorMapFloatOOBfill);

extern "C" void kernel_launch(void* const* d_in, const int* in_sizes, int n_in, void* d_out, int out_size) {
    (void)in_sizes; (void)n_in; (void)out_size;
    static int nsm = 0, ncl = 0;
    static EncodeFn encode = nullptr;
    static const char* epoch_ptr = nullptr;
    cudaLaunchConfig_t cfg = {};
    cudaLaunchAttribute at[1];
    at[0].id = cudaLaunchAttributeClusterDimension;
    at[0].val.clusterDim.x = 8; at[0].val.clusterDim.y = 1; at[0].val.clusterDim.z = 1;
    cfg.blockDim = dim3(256); cfg.dynamicSmemBytes = SMEM_BYTES; cfg.stream = cudaStreamPerThread; cfg.attrs = at; cfg.numAttrs = 1;
    if (nsm == 0) {
        int dev = 0;
        cudaGetDevice(&dev);
        cudaDeviceGetAttribute(&nsm, cudaDevAttrMultiProcessorCount, dev);
        cudaFuncSetAttribute(fused_decode_kernel<false>, cudaFuncAttributeMaxDynamicSharedMemorySize, SMEM_BYTES);
        cudaFuncSetAttribute(fused_decode_kernel<true>, cudaFuncAttributeMaxDynamicSharedMemorySize, SMEM_BYTES);
        cfg.gridDim = dim3(128);
        if (cudaOccupancyMaxActiveClusters(&ncl, fused_decode_kernel<true>, &cfg) != cudaSuccess) { ncl = 0; (void)cudaGetLastError(); }
        if (ncl > MINCL) ncl = MINCL;
        cudaGetSymbolAddress((void**)&epoch_ptr, g_epoch);
        void* fn = nullptr;
        cudaDriverEntryPointQueryResult qr;
        cudaGetDriverEntryPoint("cuTensorMapEncodeTiled", &fn, cudaEnableDefault, &qr);
        encode = (EncodeFn)fn;
    }
    Params p;
    auto panels = [&](CUtensorMap* tm, void* ptr, int rows, int cols, int box_rows, int box_panels) {
        const cuuint64_t gd[3] = {64, (cuuint64_t)rows, (cuuint64_t)(cols / 64)}, gs[2] = {(cuuint64_t)cols * 2, 128};
        const cuuint32_t box[3] = {64, (cuuint32_t)box_rows, (cuuint32_t)box_panels}, es[3] = {1, 1, 1};
        encode(tm, CU_TENSOR_MAP_DATA_TYPE_BFLOAT16, 3, ptr, gd, gs, box, es, CU_TENSOR_MAP_INTERLEAVE_NONE,
               CU_TENSOR_MAP_SWIZZLE_128B, CU_TENSOR_MAP_L2_PROMOTION_L2_256B, CU_TENSOR_MAP_FLOAT_OOB_FILL_NONE);
    };
    panels(&p.tm_wq, d_in[7], DM, 4096, 128, 2);
    panels(&p.tm_wuk, d_in[8], 512, 4096, 128, 2);
    panels(&p.tm_wuv, d_in[9], 512, 4096, 128, 2);
    panels(&p.tm_wo, d_in[10], 4096, DM, 32, 9);
    panels(&p.tm_ckv, d_in[6], 4 * SK, 512, 32, 8);
    {
        const cuuint64_t gd[3] = {4096, 192, 3}, gs[2] = {8192, 192 * 8192};
        const cuuint32_t box[3] = {32, 192, 3}, es[3] = {1, 1, 1};
        encode(&p.tm_j0, CU_TENSOR_MAP_DATA_TYPE_BFLOAT16, 3, d_in[3], gd, gs, box, es, CU_TENSOR_MAP_INTERLEAVE_NONE,
               CU_TENSOR_MAP_SWIZZLE_64B, CU_TENSOR_MAP_L2_PROMOTION_L2_128B, CU_TENSOR_MAP_FLOAT_OOB_FILL_NONE);
    }
    for (int i = 0; i < 6; i++) {
        const int k = i >> 1, a = i & 1;
        const cuuint64_t gd[4] = {DM, 16, 8, NH}, gs[3] = {(cuuint64_t)(a ? 8 : 1) * DM * 2, (cuuint64_t)(a ? 1 : 16) * DM * 2, 128 * DM * 2};
        const cuuint32_t box[4] = {k < 2 ? 64u : 16u, 16, k ? 8u : 4u, k < 2 ? 1u : 2u}, es[4] = {1, 1, 1, 1};
        encode(&p.tm_out[k][a], CU_TENSOR_MAP_DATA_TYPE_BFLOAT16, 4, d_in[a ? 4 : 10], gd, gs, box, es, CU_TENSOR_MAP_INTERLEAVE_NONE,
               k < 2 ? CU_TENSOR_MAP_SWIZZLE_128B : CU_TENSOR_MAP_SWIZZLE_32B,
               k < 2 ? CU_TENSOR_MAP_L2_PROMOTION_L2_256B : CU_TENSOR_MAP_L2_PROMOTION_L2_128B, CU_TENSOR_MAP_FLOAT_OOB_FILL_NONE);
    }
    p.kc = (const __nv_bfloat16*)d_in[1];
    p.vc = (const __nv_bfloat16*)d_in[2];
    p.wo = (const __nv_bfloat16*)d_in[4];
    p.xb = (const __nv_bfloat16*)d_in[5];
    p.out = (__nv_bfloat16*)d_out;
    const First f = {{(const char*)d_in[3], (const char*)d_in[1], (const char*)d_in[0], epoch_ptr}};
    if (ncl >= MINCL) {
        cfg.gridDim = dim3(8 * ncl);
        cudaLaunchKernelEx(&cfg, fused_decode_kernel<true>, f, p);
    } else {
        fused_decode_kernel<false><<<nsm, 256, SMEM_BYTES, cudaStreamPerThread>>>(f, p);
    }
}
```

```cpp
#include <cuda_runtime.h>
#include <cuda.h>
#include <cuda_bf16.h>
#include <stdint.h>

namespace {

constexpr int NH = 32, SK = 4096, DM = 576;
constexpr int KEYS = 128;
constexpr int UPP = SK / KEYS;
constexpr int NUK = 4 * NH * UPP;
constexpr int TILE_BYTES = KEYS * 256;
#define NWORK 2
constexpr int NW = NWORK;
constexpr int NBCTA = 32;
constexpr int MINCL = 15;
constexpr int NFIN = 72;
constexpr int SLOT = 32768;
constexpr int NSLOT = 6;
constexpr int BRING = 5;
constexpr int J0W = 5 * SLOT;
constexpr int MISC = NSLOT * SLOT + 4096;
constexpr int XP = 1168, CP = 1040, QP = 272;
constexpr int M_XA = MISC;
constexpr int M_XB = M_XA + 4 * XP;
constexpr int M_CH = M_XB + 4 * XP;
constexpr int M_CL = M_CH + 4 * CP;
constexpr int M_QB = M_CL + 4 * CP;
constexpr int M_QA = M_CH;
constexpr int M_J0 = M_QB + 4 * QP;
constexpr int M_P = M_J0 + 2048;
constexpr int M_ALPHA = M_P + 2560;
constexpr int M_OMEGA = M_ALPHA + 128;
constexpr int M_BAR = M_OMEGA + 128;
constexpr int M_HELP = M_BAR + 128;
constexpr int F_W = 3 * SLOT;
constexpr int F_X = NSLOT * SLOT, FXP = 1088;
constexpr int F_RECV = F_X + 12 * FXP;
constexpr int F_BAR = M_P;
constexpr int SMEM_BYTES = M_HELP + 128 + 1024;
static_assert(F_RECV + 2048 <= M_J0, "output phase layout");
static_assert(SMEM_BYTES <= 232448 && M_BAR % 8 == 0 && M_QA % 16 == 0 && M_P % 16 == 0, "smem layout");
#define XW 2
#define X3 2
#define X3C 3
#define NEARLY 2
#define BD 5
#define FPF 3
#define FSLEEP 800
#define FJ 250
#define FP 376
#define FN 32
#define NPOLL 2
#define PGAP 200
static_assert(NW + XW == 4 && 4 % NEARLY == 0 && BD <= BRING, "slots 4 and 5 hold the finisher weights");
constexpr float SCALE = 0.08838834764831845f;
constexpr float LOG2E = 1.4426950408889634f;
constexpr unsigned SPIN_LIMIT = 1u << 24;

#define NREP 2
constexpr int C_QUEUE = 0, C_KDONE = 1, C_BBAR = 3, C_LINES = 5;

struct First { const char* ptr[4]; };
struct Params {
    const __nv_bfloat16 *kc, *vc, *wo, *xb;
    __nv_bfloat16* out;
    CUtensorMap tm_j0;
    CUtensorMap tm_wq, tm_wuk, tm_ckv, tm_wuv, tm_wo;
    CUtensorMap tm_out[3][2];
};

__device__ unsigned g_epoch;
__device__ unsigned g_ctl[2][C_LINES][32];
__device__ uint2 g_qll[4 * 2048];
__device__ uint2 g_scores[128 * SK / 4];
__device__ float2 g_stats[128 * UPP];
__device__ float4 g_oacc[128 * 32];
__device__ unsigned g_vdone[NREP * NH][32];
__device__ uint4 g_qabs[4 * 8 * 4 * 4 * 32];
__device__ float2 g_bpart[NBCTA * NH * 256];
__device__ float2 g_bml[NBCTA * NH];
__device__ uint4 g_ctx[NH * 128];
__device__ uint4 g_outb[NBCTA * NH * 36];

__device__ __forceinline__ int cluster_role(int b) {
    const int i = b - NFIN, q = ((i >> 1) * 43 >> 7) * 2, r = i - 3 * q;
    int x = i - q;
    asm("{\n.reg .pred p;\nsetp.ge.s32 p, %1, 4;\nselp.s32 %0, %2, %0, p;\nsetp.lt.s32 p, %3, 0;\nselp.s32 %0, %4, %0, p;\n}"
        : "+r"(x) : "r"(r), "r"(NBCTA + NFIN - 4 + q + r), "r"(i), "r"(b + NBCTA));
    return x;
}

#define TS(i)
#define TSV(i, v)
#define LAND(i)
#define CLK(x)
#define ACC(a, x, y)

__device__ __forceinline__ uint32_t smem_u32(const void* p) { return (uint32_t)__cvta_generic_to_shared(p); }
__device__ __forceinline__ void mbar_init(uint32_t bar, uint32_t cnt) {
    asm volatile("mbarrier.init.shared::cta.b64 [%0], %1;" ::"r"(bar), "r"(cnt) : "memory");
}
__device__ __forceinline__ void mbar_expect_tx(uint32_t bar, uint32_t bytes) {
    asm volatile("mbarrier.arrive.expect_tx.shared::cta.b64 _, [%0], %1;" ::"r"(bar), "r"(bytes) : "memory");
}
__device__ __forceinline__ bool mbar_try(uint32_t bar, uint32_t parity) {
    uint32_t ok;
    asm volatile("{\n.reg .pred p;\nmbarrier.try_wait.parity.shared::cta.b64 p, [%1], %2;\nselp.u32 %0, 1, 0, p;\n}\n"
                 : "=r"(ok) : "r"(bar), "r"(parity) : "memory");
    return ok;
}
__device__ __forceinline__ void mbar_wait(uint32_t bar, uint32_t parity) {
    unsigned n = 0;
    while (!mbar_try(bar, parity)) { if (++n > SPIN_LIMIT) __trap(); }
}
__device__ __forceinline__ void bulk_load(uint32_t dst, const void* src, uint32_t bytes, uint32_t bar, uint64_t pol) {
    asm volatile("cp.async.bulk.shared::cluster.global.mbarrier::complete_tx::bytes.L2::cache_hint [%0], [%1], %2, [%3], %4;"
                 ::"r"(dst), "l"(src), "r"(bytes), "r"(bar), "l"(pol) : "memory");
}
__device__ __forceinline__ void tma3d(uint32_t dst, const CUtensorMap* tm, int c0, int c1, int c2, uint32_t bar, uint64_t pol) {
    asm volatile("cp.async.bulk.tensor.3d.shared::cluster.global.mbarrier::complete_tx::bytes.L2::cache_hint [%0], [%1, {%3,%4,%5}], [%2], %6;"
                 ::"r"(dst), "l"(tm), "r"(bar), "r"(c0), "r"(c1), "r"(c2), "l"(pol) : "memory");
}
__device__ __forceinline__ void tma4d(uint32_t dst, const CUtensorMap* tm, int c0, int c2, int c3, uint32_t bar, uint64_t pol) {
    asm volatile("cp.async.bulk.tensor.4d.shared::cluster.global.mbarrier::complete_tx::bytes.L2::cache_hint [%0], [%1, {%3,0,%4,%5}], [%2], %6;"
                 ::"r"(dst), "l"(tm), "r"(bar), "r"(c0), "r"(c2), "r"(c3), "l"(pol) : "memory");
}
__device__ __forceinline__ void l2_prefetch(const void* src, uint32_t bytes) {
    asm volatile("cp.async.bulk.prefetch.L2.global [%0], %1;" ::"l"(src), "r"(bytes) : "memory");
}
__device__ __forceinline__ void ldsm4(uint32_t (&r)[4], uint32_t addr) {
    asm volatile("ldmatrix.sync.aligned.m8n8.x4.shared.b16 {%0,%1,%2,%3}, [%4];"
                 : "=r"(r[0]), "=r"(r[1]), "=r"(r[2]), "=r"(r[3]) : "r"(addr));
}
__device__ __forceinline__ void ldsm4t(uint32_t (&r)[4], uint32_t addr) {
    asm volatile("ldmatrix.sync.aligned.m8n8.x4.trans.shared.b16 {%0,%1,%2,%3}, [%4];"
                 : "=r"(r[0]), "=r"(r[1]), "=r"(r[2]), "=r"(r[3]) : "r"(addr));
}
__device__ __forceinline__ void mma16816(float (&d)[4], const uint32_t (&a)[4], uint32_t b0, uint32_t b1) {
    asm("mma.sync.aligned.m16n8k16.row.col.f32.bf16.bf16.f32 {%0,%1,%2,%3}, {%4,%5,%6,%7}, {%8,%9}, {%0,%1,%2,%3};"
        : "+f"(d[0]), "+f"(d[1]), "+f"(d[2]), "+f"(d[3])
        : "r"(a[0]), "r"(a[1]), "r"(a[2]), "r"(a[3]), "r"(b0), "r"(b1));
}
__device__ __forceinline__ void wgmma_k64(float (&d)[4], uint32_t da, uint32_t db, int accumulate) {
    asm volatile("{\n.reg .pred p;\n.reg .b32 x, y;\n.reg .b64 a, b;\nsetp.ne.u32 p, %6, 0;\n"
                 "add.u32 x, %4, 0;\nadd.u32 y, %5, 0;\nmov.b64 a, {x, 0x40000040};\nmov.b64 b, {y, 1};\n"
                 "wgmma.mma_async.sync.aligned.m64n8k16.f32.bf16.bf16 {%0,%1,%2,%3}, a, b, p, 1, 1, 1, 0;\n"
                 "add.u32 x, %4, 128;\nadd.u32 y, %5, 8;\nmov.b64 a, {x, 0x40000040};\nmov.b64 b, {y, 1};\n"
                 "wgmma.mma_async.sync.aligned.m64n8k16.f32.bf16.bf16 {%0,%1,%2,%3}, a, b, 1, 1, 1, 1, 0;\n"
                 "add.u32 x, %4, 256;\nadd.u32 y, %5, 16;\nmov.b64 a, {x, 0x40000040};\nmov.b64 b, {y, 1};\n"
                 "wgmma.mma_async.sync.aligned.m64n8k16.f32.bf16.bf16 {%0,%1,%2,%3}, a, b, 1, 1, 1, 1, 0;\n"
                 "add.u32 x, %4, 384;\nadd.u32 y, %5, 24;\nmov.b64 a, {x, 0x40000040};\nmov.b64 b, {y, 1};\n"
                 "wgmma.mma_async.sync.aligned.m64n8k16.f32.bf16.bf16 {%0,%1,%2,%3}, a, b, 1, 1, 1, 1, 0;\n"
                 "}" : "+f"(d[0]), "+f"(d[1]), "+f"(d[2]), "+f"(d[3]) : "r"(da), "r"(db), "r"(accumulate) : "memory");
}
__device__ __forceinline__ uint32_t lds32(uint32_t a) {
    uint32_t v;
    asm volatile("ld.shared.u32 %0, [%1];" : "=r"(v) : "r"(a));
    return v;
}
__device__ __forceinline__ unsigned ld_acquire(const unsigned* p) {
    unsigned v;
    asm volatile("ld.acquire.gpu.global.u32 %0, [%1];" : "=r"(v) : "l"(p) : "memory");
    return v;
}
__device__ __forceinline__ uint2 ld_relaxed8(const void* p) {
    uint2 v;
    asm volatile("ld.relaxed.gpu.global.v2.u32 {%0,%1}, [%2];" : "=r"(v.x), "=r"(v.y) : "l"(p) : "memory");
    return v;
}
__device__ __forceinline__ unsigned ld_relaxed4(const void* p) {
    unsigned v;
    asm volatile("ld.relaxed.gpu.global.u32 %0, [%1];" : "=r"(v) : "l"(p) : "memory");
    return v;
}
__device__ __forceinline__ unsigned atom_inc(unsigned* p) {
    unsigned v;
    asm volatile("atom.relaxed.gpu.global.inc.u32 %0, [%1], 0x7fffffff;" : "=r"(v) : "l"(p) : "memory");
    return v;
}
__device__ __forceinline__ unsigned long long ld_relaxed64(const void* p) {
    unsigned long long v;
    asm volatile("ld.relaxed.gpu.global.u64 %0, [%1];" : "=l"(v) : "l"(p) : "memory");
    return v;
}
__device__ __forceinline__ void st_relaxed64(void* p, unsigned long long v) {
    asm volatile("st.relaxed.gpu.global.u64 [%0], %1;" ::"l"(p), "l"(v) : "memory");
}
__device__ __forceinline__ float4 ld_relaxed16(const void* p) {
    float4 v;
    asm volatile("ld.relaxed.gpu.global.v4.f32 {%0,%1,%2,%3}, [%4];" : "=f"(v.x), "=f"(v.y), "=f"(v.z), "=f"(v.w) : "l"(p) : "memory");
    return v;
}
__device__ __forceinline__ uint32_t mapa(uint32_t a, uint32_t rank) {
    uint32_t r;
    asm("mapa.shared::cluster.u32 %0, %1, %2;" : "=r"(r) : "r"(a), "r"(rank));
    return r;
}
__device__ __forceinline__ void mbar_first(uint32_t bar) {
    asm volatile("{\n.reg .pred p, q;\n.reg .u32 n;\nmov.u32 n, 0;\n"
                 "SPIN:\nmbarrier.try_wait.parity.shared::cta.b64 p, [%0], 0;\nadd.u32 n, n, 1;\nsetp.gt.u32 q, n, 0x1000000;\n@q trap;\n"
                 "@!p bra.uni SPIN;\n}" ::"r"(bar) : "memory");
}
__device__ __forceinline__ void mbar_first_cluster(uint32_t bar) {
    asm volatile("{\n.reg .pred p, q;\n.reg .u32 n;\nmov.u32 n, 0;\n"
                 "SPIN:\nmbarrier.try_wait.parity.relaxed.cluster.shared::cta.b64 p, [%0], 0;\nadd.u32 n, n, 1;\nsetp.gt.u32 q, n, 0x1000000;\n@q trap;\n"
                 "@!p bra.uni SPIN;\nfence.acquire.sync_restrict::shared::cluster.cluster;\n}" ::"r"(bar) : "memory");
}
__device__ __forceinline__ uint32_t now_ns() {
    unsigned long long t;
    asm volatile("mov.u64 %0, %globaltimer;" : "=l"(t));
    return (uint32_t)t;
}
__device__ __forceinline__ void fence_gpu() { asm volatile("fence.acq_rel.gpu;" ::: "memory"); }
__device__ __forceinline__ void red_add_u32(unsigned* p, unsigned v) {
    asm volatile("red.relaxed.gpu.global.add.u32 [%0], %1;" ::"l"(p), "r"(v) : "memory");
}
__device__ __forceinline__ void st_tagged2(void* p, float a, float b, unsigned tag) {
    const unsigned long long hi = (unsigned long long)tag << 32;
    asm volatile("st.relaxed.gpu.global.v2.b64 [%0], {%1,%2};" ::"l"(p), "l"(hi | __float_as_uint(a)), "l"(hi | __float_as_uint(b)) : "memory");
}
__device__ __forceinline__ ulonglong2 ld_tagged2(const void* p) {
    ulonglong2 v;
    asm volatile("ld.relaxed.gpu.global.v2.b64 {%0,%1}, [%2];" : "=l"(v.x), "=l"(v.y) : "l"(p) : "memory");
    return v;
}
__device__ __forceinline__ float4 atom_add_f4(void* p, float a, float b, float c, float d) {
    float4 r;
    asm volatile("atom.relaxed.gpu.global.add.v4.f32 {%0,%1,%2,%3}, [%4], {%5,%6,%7,%8};"
                 : "=f"(r.x), "=f"(r.y), "=f"(r.z), "=f"(r.w) : "l"(p), "f"(a), "f"(b), "f"(c), "f"(d) : "memory");
    return r;
}
__device__ __forceinline__ void red_release_cta_shared(uint32_t a, unsigned v) {
    asm volatile("red.release.cta.shared::cta.add.u32 [%0], %1;" ::"r"(a), "r"(v) : "memory");
}
__device__ __forceinline__ unsigned ld_acquire_cta_shared(uint32_t a) {
    unsigned v;
    asm volatile("ld.acquire.cta.shared::cta.u32 %0, [%1];" : "=r"(v) : "r"(a) : "memory");
    return v;
}
__device__ __forceinline__ void st_release_cta_shared(uint32_t a, unsigned v) {
    asm volatile("st.release.cta.shared::cta.u32 [%0], %1;" ::"r"(a), "r"(v) : "memory");
}
__device__ __forceinline__ void wait_count(const unsigned* p, unsigned target) {
    unsigned n = 0;
    while (ld_acquire(p) < target) { if (++n > SPIN_LIMIT) __trap(); }
}
__device__ __forceinline__ uint32_t pack_bf16(float lo, float hi) {
    uint32_t r;
    asm("cvt.rn.bf16x2.f32 %0, %1, %2;" : "=r"(r) : "f"(hi), "f"(lo));
    return r;
}
__device__ __forceinline__ float bf_lo(uint32_t v) { return __uint_as_float(v << 16); }
__device__ __forceinline__ float bf_hi(uint32_t v) { return __uint_as_float(v & 0xffff0000u); }
__device__ __forceinline__ float ex2(float x) { float y; asm("ex2.approx.ftz.f32 %0, %1;" : "=f"(y) : "f"(x)); return y; }
__device__ __forceinline__ float expsub(float a, float b) { return ex2((a - b) * LOG2E); }
__device__ __forceinline__ float warp_max(float v) {
#pragma unroll
    for (int m = 16; m; m >>= 1) v = fmaxf(v, __shfl_xor_sync(~0u, v, m));
    return v;
}
__device__ __forceinline__ float warp_sum(float v) {
#pragma unroll
    for (int m = 16; m; m >>= 1) v += __shfl_xor_sync(~0u, v, m);
    return v;
}
__device__ __forceinline__ unsigned unit_block(int u) {
    const unsigned v = u & (NUK - 1);
    return u < NUK ? (v & ~0x78u) | (v & 0x18u) << 2 | (v & 0x60u) >> 2 : v;
}
__device__ __forceinline__ const char* block_src(const void* base, unsigned blk) {
    const unsigned po = blk / UPP;
    return reinterpret_cast<const char*>(base) + (size_t)(((po & 3) * NH + (po >> 2)) * UPP + blk % UPP) * TILE_BYTES;
}

template <bool CLU>
__device__ __forceinline__ void a_worker(const Params& p, int un, int un2, bool once, bool hold, int nstatic, uint32_t slot, uint32_t bar, uint32_t wb,
                                         uint32_t help, unsigned epoch, uint64_t pol) {
    constexpr int NU = 2 * NUK;
    const int lane = threadIdx.x & 31, g = lane >> 2, t = lane & 3;
    const int li = lane & 7;
    uint32_t kaddr[4], vaddr[8];
    {
        const int e = (lane >> 3) & 1, kk = lane >> 4;
#pragma unroll
        for (int s = 0; s < 4; s++) kaddr[s] = slot + (16 * li + e) * 256 + ((2 * s + kk + li) & 7) * 16;
        const int vrow = 4 * (li >> 1) + (li & 1) + 2 * kk;
#pragma unroll
        for (int c = 0; c < 8; c++) vaddr[c] = slot + vrow * 256 + e * 128 + ((c + li) & 7) * 16;
#pragma unroll
        for (int c = 0; c < 8; c++) asm volatile("" : "+r"(vaddr[c]));
    }
    const uint32_t vmask = (g >> 1) != t ? 0u : ((g & 1) ? 0xffff0000u : 0xffffu);
    int kseen = -1;
    unsigned long long H0 = 0, H1 = 0;
    auto header = [&](int v, unsigned vb) {
        if (v >= NU) return;
        const void *a0, *a1;
        if (v < NUK) {
            const unsigned po = vb / UPP;
            a0 = g_qll + (po & 3) * 2048 + (po >> 2) * 64 + lane;
            a1 = reinterpret_cast<const uint2*>(a0) + 32;
        } else {
            const int half = vb / (NUK / 2);
            if (half > kseen) {
                unsigned n = 0;
                while (ld_acquire_cta_shared(help + 12 + 4 * half) == 0) { if (++n > (SPIN_LIMIT << 4)) __trap(); }
                kseen = half;
            }
            a0 = &g_scores[vb * (KEYS / 4) + lane];
            a1 = &g_stats[(vb / UPP) * UPP + lane];
        }
        H0 = ld_relaxed64(a0);
        H1 = ld_relaxed64(a1);
    };
    epoch = __shfl_sync(~0u, epoch, 0);
    if (hold) { unsigned n = 0; while (ld_acquire_cta_shared(help + 24) < 2) { if (++n > (SPIN_LIMIT << 4)) __trap(); } }
    unsigned (*ctl)[32] = g_ctl[epoch & 1];
    const unsigned tag = epoch + 1;
    unsigned nxt = un2 - nstatic;
    if (CLU && un2 < NU && lane == 0) {
        mbar_expect_tx(bar + 16, TILE_BYTES);
        bulk_load(slot + SLOT, block_src(p.kc, unit_block(un2)), TILE_BYTES, bar + 16, pol);
    }
    int u = -1;
    unsigned bu = 0, bn = unit_block(un);
    bool have = false;
    uint32_t phase = 0;
    unsigned kpend = 0;
    const unsigned zero = gridDim.x >> 24;
    uint32_t Q[16];
    float4 oret = make_float4(0.f, 0.f, 0.f, 0.f);
    while (true) {
        const char* nsrc = block_src(un < NUK ? p.kc : p.vc, bn);
        float4* odst = &g_oacc[(bu / UPP) * 32 + lane];
        unsigned* vdst = &g_vdone[(lane & (NREP - 1)) * NH + bu / (4 * UPP)][0];
        float d[8][4];
        CLK(c1);
        asm volatile("" : "+l"(odst));
        if (u >= NUK) {
#pragma unroll
            for (int j = 0; j < 8; j++) { d[j][0] = d[j][1] = d[j][2] = d[j][3] = 0.f; }
            mbar_wait(wb, phase);
            LAND(NUK + bu);
            uint32_t a[2][8][4];
#pragma unroll
            for (int c = 0; c < 8; c++) ldsm4t(a[0][c], vaddr[c]);
#pragma unroll
            for (int j = 0; j < 8; j++) {
                if (j < 7) {
#pragma unroll
                    for (int c = 0; c < 8; c++) ldsm4t(a[(j + 1) & 1][c], vaddr[c] + (j + 1) * 4096);
                }
#pragma unroll
                for (int c = 0; c < 8; c++) mma16816(d[c], a[j & 1][c], Q[2 * j], Q[2 * j + 1]);
            }
            float o[4];
#pragma unroll
            for (int r = 0; r < 2; r++) {
                o[2 * r] = d[0][2 * r] + d[7][2 * r + 1];
                o[2 * r + 1] = d[0][2 * r + 1] + d[1][2 * r];
#pragma unroll
                for (int k = 1; k < 4; k++) {
                    const int src = (lane & 28) | ((t - k) & 3);
                    o[2 * r] += __shfl_sync(~0u, d[2 * k][2 * r] + d[2 * k - 1][2 * r + 1], src);
                    o[2 * r + 1] += __shfl_sync(~0u, d[2 * k][2 * r + 1] + d[2 * k + 1][2 * r], src);
                }
            }
            oret = atom_add_f4(odst, o[0], o[1], o[2], o[3]);
        } else if (u >= 0) {
#pragma unroll
            for (int j = 0; j < 8; j++) { d[j][0] = d[j][1] = d[j][2] = d[j][3] = 0.f; }
            mbar_wait(wb, phase);
            LAND(bu);
            uint32_t a[2][8][4];
#pragma unroll
            for (int j = 0; j < 8; j++) ldsm4(a[0][j], kaddr[0] + (4 * (j & 3) + 2 * (j >> 2)) * 256);
#pragma unroll
            for (int s = 0; s < 8; s++) {
                if (s < 7) {
#pragma unroll
                    for (int j = 0; j < 8; j++)
                        ldsm4(a[(s + 1) & 1][j], kaddr[(s + 1) & 3] + (4 * (j & 3) + 2 * (j >> 2)) * 256 + ((s + 1) >> 2) * 128);
                }
#pragma unroll
                for (int j = 0; j < 8; j++)
                    mma16816(d[j], a[s & 1][j], Q[(s & 4) * 2 + ((2 * s - 2 * j) & 7)], Q[(s & 4) * 2 + ((2 * s + 1 - 2 * j) & 7)]);
            }
        }
        const bool pre = wb != bar;
        if (u >= 0) {
            phase = pre || once ? 0 : phase ^ 1;
            wb = once ? bar + 16 : bar;
            if (CLU && once) {
#pragma unroll
                for (int s = 0; s < 4; s++) kaddr[s] += SLOT;
            }
        }
        CLK(c2b);
        if (un < NU && lane == 0) {
            if (!once) nxt = atom_inc(&ctl[C_QUEUE][0]);
            if (u >= 0 ? !once : !pre) {
                mbar_expect_tx(bar, TILE_BYTES);
                bulk_load(slot, nsrc, TILE_BYTES, bar, pol);
            }
        }
        const uint32_t tiss = now_ns();
        CLK(c3);
        if ((unsigned)u < (unsigned)NUK) {
            const int j0 = (t - (g >> 1)) & 3;
            float v[4];
#pragma unroll
            for (int q = 0; q < 4; q++) {
                const int jq = (q >> 1) * 4, e = (q & 1) * 2;
                const float x0 = (g & 1) ? d[jq + 0][e + 1] : d[jq + 0][e];
                const float x1 = (g & 1) ? d[jq + 1][e + 1] : d[jq + 1][e];
                const float x2 = (g & 1) ? d[jq + 2][e + 1] : d[jq + 2][e];
                const float x3 = (g & 1) ? d[jq + 3][e + 1] : d[jq + 3][e];
                const float y0 = (j0 & 1) ? x1 : x0, y1 = (j0 & 1) ? x3 : x2;
                v[q] = (j0 & 2) ? y1 : y0;
            }
            const uint32_t r0 = pack_bf16(v[0], v[1]), r1 = pack_bf16(v[2], v[3]);
            const uint32_t s0 = pack_bf16(bf_lo(r0) * SCALE, bf_hi(r0) * SCALE);
            const uint32_t s1 = pack_bf16(bf_lo(r1) * SCALE, bf_hi(r1) * SCALE);
            g_scores[bu * (KEYS / 4) + 4 * g + j0] = make_uint2(s0, s1);
            const float f0 = bf_lo(s0), f1 = bf_hi(s0), f2 = bf_lo(s1), f3 = bf_hi(s1);
            const float m = warp_max(fmaxf(fmaxf(f0, f1), fmaxf(f2, f3)));
            const float l = warp_sum((expsub(f0, m) + expsub(f1, m)) + (expsub(f2, m) + expsub(f3, m)));
            if (lane == 0) g_stats[bu] = make_float2(m, l);
            kpend++;
            if (un / (NUK / 2) != u / (NUK / 2)) {
                __syncwarp();
                if (lane == 0) {
                    red_release_cta_shared(help + 4 * (u / (NUK / 2)), kpend);
                    if (un >= NUK) red_release_cta_shared(help + 8, 1u);
                }
                kpend = 0;
            }
        }
        CLK(c4);
        int unn = NU;
        if (un < NU) {
            unsigned n = 0;
            while (true) {
                if (!have) header(un, bn);
                if (un >= NUK || __all_sync(~0u, (uint32_t)(H0 >> 32) == tag && (uint32_t)(H1 >> 32) == tag)) break;
                if (++n > SPIN_LIMIT) __trap();
                have = false;
            }
            if (un >= NUK) {
                const uint32_t s0 = (uint32_t)H0, s1 = (uint32_t)(H0 >> 32);
                const float mu = __uint_as_float((uint32_t)H1);
                const float m = warp_max(mu);
                const float l = warp_sum(__uint_as_float((uint32_t)(H1 >> 32)) * expsub(mu, m));
                const float inv = 1.0f / l;
                const uint32_t w0 = pack_bf16(expsub(bf_lo(s0), m) * inv, expsub(bf_hi(s0), m) * inv);
                const uint32_t w1 = pack_bf16(expsub(bf_lo(s1), m) * inv, expsub(bf_hi(s1), m) * inv);
#pragma unroll
                for (int j = 0; j < 8; j++) {
                    Q[2 * j] = __shfl_sync(~0u, w0, 4 * j + t) & vmask;
                    Q[2 * j + 1] = __shfl_sync(~0u, w1, 4 * j + t) & vmask;
                }
            } else {
#pragma unroll
                for (int j = 0; j < 8; j++) {
                    const int src = (((j + g) & 7) << 2) + t;
                    Q[j] = __shfl_sync(~0u, (uint32_t)H0, src);
                    Q[8 + j] = __shfl_sync(~0u, (uint32_t)H1, src);
                }
            }
            if (u < 0) TS(2);
            unn = nstatic + (int)__shfl_sync(~0u, nxt, 0);
            nxt = NU;
            if (CLU && !once && unn >= NU && lane == 0)
                asm volatile("st.relaxed.cta.shared::cta.u32 [%0], %1;" ::"r"(help + 28), "r"((tiss + (FJ - (unn - NU)) * 10) | 1u) : "memory");
        }
        if (u >= NUK && lane < (CLU ? 1 : NREP))
            red_add_u32(vdst,
                        1u + ((__float_as_uint(oret.x) | __float_as_uint(oret.y) | __float_as_uint(oret.z) | __float_as_uint(oret.w)) & zero));
        if (un >= NU) break;
        bu = bn;
        have = !(un < NUK && unn >= NUK && !(un >= NUK / 2 && unn < NUK + NUK / 2));
        bn = unit_block(unn);
        if (have) header(unn, bn);
        u = un;
        un = unn;
    }
    TS(4);
}

__device__ __forceinline__ void k_helper(uint32_t help, unsigned epoch) {
    if ((threadIdx.x & 31) != 0) return;
    unsigned (*ctl)[32] = g_ctl[epoch & 1];
    unsigned sent0 = 0, sent1 = 0, n = 0;
    int seen = 0;
    bool fin = false;
    while (!fin || seen < 2) {
        if (!fin) {
            fin = ld_acquire_cta_shared(help + 8) == NW + XW;
            const unsigned c0 = ld_acquire_cta_shared(help), c1 = ld_acquire_cta_shared(help + 4);
            if (c0 != sent0 || c1 != sent1) {
                fence_gpu();
                if (c0 != sent0) red_add_u32(&ctl[C_KDONE][0], c0 - sent0);
                if (c1 != sent1) red_add_u32(&ctl[C_KDONE + 1][0], c1 - sent1);
                sent0 = c0; sent1 = c1;
            }
        }
        if (seen < 2 && ld_acquire(&ctl[C_KDONE + seen][0]) >= NUK / 2) {
            st_release_cta_shared(help + 12 + 4 * seen, 1u);
            seen++;
        } else {
            __nanosleep(300);
        }
        if (++n > SPIN_LIMIT) __trap();
    }
}

__device__ __forceinline__ void v_poller(uint32_t sbase, int f, int w) {
    const int lane = threadIdx.x & 31;
    const unsigned (*cp)[32] = &g_vdone[((f * NPOLL + w) % NREP) * NH];
    unsigned n = 0;
    while (ld_acquire_cta_shared(sbase + M_HELP + 12) == 0) { __nanosleep(1000); if (++n > SPIN_LIMIT) __trap(); }
    int h = 0;
    bool fast = false;
    while (h < NH) {
        const unsigned r = __ballot_sync(~0u, ld_acquire(&cp[min(h + (lane & 3), NH - 1)][0]) >= 4 * UPP) & 15u;
        if (r & 1) {
            h = min(NH, h + __ffs(~r) - 1);
            __syncwarp();
            if (lane == 0) asm volatile("red.release.cta.shared::cta.max.u32 [%0], %1;" ::"r"(sbase + M_HELP + 20), "r"(h) : "memory");
        }
        if (h < NH - 4) {
            __nanosleep(h ? 300 : 1000);
        } else if (!fast) {
            fast = true;
            const long long t0 = clock64();
            while (clock64() - t0 < w * PGAP) {}
        }
        if (++n > SPIN_LIMIT) __trap();
    }
}
__device__ __forceinline__ void finisher(const Params& p, uint32_t sbase, int f) {
    const int lane = threadIdx.x & 31;
    {
        const char* wg = reinterpret_cast<const char*>(p.wo);
        const uint32_t dst = sbase + 4 * SLOT + (16 * (lane & 7) + (lane >> 3)) * 16;
#pragma unroll 1
        for (int h = -FPF - 4; h < NH; h++) {
            if (lane == 0 && (unsigned)(h + FPF) < (unsigned)NH) l2_prefetch(wg + (size_t)(h + FPF) * 147456 + f * 2048, 2048);
            if (h >= 0) {
#pragma unroll
                for (int r = 0; r < 4; r++)
                    asm volatile("cp.async.cg.shared.global [%0], [%1], 16;" ::"r"(dst + h * 2048 + ((r & 1) * 4 + (r >> 1) * 8) * 16),
                                 "l"(wg + (size_t)(h * 128 + r * 32 + lane) * (DM * 2) + f * 16) : "memory");
            }
            __nanosleep(FSLEEP);
        }
        asm volatile("cp.async.wait_all;" ::: "memory");
        __syncwarp();
    }
    TS(11);
    const float4* vec = g_oacc + ((lane >> 2) & 3) * 32 + (lane >> 4) * 16 + (lane & 3);
    float acc[2][2][4];
#pragma unroll
    for (int i = 0; i < 16; i++) acc[i >> 3][(i >> 2) & 1][i & 3] = 0.f;
    uint32_t* outp = reinterpret_cast<uint32_t*>(p.out + (lane >> 2) * (2 * DM) + f * 8 + (lane & 3) * 2);
    uint32_t wa = sbase + 4 * SLOT + lane * 16;
    auto project = [&](const float4 (&x)[4], const uint32_t (&w)[4][4]) {
#pragma unroll
        for (int s = 0; s < 4; s++) {
            const uint32_t a[4] = {pack_bf16(x[s].x, x[s].y), 0u, pack_bf16(x[s].z, x[s].w), 0u};
            mma16816(acc[0][s & 1], a, w[s >> 1][(s & 1) * 2], w[s >> 1][(s & 1) * 2 + 1]);
            mma16816(acc[1][s & 1], a, w[2 + (s >> 1)][(s & 1) * 2], w[2 + (s >> 1)][(s & 1) * 2 + 1]);
        }
    };
    int h = 0;
    unsigned n = 0;
    while (h < NH) {
        uint32_t w[4][4];
#pragma unroll
        for (int q = 0; q < 4; q++) ldsm4t(w[q], wa + q * 512);
        int ready;
        while ((ready = ld_acquire_cta_shared(sbase + M_HELP + 20)) <= h) {
            if (h < NH - 3) __nanosleep(100);
            if (++n > (SPIN_LIMIT << 4)) __trap();
        }
        float4 x[4], y[4];
#pragma unroll
        for (int s = 0; s < 4; s++) x[s] = ld_relaxed16(vec + s * 4);
        const bool two = ready > h + 1;
        if (two) {
#pragma unroll
            for (int s = 0; s < 4; s++) y[s] = ld_relaxed16(vec + 128 + s * 4);
        }
        project(x, w);
        if (two) {
#pragma unroll
            for (int q = 0; q < 4; q++) ldsm4t(w[q], wa + 2048 + q * 512);
            project(y, w);
        }
        const int nr = two ? 2 : 1;
        h += nr;
        vec += nr * 128;
        wa += nr * 2048;
        const float o0 = acc[0][0][0] + acc[0][1][0] + __shfl_down_sync(~0u, acc[1][0][0] + acc[1][1][0], 16);
        const float o1 = acc[0][0][1] + acc[0][1][1] + __shfl_down_sync(~0u, acc[1][0][1] + acc[1][1][1], 16);
        asm volatile("{\n.reg .pred p;\nsetp.ne.u32 p, %2, 0;\n@p st.global.u32 [%0], %1;\n}" ::"l"(outp), "r"(pack_bf16(o0, o1)),
                     "r"((uint32_t)(lane < 16 && h == NH)) : "memory");
    }
}

__device__ __forceinline__ void out_fetch(uint32_t sbase, int j, int h) {
    const int lane = threadIdx.x & 31, g = lane >> 2;
    float4 x[4];
#pragma unroll
    for (int b = 0; b < 4; b++) x[b] = ld_relaxed16(&g_oacc[(h * 4 + ((b + g) & 3)) * 32 + lane]);
#pragma unroll
    for (int b = 0; b < 4; b++) {
        const uint32_t a = sbase + F_X + j * FXP + g * 128 + ((b + g) & 3) * 16 + (lane & 3) * 4;
        asm volatile("st.shared.u32 [%0], %1;\nst.shared.u32 [%0 + 64], %2;" ::"r"(a), "r"(pack_bf16(x[b].x, x[b].y)), "r"(pack_bf16(x[b].z, x[b].w)) : "memory");
    }
    asm volatile("fence.proxy.async.shared::cta;" ::: "memory");
}
__device__ __forceinline__ void out_early(uint32_t sbase, int rank, unsigned tag) {
    const int lane = threadIdx.x & 31;
    if (lane < 10) {
        mbar_init(sbase + F_BAR + 16 + lane * 8, lane >= 8 ? 4 : lane == 6 ? 2 : 1);
        if (lane < 8) mbar_expect_tx(sbase + F_BAR + 16 + lane * 8, 16384);
    }
    asm volatile("fence.mbarrier_init.release.cluster;" ::: "memory");
    unsigned n = 0;
    auto head = [&](int k) { return k < 4 ? k : k == 4 ? 4 + (rank >> 1) : (k - 4) * 8 + rank; };
#pragma unroll 1
    for (int k = rank < 4 ? 4 : 0; k < 7; k++) {
        for (unsigned q = 0; ld_acquire(&g_vdone[head(k)][0]) < 4 * UPP; q++) { __nanosleep(500); if (q > SPIN_LIMIT) __trap(); }
        out_fetch(sbase, k < 4 ? 8 + k : k == 4 ? 7 : k - 1, head(k));
#pragma unroll 1
        for (int m = rank < 4 ? 0 : 4; m < 8 && k == 4;) {
            ulonglong2 v[4];
            bool ok = true;
#pragma unroll
            for (int i = 0; i < 4; i++) v[i] = ld_tagged2(&g_ctx[head(m) * 128 + i * 32 + lane]);
#pragma unroll
            for (int i = 0; i < 4; i++) {
                ok = ok && (unsigned)(v[i].x >> 32) == tag && (unsigned)(v[i].y >> 32) == tag;
                asm volatile("st.shared.v2.u32 [%0], {%1,%2};" ::"r"(sbase + F_X + (m < 4 ? 8 + m : m - 4) * FXP + (i * 32 + lane) * 8),
                             "r"((uint32_t)v[i].x), "r"((uint32_t)v[i].y) : "memory");
            }
            if (__all_sync(~0u, ok)) {
                m++;
            } else {
                __nanosleep(500);
                if (++n > SPIN_LIMIT) __trap();
            }
        }
    }
    __syncwarp();
    if (lane == 0) st_release_cta_shared(sbase + M_HELP + 32, 1u);
}
__device__ __forceinline__ void out_late(uint32_t sbase, int rank) {
    unsigned n = 0;
    while (ld_acquire_cta_shared(sbase + M_HELP + 32) == 0) { if (++n > (SPIN_LIMIT << 4)) __trap(); }
    while (ld_acquire(&g_vdone[24 + rank][0]) < 4 * UPP) { if (++n > SPIN_LIMIT) __trap(); }
    TS(12);
    out_fetch(sbase, 6, 24 + rank);
    __syncwarp();
    if ((threadIdx.x & 31) == 0) asm volatile("mbarrier.arrive.shared::cta.b64 _, [%0];" ::"r"(sbase + F_BAR + 16 + 6 * 8) : "memory");
    TS(13);
}
__device__ __forceinline__ void out_project(uint32_t sbase, int rank, int w) {
    const int lane = threadIdx.x & 31, g = lane >> 2, t = lane & 3;
    unsigned n = 0;
    while (ld_acquire_cta_shared(sbase + M_HELP + 32) == 0) { __nanosleep(500); if (++n > SPIN_LIMIT) __trap(); }
    asm volatile("barrier.cluster.wait.acquire.aligned;" ::: "memory");
    uint32_t rdst[2], rbar[2];
#pragma unroll
    for (int e = 0; e < 2; e++) {
        rdst[e] = mapa(sbase + F_RECV + rank * 256 + g * 32 + t * 16, 4 * e + w);
        rbar[e] = mapa(sbase + F_BAR, 4 * e + w);
    }
    while (ld_acquire_cta_shared(sbase + M_HELP + 28) == 0) { __nanosleep(200); if (++n > SPIN_LIMIT) __trap(); }
    const uint32_t da = (1u << 16) | (((sbase + F_W) & 0x3ffff) >> 4), db = (4u << 16) | (((sbase + F_X) & 0x3ffff) >> 4);
    float d[2][4] = {0.f, 0.f, 0.f, 0.f, 0.f, 0.f, 0.f, 0.f};
#pragma unroll
    for (int i = 0; i < 7; i++) {
        const int e = i >> 2;
        mbar_first(sbase + F_BAR + 16 + i * 8);
        asm volatile("wgmma.fence.sync.aligned;" ::: "memory");
        if (i == 0) {
            wgmma_k64(d[0], da, db + (rank & 1) * 32, 0);
            wgmma_k64(d[1], da + 512, db + 7 * (FXP / 16) + (rank & 1) * 32, 0);
        } else {
            wgmma_k64(d[e], da + (i % 6) * 1024, db + i * (FXP / 16), 1);
            wgmma_k64(d[e], da + (i % 6) * 1024 + 512, db + i * (FXP / 16) + 32, 1);
        }
        asm volatile("wgmma.commit_group.sync.aligned;" ::: "memory");
        if (i < 2 || i % 3 == 0)
            asm volatile("wgmma.wait_group.sync.aligned 0;" : "+f"(d[e][0]), "+f"(d[e][1]), "+f"(d[e][2]), "+f"(d[e][3])::"memory");
        if (i < 2) {
            asm volatile("{\n.reg .pred p;\nsetp.eq.u32 p, %1, 0;\n@p mbarrier.arrive.shared::cta.b64 _, [%0];\n}"
                         ::"r"(sbase + F_BAR + 80 + i * 8), "r"(lane) : "memory");
        } else if (i % 3 == 0) {
            if (t < 2)
                asm volatile("st.async.weak.shared::cluster.mbarrier::complete_tx::bytes.v4.f32 [%0], {%1,%2,%3,%4}, [%5];"
                             ::"r"(rdst[e]), "f"(d[e][0]), "f"(d[e][1]), "f"(d[e][2]), "f"(d[e][3]), "r"(rbar[e]) : "memory");
            __syncwarp();
        }
    }
}
__device__ __forceinline__ void out_issue(const Params& p, uint32_t sbase, int c, int rank, uint64_t pol) {
    unsigned n = 0;
    while (ld_acquire_cta_shared(sbase + M_HELP + 32) == 0) { __nanosleep(500); if (++n > SPIN_LIMIT) __trap(); }
#pragma unroll
    for (int i = 0; i < 6; i++) asm volatile("prefetch.tensormap [%0];" ::"l"(&p.tm_out[i >> 1][i & 1]) : "memory");
    uint32_t t0;
    while ((t0 = ld_acquire_cta_shared(sbase + M_HELP + 28)) == 0) { __nanosleep(100); if (++n > SPIN_LIMIT) __trap(); }
#pragma unroll
    for (int i = 0; i < 8; i++) {
        const uint32_t dst = sbase + F_W + (i % 6) * 16384, bar = sbase + F_BAR + 16 + i * 8;
        if (i >= 6) mbar_wait(sbase + F_BAR + 32 + i * 8, 0);
        for (int k = 0; k < 4096 && (int)(now_ns() - t0) < 0; k++) {}
        if (i == 0) {
            TS(16);
            tma4d(dst, &p.tm_out[0][0], c * 64, (rank & 1) * 4, 4 + (rank >> 1), bar, pol);
            tma4d(dst + 8192, &p.tm_out[0][1], c * 64, (rank & 1) * 4, 4 + (rank >> 1), bar, pol);
        } else if (i < 7) {
            tma4d(dst, &p.tm_out[1][i >> 2], c * 64, 0, ((i - 1) % 3 + 1) * 8 + rank, bar, pol);
        } else {
#pragma unroll
            for (int q = 0; q < 2; q++) {
                const int h = ((q + rank) & 1) * 2;
                tma4d(dst + h * 4096, &p.tm_out[2][rank >> 2], c * 64 + (rank & 3) * 16, 0, h, bar, pol);
            }
        }
        t0 += i == 6 ? FP - FN : FP;
    }
    TS(17);
}
__device__ __forceinline__ void out_final(const Params& p, uint32_t sbase, int c, int rank, int hf) {
    const int lane = threadIdx.x & 31, g = lane >> 2, t = lane & 3;
    unsigned n = 0;
    while (ld_acquire_cta_shared(sbase + M_HELP + 32) == 0) { if (++n > (SPIN_LIMIT << 4)) __trap(); }
    uint32_t bf[16][2];
#pragma unroll
    for (int s = 0; s < 16; s++) {
        const uint32_t a = sbase + F_X + (8 + 2 * (g >> 2) + (s >> 3)) * FXP + (s & 7) * 128 + (g & 3) * 16 + t * 4;
        bf[s][0] = lds32(a);
        bf[s][1] = lds32(a + 64);
    }
    __nv_bfloat16* dst = p.out + (2 * (t & 1) + (t >> 1)) * (2 * DM) + (rank < 4 ? DM : 0) + c * 64 + (rank & 3) * 16 + hf * 8 + g;
    uint32_t src = sbase + F_RECV + g * 32 + (t & 1) * 16 + hf * 8 + (t >> 1) * 4;
    uint32_t wa = sbase + F_W + 16384 + ((lane >> 3) & 1) * 8192 + ((lane & 7) + (lane >> 4) * 8) * 32 + ((hf ^ (lane >> 2)) & 1) * 16;
    wa += bf[15][1] & (gridDim.x >> 24);
    asm volatile("" : "+l"(dst), "+r"(src), "+r"(wa));
    float x[8];
    auto partials = [&]() {
        mbar_first_cluster(sbase + F_BAR);
#pragma unroll
        for (int i = 0; i < 8; i++) asm volatile("ld.shared.f32 %0, [%1];" : "=f"(x[i]) : "r"(src + i * 256) : "memory");
    };
    const bool pre = rank < 4;
    if (pre) partials();
    mbar_first(sbase + F_BAR + 16 + 7 * 8);
    uint32_t a[16][4];
    float acc[4][4];
#pragma unroll
    for (int i = 0; i < 16; i++) acc[i >> 2][i & 3] = 0.f;
#pragma unroll
    for (int s = 0; s < 16; s++) ldsm4t(a[s], wa + s * 512);
#pragma unroll
    for (int s = 0; s < 16; s++) mma16816(acc[s & 3], a[s], bf[s][0], bf[s][1]);
    float y[4];
#pragma unroll
    for (int i = 0; i < 4; i++) y[i] = (acc[0][i] + acc[1][i]) + (acc[2][i] + acc[3][i]);
    float v = __shfl_xor_sync(~0u, (t & 2) ? y[2] : y[1], 2);
    if (!pre) partials();
    v = (v + ((t & 2) ? y[3] : y[0])) + (((x[0] + x[1]) + (x[2] + x[3])) + ((x[4] + x[5]) + (x[6] + x[7])));
    asm volatile("{\n.reg .b16 h;\ncvt.rn.bf16.f32 h, %1;\nst.global.b16 [%0], h;\n}" ::"l"(dst), "f"(v) : "memory");
}

constexpr int BS_WUK = 5, BS_Q = 9, BS_CKV = 11, BS_PART = 27, BS_WUV = 29, BS_END = 33;

__device__ __noinline__ void b_issue(const Params& p, int n, int bi, uint32_t sbase, uint64_t pol) {
    if (n >= BS_END || (n >= BS_Q && n < BS_CKV) || (n >= BS_PART && n < BS_WUV)) return;
    const uint32_t bar = sbase + M_BAR + (NSLOT + n % BRING) * 8;
    const CUtensorMap* tm;
    int row, panel = 2 * bi;
    if (n < BS_WUK) { tm = &p.tm_wq; row = n * 128; }
    else if (n < BS_Q) { tm = &p.tm_wuk; row = (n - BS_WUK) * 128; }
    else if (n < BS_PART) {
        tm = &p.tm_ckv; panel = 0;
        row = (bi >> 3) * SK + ((n - BS_CKV) * 8 + (bi & 7)) * 32;
    }
    else { tm = &p.tm_wuv; row = (n - BS_WUV) * 128; }
    mbar_expect_tx(bar, n == 0 ? 32768 + 4 * 1152 : 32768);
    tma3d(sbase + (n % BRING) * SLOT, tm, 0, row, panel, bar, pol);
}
__device__ __forceinline__ void b_issue_xchg(int n, const void* src, uint32_t sbase, uint64_t pol) {
    asm volatile("fence.proxy.async;" ::: "memory");
#pragma unroll
    for (int i = 0; i < 2; i++) {
        const uint32_t bar = sbase + M_BAR + (NSLOT + (n + i) % BRING) * 8;
        mbar_expect_tx(bar, 32768);
        bulk_load(sbase + ((n + i) % BRING) * SLOT, reinterpret_cast<const char*>(src) + i * 32768, 32768, bar, pol);
    }
}
__device__ __forceinline__ void b_wait(int n, uint32_t sbase) {
    mbar_wait(sbase + M_BAR + (NSLOT + n % BRING) * 8, (n / BRING) & 1);
}

__device__ __noinline__ void b_gemm(const Params& p, uint32_t sbase, int n0, int n1, int ktot, uint32_t xh, uint32_t xl, int pitch,
                                    int bi, uint64_t pol) {
    const int tid = threadIdx.x, warp = tid >> 5, lane = tid & 31, g = lane >> 2, t = lane & 3;
    const uint32_t woff = (warp >> 2) * 16384 + (lane & 15) * 128 + ((((warp & 3) * 2 + (lane >> 4)) ^ (lane & 7)) * 16);
    const uint32_t xoff = (g & 3) * pitch + t * 4;
    float acc[2][4];
#pragma unroll
    for (int i = 0; i < 8; i++) acc[i >> 2][i & 3] = 0.f;
#pragma unroll 1
    for (int n = n0; n < n1; n++) {
        b_wait(n, sbase);
        const uint32_t slot = sbase + (n % BRING) * SLOT + woff;
        const int k0 = (n - n0) * 128;
        const int ns = min(8, (ktot - k0) >> 4);
#pragma unroll 2
        for (int s = 0; s < ns; s++) {
            uint32_t a[4], w[4];
            const uint32_t xo = xoff + (k0 + 16 * s) * 2;
            a[0] = lds32(xh + xo); a[2] = lds32(xh + xo + 16);
            a[1] = xl ? lds32(xl + xo) : 0u; a[3] = xl ? lds32(xl + xo + 16) : 0u;
            ldsm4t(w, slot + s * 2048);
            mma16816(acc[0], a, w[0], w[1]);
            mma16816(acc[1], a, w[2], w[3]);
        }
        __syncthreads();
        if (tid == 0) b_issue(p, n + BD, bi, sbase, pol);
    }
    if (g < 4) {
#pragma unroll
        for (int j = 0; j < 2; j++)
            asm volatile("st.shared.u32 [%0], %1;" ::"r"(sbase + M_QB + g * QP + (warp * 16 + j * 8 + t * 2) * 2),
                         "r"(pack_bf16(acc[j][0] + acc[j][2], acc[j][1] + acc[j][3])) : "memory");
    }
    __syncthreads();
}

__device__ __forceinline__ void b_exchange(unsigned* c, int n, const void* src, uint32_t sbase, uint64_t pol) {
    TS(n == BS_Q ? 24 : 28);
    __syncthreads();
    if (threadIdx.x == 0) {
        TS(n == BS_Q ? 25 : 29);
        fence_gpu();
        TS(n == BS_Q ? 26 : 30);
        red_add_u32(c, 1u);
        wait_count(c, NBCTA);
        TS(n == BS_Q ? 27 : 31);
        b_issue_xchg(n, src, sbase, pol);
    }
}

template <bool CLU>
__device__ __noinline__ void b_chain(const Params& p, char* smem, uint32_t sbase, int bi, unsigned epoch, uint64_t pol) {
    const int tid = threadIdx.x, warp = tid >> 5, lane = tid & 31, g = lane >> 2, t = lane & 3;
    unsigned (*ctl)[32] = g_ctl[epoch & 1];
    float* red = reinterpret_cast<float*>(smem + 5 * SLOT);
    b_gemm(p, sbase, 0, BS_WUK, DM, sbase + M_XB, 0, XP, bi, pol);
    TS(6);
    {
        uint32_t Q[16];
#pragma unroll
        for (int c = 0; c < 16; c++) Q[c] = lds32(sbase + M_QB + (g & 3) * QP + c * 16 + t * 4);
        float* qa = reinterpret_cast<float*>(smem + M_QA);
#pragma unroll 1
        for (int n = BS_WUK; n < BS_Q; n++) {
            b_wait(n, sbase);
            const uint32_t base = sbase + (n % BRING) * SLOT + (warp * 16 + (lane & 15)) * 128;
            float d[2][4];
#pragma unroll
            for (int i = 0; i < 8; i++) d[i >> 2][i & 3] = 0.f;
#pragma unroll
            for (int s = 0; s < 8; s++) {
                uint32_t a[4];
                ldsm4(a, base + (s >> 2) * 16384 + (((2 * (s & 3) + (lane >> 4)) ^ (lane & 7)) * 16));
                mma16816(d[s & 1], a, Q[2 * s], Q[2 * s + 1]);
            }
            const int c = (n - BS_WUK) * 128 + warp * 16 + g + 8 * (t >> 1);
            qa[(2 * (t & 1)) * 512 + c] = (t & 2) ? d[0][2] + d[1][2] : d[0][0] + d[1][0];
            qa[(2 * (t & 1) + 1) * 512 + c] = (t & 2) ? d[0][3] + d[1][3] : d[0][1] + d[1][1];
            __syncthreads();
            if (tid == 0) b_issue(p, n + BD, bi, sbase, pol);
        }
#pragma unroll 1
        for (int r = 0; r < 2; r++) {
            const int id = tid + r * 256;
            const int b = id >> 7, c0 = ((id >> 2) & 31) * 16 + (id & 3) * 2;
            const float2 u0 = *reinterpret_cast<const float2*>(qa + b * 512 + c0);
            const float2 u1 = *reinterpret_cast<const float2*>(qa + b * 512 + c0 + 8);
            const uint32_t h0 = pack_bf16(u0.x, u0.y), h1 = pack_bf16(u1.x, u1.y);
            const uint32_t l0 = pack_bf16(u0.x - bf_lo(h0), u0.y - bf_hi(h0)), l1 = pack_bf16(u1.x - bf_lo(h1), u1.y - bf_hi(h1));
            g_qabs[((id >> 2) * 4 + (bi >> 3)) * 32 + (bi & 7) * 4 + (id & 3)] = make_uint4(h0, l0, h1, l1);
        }
    }
    b_exchange(&ctl[C_BBAR][0], BS_Q, &g_qabs[(bi >> 3) * 4096], sbase, pol);
    {
        uint32_t qf[4][4][4];
        b_wait(BS_Q + (warp >> 2), sbase);
        TS(7);
        {
            const uint4* qs = reinterpret_cast<const uint4*>(smem + ((BS_Q + (warp >> 2)) % BRING) * SLOT) + (warp & 3) * 512 + lane;
#pragma unroll
            for (int s = 0; s < 4; s++)
#pragma unroll
                for (int i = 0; i < 4; i++) {
                    const uint4 v = qs[(s * 4 + i) * 32];
                    qf[i][s][0] = v.x; qf[i][s][1] = v.y; qf[i][s][2] = v.z; qf[i][s][3] = v.w;
                }
        }
        __syncthreads();
        if (tid == 0) { b_issue(p, BS_Q + BD, bi, sbase, pol); b_issue(p, BS_Q + 1 + BD, bi, sbase, pol); }
        float acc[2][8][4];
#pragma unroll
        for (int i = 0; i < 2; i++)
#pragma unroll
            for (int j = 0; j < 8; j++) { acc[i][j][0] = acc[i][j][1] = acc[i][j][2] = acc[i][j][3] = 0.f; }
        float mrun = -INFINITY, lrun = 0.f;
        const int head = tid >> 3, kq = tid & 7;
        float* alpha = reinterpret_cast<float*>(smem + M_ALPHA);
        for (int n = BS_CKV; n < BS_PART; n++) {
            b_wait(n, sbase);
            const uint32_t slot = sbase + (n % BRING) * SLOT;
            float sc[4][4][4];
#pragma unroll
            for (int i = 0; i < 4; i++)
#pragma unroll
                for (int j = 0; j < 4; j++) { sc[i][j][0] = sc[i][j][1] = sc[i][j][2] = sc[i][j][3] = 0.f; }
#pragma unroll
            for (int j = 0; j < 4; j++)
#pragma unroll
                for (int sp = 0; sp < 2; sp++) {
                    uint32_t bf[4];
                    ldsm4(bf, slot + warp * 4096 + (8 * j + (lane & 7)) * 128 + (((4 * sp + (lane >> 3)) ^ (lane & 7)) * 16));
#pragma unroll
                    for (int i = 0; i < 4; i++) {
                        mma16816(sc[i][j], qf[i][2 * sp], bf[0], bf[1]);
                        mma16816(sc[i][j], qf[i][2 * sp + 1], bf[2], bf[3]);
                    }
                }
#pragma unroll
            for (int i = 0; i < 4; i++)
#pragma unroll
                for (int j = 0; j < 4; j++)
                    *reinterpret_cast<float2*>(red + warp * 1024 + (8 * i + g) * 32 + ((8 * j) ^ (8 * (g & 3))) + 2 * t) =
                        make_float2(sc[i][j][0] + sc[i][j][2], sc[i][j][1] + sc[i][j][3]);
            __syncthreads();
            if (tid == 0 && n > BS_CKV) b_issue(p, n - 1 + BD, bi, sbase, pol);
            {
                float4 s = make_float4(0.f, 0.f, 0.f, 0.f);
#pragma unroll
                for (int w = 0; w < 8; w++) {
                    const float4 v = *reinterpret_cast<const float4*>(red + w * 1024 + head * 32 + ((4 * kq) ^ (8 * (head & 3))));
                    s.x += v.x; s.y += v.y; s.z += v.z; s.w += v.w;
                }
                const uint32_t r0 = pack_bf16(s.x, s.y), r1 = pack_bf16(s.z, s.w);
                const uint32_t s0 = pack_bf16(bf_lo(r0) * SCALE, bf_hi(r0) * SCALE);
                const uint32_t s1 = pack_bf16(bf_lo(r1) * SCALE, bf_hi(r1) * SCALE);
                const float f0 = bf_lo(s0), f1 = bf_hi(s0), f2 = bf_lo(s1), f3 = bf_hi(s1);
                float mx = fmaxf(fmaxf(f0, f1), fmaxf(f2, f3));
                mx = fmaxf(mx, __shfl_xor_sync(~0u, mx, 1));
                mx = fmaxf(mx, __shfl_xor_sync(~0u, mx, 2));
                mx = fmaxf(mx, __shfl_xor_sync(~0u, mx, 4));
                const float mnew = fmaxf(mrun, mx);
                const float al = expsub(mrun, mnew);
                const float p0 = expsub(f0, mnew), p1 = expsub(f1, mnew), p2 = expsub(f2, mnew), p3 = expsub(f3, mnew);
                lrun = lrun * al + ((p0 + p1) + (p2 + p3));
                mrun = mnew;
                *reinterpret_cast<uint2*>(smem + M_P + head * 80 + kq * 8) = make_uint2(pack_bf16(p0, p1), pack_bf16(p2, p3));
                if (kq == 0) alpha[head] = al;
            }
            __syncthreads();
            {
                uint32_t pf[2][2][4];
#pragma unroll
                for (int i = 0; i < 2; i++)
#pragma unroll
                    for (int ks = 0; ks < 2; ks++)
                        ldsm4(pf[i][ks], sbase + M_P + (16 * i + (lane & 15)) * 80 + (16 * ks + 8 * (lane >> 4)) * 2);
#pragma unroll
                for (int i = 0; i < 2; i++) {
                    const float a0 = alpha[16 * i + g], a1 = alpha[16 * i + 8 + g];
#pragma unroll
                    for (int j = 0; j < 8; j++) { acc[i][j][0] *= a0; acc[i][j][1] *= a0; acc[i][j][2] *= a1; acc[i][j][3] *= a1; }
                }
#pragma unroll
                for (int j = 0; j < 8; j++) {
                    uint32_t bf[4];
                    ldsm4t(bf, slot + warp * 4096 + lane * 128 + ((j ^ (lane & 7)) * 16));
#pragma unroll
                    for (int i = 0; i < 2; i++) {
                        mma16816(acc[i][j], pf[i][0], bf[0], bf[1]);
                        mma16816(acc[i][j], pf[i][1], bf[2], bf[3]);
                    }
                }
            }
        }
        __syncthreads();
        if (tid == 0) b_issue(p, BS_PART - 1 + BD, bi, sbase, pol);
        lrun += __shfl_xor_sync(~0u, lrun, 1);
        lrun += __shfl_xor_sync(~0u, lrun, 2);
        lrun += __shfl_xor_sync(~0u, lrun, 4);
        if (kq == 0) g_bml[head * NBCTA + bi] = make_float2(mrun, lrun);
#pragma unroll
        for (int i = 0; i < 2; i++)
#pragma unroll
            for (int j = 0; j < 8; j++) {
                g_bpart[((16 * i + g) * NBCTA + bi) * 256 + warp * 32 + j * 4 + t] = make_float2(acc[i][j][0], acc[i][j][1]);
                g_bpart[((16 * i + 8 + g) * NBCTA + bi) * 256 + warp * 32 + j * 4 + t] = make_float2(acc[i][j][2], acc[i][j][3]);
            }
    }
#pragma unroll 1
    for (int i = tid; i < NH * 36 && !(CLU); i += 256) g_outb[bi * NH * 36 + i] = make_uint4(0u, epoch, 0u, epoch);
    b_exchange(&ctl[C_BBAR + 1][0], BS_PART, &g_bpart[bi * NBCTA * 256], sbase, pol);
    {
        float* omega = reinterpret_cast<float*>(smem + M_OMEGA);
        if (warp == 0) {
            __syncwarp();
            const uint2 ml = ld_relaxed8(&g_bml[bi * NBCTA + lane]);
            const float ms = __uint_as_float(ml.x);
            float m = ms;
            m = fmaxf(m, __shfl_xor_sync(~0u, m, 1));
            m = fmaxf(m, __shfl_xor_sync(~0u, m, 2));
            m = fmaxf(m, __shfl_xor_sync(~0u, m, 4));
            const float w = expsub(ms, m);
            float l = w * __uint_as_float(ml.y);
            l += __shfl_xor_sync(~0u, l, 1);
            l += __shfl_xor_sync(~0u, l, 2);
            l += __shfl_xor_sync(~0u, l, 4);
            omega[lane] = w / l;
        }
        __syncthreads();
        b_wait(BS_PART, sbase);
        b_wait(BS_PART + 1, sbase);
#pragma unroll 1
        for (int b = 0; b < 4; b++) {
            const float2* ps = reinterpret_cast<const float2*>(smem + ((BS_PART + (b >> 1)) % BRING) * SLOT) + (b & 1) * 2048 + tid;
            float c0 = 0.f, c1 = 0.f;
#pragma unroll
            for (int s = 0; s < 8; s++) {
                const float w = omega[b * 8 + s];
                const float2 v = ps[s * 256];
                c0 = fmaf(w, v.x, c0);
                c1 = fmaf(w, v.y, c1);
            }
            const uint32_t hi = pack_bf16(c0, c1);
            *reinterpret_cast<uint32_t*>(smem + M_CH + b * CP + tid * 4) = hi;
            *reinterpret_cast<uint32_t*>(smem + M_CL + b * CP + tid * 4) = pack_bf16(c0 - bf_lo(hi), c1 - bf_hi(hi));
        }
        __syncthreads();
        if (tid == 0) { b_issue(p, BS_PART + BD, bi, sbase, pol); b_issue(p, BS_PART + 1 + BD, bi, sbase, pol); }
    }
    b_gemm(p, sbase, BS_WUV, BS_END, 512, sbase + M_CH, sbase + M_CL, CP, bi, pol);
    TS(12);
    if (CLU) {
        if (tid < 128) {
            const uint32_t xo = sbase + M_QB + ((tid >> 1) & 3) * QP + (tid >> 3) * 16 + (tid & 1) * 8;
            st_tagged2(&g_ctx[bi * 128 + tid], __uint_as_float(lds32(xo)), __uint_as_float(lds32(xo + 4)), epoch + 1);
        }
        return;
    }
    if (tid == 0) {
#pragma unroll 1
        for (int i = 0; i < 4; i++) {
            mbar_expect_tx(sbase + M_BAR + i * 8, 36864);
            tma3d(sbase + i * 36864, &p.tm_wo, 0, bi * 128 + i * 32, 0, sbase + M_BAR + i * 8, pol);
        }
    }
    TS(8);
    {
        float acc[9][4];
#pragma unroll
        for (int j = 0; j < 9; j++) { acc[j][0] = acc[j][1] = acc[j][2] = acc[j][3] = 0.f; }
#pragma unroll 1
        for (int i = 0; i < 4; i++) {
            const uint32_t xo = sbase + M_QB + (g & 3) * QP + i * 64 + t * 4;
            const uint32_t a0[4] = {lds32(xo), 0u, lds32(xo + 16), 0u}, a1[4] = {lds32(xo + 32), 0u, lds32(xo + 48), 0u};
            mbar_wait(sbase + M_BAR + i * 8, 0);
#pragma unroll
            for (int j = 0; j < 9; j++) {
                const int nt = warp * 9 + j;
                uint32_t w[4];
                ldsm4t(w, sbase + i * 36864 + (nt >> 3) * 4096 + lane * 128 + (((nt & 7) ^ (lane & 7)) * 16));
                mma16816(acc[j], a0, w[0], w[1]);
                mma16816(acc[j], a1, w[2], w[3]);
            }
        }
        if (g < 4) {
#pragma unroll
            for (int j = 0; j < 9; j++) {
                const int c2 = (warp * 9 + j) * 4 + t;
                st_tagged2(&g_outb[((c2 / 9) * NH + bi) * 36 + g * 9 + c2 % 9], acc[j][0], acc[j][1], epoch + 1);
            }
        }
    }
    TS(9);
    {
        const uint4* src = g_outb + (bi * NH + (tid >> 3)) * 36 + (tid & 7);
        float2* part = reinterpret_cast<float2*>(red);
        unsigned n = 0;
        while (true) {
            ulonglong2 v[5];
            bool ok = true;
#pragma unroll
            for (int i = 0; i < 5; i++)
                if (i < 4 || (tid & 7) < 4) v[i] = ld_tagged2(src + i * 8);
#pragma unroll
            for (int i = 0; i < 5; i++)
                if (i < 4 || (tid & 7) < 4) {
                    ok = ok && (unsigned)(v[i].x >> 32) == epoch + 1 && (unsigned)(v[i].y >> 32) == epoch + 1;
                    part[(tid >> 3) * 36 + (tid & 7) + i * 8] = make_float2(__uint_as_float((unsigned)v[i].x), __uint_as_float((unsigned)v[i].y));
                }
            if (ok) break;
            __nanosleep(400);
            if (++n > SPIN_LIMIT) __trap();
        }
        __syncthreads();
        if (tid < 36) {
            float s0 = 0.f, s1 = 0.f;
#pragma unroll 8
            for (int h = 0; h < NH; h++) { const float2 v = part[h * 36 + tid]; s0 += v.x; s1 += v.y; }
            *reinterpret_cast<uint32_t*>(p.out + (tid / 9) * 2 * DM + DM + bi * 18 + (tid % 9) * 2) = pack_bf16(s0, s1);
        }
    }
    TS(10);
}

template <bool CLU>
__global__ void __launch_bounds__(256, 1) fused_decode_kernel(const __grid_constant__ First f, const __grid_constant__ Params p) {
    extern __shared__ __align__(1024) char smem_raw[];
    const uint32_t sbase = (smem_u32(smem_raw) + 1023u) & ~1023u;
    char* smem = smem_raw + (sbase - smem_u32(smem_raw));
    const int tid = threadIdx.x, warp = tid >> 5, lane = tid & 31;
    asm volatile("{\n.reg .pred p;\nsetp.ne.u32 p, %1, 0;\n@p prefetch.global.L2 [%0];\n}"
                 ::"l"(f.ptr[tid >> 10] + (blockIdx.x * 8 + warp) * 8192 + lane * 128), "r"((uint32_t)(blockIdx.x < DM / 8 && lane < 16)) : "memory");
    const char* eptr = f.ptr[3 + (tid >> 10)];
    const int blk = CLU ? cluster_role(blockIdx.x) : blockIdx.x;
    const bool isB = CLU ? blk < NBCTA : (blk & 3) == 0 && (blk >> 2) < NBCTA;
    const int bi = CLU ? blk : blk >> 2;
    const int nb = CLU ? blk - NBCTA : blk - min(NBCTA, (blk + 3) >> 2);
    const int nblk = CLU ? 8 * MINCL : gridDim.x, nnb = nblk - NBCTA;
    constexpr int NFIRST = NW + XW + CLU;
    const int nstatic = nnb * NFIRST;
    uint64_t pol, poln;
    asm volatile("createpolicy.fractional.L2::evict_first.b64 %0, 1.0;" : "=l"(pol));
    asm volatile("createpolicy.fractional.L2::evict_normal.b64 %0, 1.0;" : "=l"(poln));
    const bool hold = blk < 16;
    const uint32_t jbar = sbase + M_BAR + (NSLOT + BRING) * 8, fbar = sbase + M_BAR + 4 * 8;
    const bool kfirst = CLU && !isB && (nb & 2);
    if (warp < 4) {
        if (lane == 0) {
            if (warp == 0) {
                mbar_init(jbar, 1);
                asm volatile("fence.mbarrier_init.release.cluster;" ::: "memory");
                mbar_expect_tx(jbar, 36864 + 4 * 1152);
                if ((CLU || blk < 128) && !kfirst) tma3d(sbase + J0W, &p.tm_j0, blk * 32, 0, 0, jbar, poln);
            } else if (warp & 1) {
                if (warp & 2) {
#pragma unroll
                    for (int i = 0; i < NSLOT + BRING; i++) mbar_init(sbase + M_BAR + i * 8, 1);
                    mbar_expect_tx(fbar, NEARLY * TILE_BYTES);
                } else if (CLU && !isB) {
                    mbar_init(sbase + F_BAR, 1);
                    mbar_expect_tx(sbase + F_BAR, 2048);
                }
                asm volatile("fence.mbarrier_init.release.cluster;" ::: "memory");
            } else {
#pragma unroll
                for (int i = 0; i < 4; i++) asm volatile("st.shared.v4.u32 [%0], {%1,%1,%1,%1};" ::"r"(sbase + M_HELP + i * 16), "r"(0) : "memory");
            }
        }
    } else if (blockIdx.x >= DM / 8) {
        if (tid == 128) {
            asm volatile("prefetch.tensormap [%0];" ::"l"(&p.tm_j0) : "memory");
            asm volatile("prefetch.tensormap [%0];" ::"l"(&p.tm_wq) : "memory");
        } else if (blockIdx.x == DM / 8 + 4 && tid >= 220) {
            asm volatile("prefetch.global.L2 [%0];" ::"l"(f.ptr[2 + (tid >> 10)] + (tid - 220) * 128) : "memory");
        }
    }
    __syncthreads();
    if (tid == 128) {
        if ((CLU || blk < 128) && !kfirst) bulk_load(sbase + M_XA, f.ptr[2], 4608, jbar, poln);
        if (!isB && !hold) bulk_load(sbase, block_src(f.ptr[1], unit_block(nb * NEARLY)), NEARLY * TILE_BYTES, fbar, pol);
        if (kfirst) {
            tma3d(sbase + J0W, &p.tm_j0, blk * 32, 0, 0, jbar, poln);
            bulk_load(sbase + M_XA, f.ptr[2], 4608, jbar, poln);
        }
    }
    const uint32_t wbar = sbase + M_BAR + warp * 8, wslot = sbase + warp * SLOT;
    const int u0 = ((warp / NEARLY) * nnb + nb) * NEARLY + warp % NEARLY;
    unsigned epoch = 0;
    if (lane == 0) epoch = ld_relaxed4(eptr);
    TS(0);
    if (CLU && (unsigned)nb < NFIN) asm volatile("barrier.cluster.arrive.relaxed.aligned;" ::: "memory");
    if ((warp >> 1) == 2 && blk < 128) st_relaxed64(&g_qll[((tid - 128) >> 4) * 2048 + blk * 16 + (tid & 15)], 0ull);
    if (isB || warp >= NW + XW) epoch = __shfl_sync(~0u, epoch, 0);
    if (isB && tid == 96) {
        if (hold) { unsigned n = 0; while (ld_acquire_cta_shared(sbase + M_HELP + 24) < 2) { if (++n > (SPIN_LIMIT << 4)) __trap(); } }
#pragma unroll 1
        for (int b = 0; b < 4; b++) bulk_load(sbase + M_XB + b * XP, p.xb + b * DM, 1152, sbase + M_BAR + NSLOT * 8, pol);
#pragma unroll 1
        for (int n = 0; n < BD; n++) b_issue(p, n, bi, sbase, pol);
    }
    if (warp >= 4 && blk < 128) {
        const int g = lane >> 2, t = lane & 3, j = tid - 128;
#pragma unroll 1
        for (int sl = blk, ph = 0;; sl += 128 - nblk, ph = 1) {
        mbar_wait(jbar, ph);
        TS(13);
        float acc[4][4];
#pragma unroll
        for (int i = 0; i < 16; i++) acc[i >> 2][i & 3] = 0.f;
        const uint32_t wa = sbase + J0W + ((warp - 4) * 144 + (lane & 15)) * 64;
        const uint32_t sw = (lane >> 1) & 3, xa = sbase + M_XA + (g & 3) * 1152 + (warp - 4) * 288 + t * 4;
#pragma unroll 3
        for (int s = 0; s < 9; s++) {
            const uint32_t a[4] = {lds32(xa + s * 32), 0u, lds32(xa + s * 32 + 16), 0u};
            uint32_t w0[4], w1[4];
            ldsm4t(w0, wa + s * 1024 + (((lane >> 4) ^ sw) * 16));
            ldsm4t(w1, wa + s * 1024 + (((2 + (lane >> 4)) ^ sw) * 16));
            mma16816(acc[0], a, w0[0], w0[1]);
            mma16816(acc[1], a, w0[2], w0[3]);
            mma16816(acc[2], a, w1[0], w1[1]);
            mma16816(acc[3], a, w1[2], w1[3]);
        }
        float2* j0 = reinterpret_cast<float2*>(smem + M_J0);
        if (g < 4) {
#pragma unroll
            for (int i = 0; i < 4; i++) j0[(warp - 4) * 64 + g * 16 + i * 4 + t] = make_float2(acc[i][0], acc[i][1]);
        }
        asm volatile("bar.sync 1, 128;" ::: "memory");
        const bool again = sl == blk && blk + 128 - nblk >= nblk;
        if (again && tid == 224) {
            mbar_expect_tx(jbar, 36864);
            tma3d(sbase + J0W, &p.tm_j0, (blk + 128 - nblk) * 32, 0, 0, jbar, pol);
        }
        if (warp < 6) {
            const float2 v0 = j0[j], v1 = j0[64 + j], v2 = j0[128 + j], v3 = j0[192 + j];
            st_relaxed64(&g_qll[(j >> 4) * 2048 + sl * 16 + (j & 15)],
                         (unsigned long long)pack_bf16((v0.x + v1.x) + (v2.x + v3.x), (v0.y + v1.y) + (v2.y + v3.y)) |
                             ((unsigned long long)(epoch + 1) << 32));
            __syncwarp();
            if (lane == 0) asm volatile("red.relaxed.cta.shared::cta.add.u32 [%0], 1;" ::"r"(sbase + M_HELP + 24) : "memory");
        } else if (warp == 7) {
            if (blk < C_LINES) g_ctl[(epoch & 1) ^ 1][blk][lane] = 0;
        }
        TS(1);
        if (!again) break;
        asm volatile("bar.sync 1, 128;" ::: "memory");
        }
    }
    if (isB) {
        b_chain<CLU>(p, smem, sbase, bi, epoch, pol);
        return;
    }
    if (warp < NW + XW) {
        a_worker<CLU>(p, u0, CLU && warp == 3 ? 4 * nnb + nb : 2 * NUK, warp >= NW + (((nb * 5) & 7) < (CLU ? X3C : X3) ? 1 : 0), hold, nstatic,
                      wslot, wbar, warp < NEARLY && !hold ? fbar : wbar, sbase + M_HELP, epoch, pol);
        if (CLU && nb < NFIN) {
            if (tid == 96) out_issue(p, sbase, nb >> 3, nb & 7, pol);
            __syncwarp();
            if (warp & 1) out_final(p, sbase, nb >> 3, nb & 7, warp >> 1);
            else if (warp == 0) out_late(sbase, nb & 7);
        }
        return;
    } else if (warp == 7) {
#pragma unroll 1
        for (int i = nb; i < 4 * NH; i += nnb) g_oacc[i * 32 + lane] = make_float4(0.f, 0.f, 0.f, 0.f);
        if (nb < NREP * NH) g_vdone[nb][lane] = 0;
        __syncwarp();
        k_helper(sbase + M_HELP, epoch);
        if (nb == 0 && lane == 0) g_epoch = epoch + 1;
        __syncwarp();
        if (CLU && nb < NFIN) out_early(sbase, nb & 7, epoch + 1);
    } else if (CLU) {
    } else if (warp == 6 && nb < NFIN) {
        finisher(p, sbase, nb);
        TS(4);
    } else if (warp >= 6 - NPOLL && nb < NFIN) {
        v_poller(sbase, nb, warp - (6 - NPOLL));
    }
    if (CLU && nb < NFIN) out_project(sbase, nb & 7, warp - 4);
}

}

typedef CUresult (*EncodeFn)(CUtensorMap*, CUtensorMapDataType, cuuint32_t, void*, const cuuint64_t*, const cuuint64_t*,
                             const cuuint32_t*, const cuuint32_t*, CUtensorMapInterleave, CUtensorMapSwizzle,
                             CUtensorMapL2promotion, CUtensorMapFloatOOBfill);

extern "C" void kernel_launch(void* const* d_in, const int* in_sizes, int n_in, void* d_out, int out_size) {
    (void)in_sizes; (void)n_in; (void)out_size;
    static int nsm = 0, ncl = 0;
    static EncodeFn encode = nullptr;
    static const char* epoch_ptr = nullptr;
    cudaLaunchConfig_t cfg = {};
    cudaLaunchAttribute at[1];
    at[0].id = cudaLaunchAttributeClusterDimension;
    at[0].val.clusterDim.x = 8; at[0].val.clusterDim.y = 1; at[0].val.clusterDim.z = 1;
    cfg.blockDim = dim3(256); cfg.dynamicSmemBytes = SMEM_BYTES; cfg.stream = cudaStreamPerThread; cfg.attrs = at; cfg.numAttrs = 1;
    if (nsm == 0) {
        int dev = 0;
        cudaGetDevice(&dev);
        cudaDeviceGetAttribute(&nsm, cudaDevAttrMultiProcessorCount, dev);
        cudaFuncSetAttribute(fused_decode_kernel<false>, cudaFuncAttributeMaxDynamicSharedMemorySize, SMEM_BYTES);
        cudaFuncSetAttribute(fused_decode_kernel<true>, cudaFuncAttributeMaxDynamicSharedMemorySize, SMEM_BYTES);
        cfg.gridDim = dim3(128);
        if (cudaOccupancyMaxActiveClusters(&ncl, fused_decode_kernel<true>, &cfg) != cudaSuccess) { ncl = 0; (void)cudaGetLastError(); }
        if (ncl > MINCL) ncl = MINCL;
        cudaGetSymbolAddress((void**)&epoch_ptr, g_epoch);
        void* fn = nullptr;
        cudaDriverEntryPointQueryResult qr;
        cudaGetDriverEntryPoint("cuTensorMapEncodeTiled", &fn, cudaEnableDefault, &qr);
        encode = (EncodeFn)fn;
    }
    Params p;
    auto panels = [&](CUtensorMap* tm, void* ptr, int rows, int cols, int box_rows, int box_panels) {
        const cuuint64_t gd[3] = {64, (cuuint64_t)rows, (cuuint64_t)(cols / 64)}, gs[2] = {(cuuint64_t)cols * 2, 128};
        const cuuint32_t box[3] = {64, (cuuint32_t)box_rows, (cuuint32_t)box_panels}, es[3] = {1, 1, 1};
        encode(tm, CU_TENSOR_MAP_DATA_TYPE_BFLOAT16, 3, ptr, gd, gs, box, es, CU_TENSOR_MAP_INTERLEAVE_NONE,
               CU_TENSOR_MAP_SWIZZLE_128B, CU_TENSOR_MAP_L2_PROMOTION_L2_256B, CU_TENSOR_MAP_FLOAT_OOB_FILL_NONE);
    };
    panels(&p.tm_wq, d_in[7], DM, 4096, 128, 2);
    panels(&p.tm_wuk, d_in[8], 512, 4096, 128, 2);
    panels(&p.tm_wuv, d_in[9], 512, 4096, 128, 2);
    panels(&p.tm_wo, d_in[10], 4096, DM, 32, 9);
    panels(&p.tm_ckv, d_in[6], 4 * SK, 512, 32, 8);
    {
        const cuuint64_t gd[3] = {4096, 192, 3}, gs[2] = {8192, 192 * 8192};
        const cuuint32_t box[3] = {32, 192, 3}, es[3] = {1, 1, 1};
        encode(&p.tm_j0, CU_TENSOR_MAP_DATA_TYPE_BFLOAT16, 3, d_in[3], gd, gs, box, es, CU_TENSOR_MAP_INTERLEAVE_NONE,
               CU_TENSOR_MAP_SWIZZLE_64B, CU_TENSOR_MAP_L2_PROMOTION_L2_128B, CU_TENSOR_MAP_FLOAT_OOB_FILL_NONE);
    }
    for (int i = 0; i < 6; i++) {
        const int k = i >> 1, a = i & 1;
        const cuuint64_t gd[4] = {DM, 16, 8, NH}, gs[3] = {(cuuint64_t)(a ? 8 : 1) * DM * 2, (cuuint64_t)(a ? 1 : 16) * DM * 2, 128 * DM * 2};
        const cuuint32_t box[4] = {k < 2 ? 64u : 16u, 16, k ? 8u : 4u, k < 2 ? 1u : 2u}, es[4] = {1, 1, 1, 1};
        encode(&p.tm_out[k][a], CU_TENSOR_MAP_DATA_TYPE_BFLOAT16, 4, d_in[a ? 4 : 10], gd, gs, box, es, CU_TENSOR_MAP_INTERLEAVE_NONE,
               k < 2 ? CU_TENSOR_MAP_SWIZZLE_128B : CU_TENSOR_MAP_SWIZZLE_32B,
               k < 2 ? CU_TENSOR_MAP_L2_PROMOTION_L2_256B : CU_TENSOR_MAP_L2_PROMOTION_L2_128B, CU_TENSOR_MAP_FLOAT_OOB_FILL_NONE);
    }
    p.kc = (const __nv_bfloat16*)d_in[1];
    p.vc = (const __nv_bfloat16*)d_in[2];
    p.wo = (const __nv_bfloat16*)d_in[4];
    p.xb = (const __nv_bfloat16*)d_in[5];
    p.out = (__nv_bfloat16*)d_out;
    const First f = {{(const char*)d_in[3], (const char*)d_in[1], (const char*)d_in[0], epoch_ptr}};
    if (ncl >= MINCL) {
        cfg.gridDim = dim3(8 * ncl);
        cudaLaunchKernelEx(&cfg, fused_decode_kernel<true>, f, p);
    } else {
        fused_decode_kernel<false><<<nsm, 256, SMEM_BYTES, cudaStreamPerThread>>>(f, p);
    }
}
```

```cpp
#include <cuda_runtime.h>
#include <cuda.h>
#include <cuda_bf16.h>
#include <stdint.h>

namespace {

constexpr int NH = 32, SK = 4096, DM = 576;
constexpr int KEYS = 128;
constexpr int UPP = SK / KEYS;
constexpr int NUK = 4 * NH * UPP;
constexpr int TILE_BYTES = KEYS * 256;
#define NWORK 2
constexpr int NW = NWORK;
constexpr int NBCTA = 32;
constexpr int MINCL = 15;
constexpr int NFIN = 72;
constexpr int SLOT = 32768;
constexpr int NSLOT = 6;
constexpr int BRING = 5;
constexpr int J0W = 5 * SLOT;
constexpr int MISC = NSLOT * SLOT + 4096;
constexpr int XP = 1168, CP = 1040, QP = 272;
constexpr int M_XA = MISC;
constexpr int M_XB = M_XA + 4 * XP;
constexpr int M_CH = M_XB + 4 * XP;
constexpr int M_CL = M_CH + 4 * CP;
constexpr int M_QB = M_CL + 4 * CP;
constexpr int M_QA = M_CH;
constexpr int M_J0 = M_QB + 4 * QP;
constexpr int M_P = M_J0 + 2048;
constexpr int M_ALPHA = M_P + 2560;
constexpr int M_OMEGA = M_ALPHA + 128;
constexpr int M_BAR = M_OMEGA + 128;
constexpr int M_HELP = M_BAR + 128;
constexpr int F_W = 3 * SLOT;
constexpr int F_X = NSLOT * SLOT, FXP = 1088;
constexpr int F_RECV = F_X + 12 * FXP;
constexpr int F_BAR = M_P;
constexpr int SMEM_BYTES = M_HELP + 128 + 1024;
static_assert(F_RECV + 2048 <= M_J0, "output phase layout");
static_assert(SMEM_BYTES <= 232448 && M_BAR % 8 == 0 && M_QA % 16 == 0 && M_P % 16 == 0, "smem layout");
#define XW 2
#define X3 2
#define X3C 3
#define NEARLY 2
#define BD 5
#define FPF 3
#define FSLEEP 800
#define FJ 250
#define FP 376
#define FN 32
#define NPOLL 2
#define PGAP 200
static_assert(NW + XW == 4 && 4 % NEARLY == 0 && BD <= BRING, "slots 4 and 5 hold the finisher weights");
constexpr float SCALE = 0.08838834764831845f;
constexpr float LOG2E = 1.4426950408889634f;
constexpr unsigned SPIN_LIMIT = 1u << 24;

#define NREP 2
constexpr int C_QUEUE = 0, C_KDONE = 1, C_BBAR = 3, C_LINES = 5;

struct First { const char* ptr[4]; };
struct Params {
    const __nv_bfloat16 *kc, *vc, *wo, *xb;
    __nv_bfloat16* out;
    CUtensorMap tm_j0;
    CUtensorMap tm_wq, tm_wuk, tm_ckv, tm_wuv, tm_wo;
    CUtensorMap tm_out[3][2];
};

__device__ unsigned g_epoch;
__device__ unsigned g_ctl[2][C_LINES][32];
__device__ uint2 g_qll[4 * 2048];
__device__ uint2 g_scores[128 * SK / 4];
__device__ float2 g_stats[128 * UPP];
__device__ float4 g_oacc[128 * 32];
__device__ unsigned g_vdone[NREP * NH][32];
__device__ uint4 g_qabs[4 * 8 * 4 * 4 * 32];
__device__ float2 g_bpart[NBCTA * NH * 256];
__device__ float2 g_bml[NBCTA * NH];
__device__ uint4 g_ctx[NH * 128];
__device__ uint4 g_outb[NBCTA * NH * 36];

__device__ __forceinline__ int cluster_role(int b) {
    const int i = b - NFIN, q = ((i >> 1) * 43 >> 7) * 2, r = i - 3 * q;
    int x = i - q;
    asm("{\n.reg .pred p;\nsetp.ge.s32 p, %1, 4;\nselp.s32 %0, %2, %0, p;\nsetp.lt.s32 p, %3, 0;\nselp.s32 %0, %4, %0, p;\n}"
        : "+r"(x) : "r"(r), "r"(NBCTA + NFIN - 4 + q + r), "r"(i), "r"(b + NBCTA));
    return x;
}

#define TS(i)
#define TSV(i, v)
#define LAND(i)
#define CLK(x)
#define ACC(a, x, y)

__device__ __forceinline__ uint32_t smem_u32(const void* p) { return (uint32_t)__cvta_generic_to_shared(p); }
__device__ __forceinline__ void mbar_init(uint32_t bar, uint32_t cnt) {
    asm volatile("mbarrier.init.shared::cta.b64 [%0], %1;" ::"r"(bar), "r"(cnt) : "memory");
}
__device__ __forceinline__ void mbar_expect_tx(uint32_t bar, uint32_t bytes) {
    asm volatile("mbarrier.arrive.expect_tx.shared::cta.b64 _, [%0], %1;" ::"r"(bar), "r"(bytes) : "memory");
}
__device__ __forceinline__ bool mbar_try(uint32_t bar, uint32_t parity) {
    uint32_t ok;
    asm volatile("{\n.reg .pred p;\nmbarrier.try_wait.parity.shared::cta.b64 p, [%1], %2;\nselp.u32 %0, 1, 0, p;\n}\n"
                 : "=r"(ok) : "r"(bar), "r"(parity) : "memory");
    return ok;
}
__device__ __forceinline__ void mbar_wait(uint32_t bar, uint32_t parity) {
    unsigned n = 0;
    while (!mbar_try(bar, parity)) { if (++n > SPIN_LIMIT) __trap(); }
}
__device__ __forceinline__ void bulk_load(uint32_t dst, const void* src, uint32_t bytes, uint32_t bar, uint64_t pol) {
    asm volatile("cp.async.bulk.shared::cluster.global.mbarrier::complete_tx::bytes.L2::cache_hint [%0], [%1], %2, [%3], %4;"
                 ::"r"(dst), "l"(src), "r"(bytes), "r"(bar), "l"(pol) : "memory");
}
__device__ __forceinline__ void tma3d(uint32_t dst, const CUtensorMap* tm, int c0, int c1, int c2, uint32_t bar, uint64_t pol) {
    asm volatile("cp.async.bulk.tensor.3d.shared::cluster.global.mbarrier::complete_tx::bytes.L2::cache_hint [%0], [%1, {%3,%4,%5}], [%2], %6;"
                 ::"r"(dst), "l"(tm), "r"(bar), "r"(c0), "r"(c1), "r"(c2), "l"(pol) : "memory");
}
__device__ __forceinline__ void tma4d(uint32_t dst, const CUtensorMap* tm, int c0, int c2, int c3, uint32_t bar, uint64_t pol) {
    asm volatile("cp.async.bulk.tensor.4d.shared::cluster.global.mbarrier::complete_tx::bytes.L2::cache_hint [%0], [%1, {%3,0,%4,%5}], [%2], %6;"
                 ::"r"(dst), "l"(tm), "r"(bar), "r"(c0), "r"(c2), "r"(c3), "l"(pol) : "memory");
}
__device__ __forceinline__ void l2_prefetch(const void* src, uint32_t bytes) {
    asm volatile("cp.async.bulk.prefetch.L2.global [%0], %1;" ::"l"(src), "r"(bytes) : "memory");
}
__device__ __forceinline__ void ldsm4(uint32_t (&r)[4], uint32_t addr) {
    asm volatile("ldmatrix.sync.aligned.m8n8.x4.shared.b16 {%0,%1,%2,%3}, [%4];"
                 : "=r"(r[0]), "=r"(r[1]), "=r"(r[2]), "=r"(r[3]) : "r"(addr));
}
__device__ __forceinline__ void ldsm4t(uint32_t (&r)[4], uint32_t addr) {
    asm volatile("ldmatrix.sync.aligned.m8n8.x4.trans.shared.b16 {%0,%1,%2,%3}, [%4];"
                 : "=r"(r[0]), "=r"(r[1]), "=r"(r[2]), "=r"(r[3]) : "r"(addr));
}
__device__ __forceinline__ void mma16816(float (&d)[4], const uint32_t (&a)[4], uint32_t b0, uint32_t b1) {
    asm("mma.sync.aligned.m16n8k16.row.col.f32.bf16.bf16.f32 {%0,%1,%2,%3}, {%4,%5,%6,%7}, {%8,%9}, {%0,%1,%2,%3};"
        : "+f"(d[0]), "+f"(d[1]), "+f"(d[2]), "+f"(d[3])
        : "r"(a[0]), "r"(a[1]), "r"(a[2]), "r"(a[3]), "r"(b0), "r"(b1));
}
__device__ __forceinline__ void wgmma_k64(float (&d)[4], uint32_t da, uint32_t db, int accumulate) {
    asm volatile("{\n.reg .pred p;\n.reg .b32 x, y;\n.reg .b64 a, b;\nsetp.ne.u32 p, %6, 0;\n"
                 "add.u32 x, %4, 0;\nadd.u32 y, %5, 0;\nmov.b64 a, {x, 0x40000040};\nmov.b64 b, {y, 1};\n"
                 "wgmma.mma_async.sync.aligned.m64n8k16.f32.bf16.bf16 {%0,%1,%2,%3}, a, b, p, 1, 1, 1, 0;\n"
                 "add.u32 x, %4, 128;\nadd.u32 y, %5, 8;\nmov.b64 a, {x, 0x40000040};\nmov.b64 b, {y, 1};\n"
                 "wgmma.mma_async.sync.aligned.m64n8k16.f32.bf16.bf16 {%0,%1,%2,%3}, a, b, 1, 1, 1, 1, 0;\n"
                 "add.u32 x, %4, 256;\nadd.u32 y, %5, 16;\nmov.b64 a, {x, 0x40000040};\nmov.b64 b, {y, 1};\n"
                 "wgmma.mma_async.sync.aligned.m64n8k16.f32.bf16.bf16 {%0,%1,%2,%3}, a, b, 1, 1, 1, 1, 0;\n"
                 "add.u32 x, %4, 384;\nadd.u32 y, %5, 24;\nmov.b64 a, {x, 0x40000040};\nmov.b64 b, {y, 1};\n"
                 "wgmma.mma_async.sync.aligned.m64n8k16.f32.bf16.bf16 {%0,%1,%2,%3}, a, b, 1, 1, 1, 1, 0;\n"
                 "}" : "+f"(d[0]), "+f"(d[1]), "+f"(d[2]), "+f"(d[3]) : "r"(da), "r"(db), "r"(accumulate) : "memory");
}
__device__ __forceinline__ uint32_t lds32(uint32_t a) {
    uint32_t v;
    asm volatile("ld.shared.u32 %0, [%1];" : "=r"(v) : "r"(a));
    return v;
}
__device__ __forceinline__ unsigned ld_acquire(const unsigned* p) {
    unsigned v;
    asm volatile("ld.acquire.gpu.global.u32 %0, [%1];" : "=r"(v) : "l"(p) : "memory");
    return v;
}
__device__ __forceinline__ uint2 ld_relaxed8(const void* p) {
    uint2 v;
    asm volatile("ld.relaxed.gpu.global.v2.u32 {%0,%1}, [%2];" : "=r"(v.x), "=r"(v.y) : "l"(p) : "memory");
    return v;
}
__device__ __forceinline__ unsigned ld_relaxed4(const void* p) {
    unsigned v;
    asm volatile("ld.relaxed.gpu.global.u32 %0, [%1];" : "=r"(v) : "l"(p) : "memory");
    return v;
}
__device__ __forceinline__ unsigned atom_inc(unsigned* p) {
    unsigned v;
    asm volatile("atom.relaxed.gpu.global.inc.u32 %0, [%1], 0x7fffffff;" : "=r"(v) : "l"(p) : "memory");
    return v;
}
__device__ __forceinline__ unsigned long long ld_relaxed64(const void* p) {
    unsigned long long v;
    asm volatile("ld.relaxed.gpu.global.u64 %0, [%1];" : "=l"(v) : "l"(p) : "memory");
    return v;
}
__device__ __forceinline__ void st_relaxed64(void* p, unsigned long long v) {
    asm volatile("st.relaxed.gpu.global.u64 [%0], %1;" ::"l"(p), "l"(v) : "memory");
}
__device__ __forceinline__ float4 ld_relaxed16(const void* p) {
    float4 v;
    asm volatile("ld.relaxed.gpu.global.v4.f32 {%0,%1,%2,%3}, [%4];" : "=f"(v.x), "=f"(v.y), "=f"(v.z), "=f"(v.w) : "l"(p) : "memory");
    return v;
}
__device__ __forceinline__ uint32_t mapa(uint32_t a, uint32_t rank) {
    uint32_t r;
    asm("mapa.shared::cluster.u32 %0, %1, %2;" : "=r"(r) : "r"(a), "r"(rank));
    return r;
}
__device__ __forceinline__ void mbar_first(uint32_t bar) {
    asm volatile("{\n.reg .pred p, q;\n.reg .u32 n;\nmov.u32 n, 0;\n"
                 "SPIN:\nmbarrier.try_wait.parity.shared::cta.b64 p, [%0], 0;\nadd.u32 n, n, 1;\nsetp.gt.u32 q, n, 0x1000000;\n@q trap;\n"
                 "@!p bra.uni SPIN;\n}" ::"r"(bar) : "memory");
}
__device__ __forceinline__ void mbar_first_cluster(uint32_t bar) {
    asm volatile("{\n.reg .pred p, q;\n.reg .u32 n;\nmov.u32 n, 0;\n"
                 "SPIN:\nmbarrier.try_wait.parity.relaxed.cluster.shared::cta.b64 p, [%0], 0;\nadd.u32 n, n, 1;\nsetp.gt.u32 q, n, 0x1000000;\n@q trap;\n"
                 "@!p bra.uni SPIN;\nfence.acquire.sync_restrict::shared::cluster.cluster;\n}" ::"r"(bar) : "memory");
}
__device__ __forceinline__ uint32_t now_ns() {
    unsigned long long t;
    asm volatile("mov.u64 %0, %globaltimer;" : "=l"(t));
    return (uint32_t)t;
}
__device__ __forceinline__ void fence_gpu() { asm volatile("fence.acq_rel.gpu;" ::: "memory"); }
__device__ __forceinline__ void red_add_u32(unsigned* p, unsigned v) {
    asm volatile("red.relaxed.gpu.global.add.u32 [%0], %1;" ::"l"(p), "r"(v) : "memory");
}
__device__ __forceinline__ void st_tagged2(void* p, float a, float b, unsigned tag) {
    const unsigned long long hi = (unsigned long long)tag << 32;
    asm volatile("st.relaxed.gpu.global.v2.b64 [%0], {%1,%2};" ::"l"(p), "l"(hi | __float_as_uint(a)), "l"(hi | __float_as_uint(b)) : "memory");
}
__device__ __forceinline__ ulonglong2 ld_tagged2(const void* p) {
    ulonglong2 v;
    asm volatile("ld.relaxed.gpu.global.v2.b64 {%0,%1}, [%2];" : "=l"(v.x), "=l"(v.y) : "l"(p) : "memory");
    return v;
}
__device__ __forceinline__ float4 atom_add_f4(void* p, float a, float b, float c, float d) {
    float4 r;
    asm volatile("atom.relaxed.gpu.global.add.v4.f32 {%0,%1,%2,%3}, [%4], {%5,%6,%7,%8};"
                 : "=f"(r.x), "=f"(r.y), "=f"(r.z), "=f"(r.w) : "l"(p), "f"(a), "f"(b), "f"(c), "f"(d) : "memory");
    return r;
}
__device__ __forceinline__ void red_release_cta_shared(uint32_t a, unsigned v) {
    asm volatile("red.release.cta.shared::cta.add.u32 [%0], %1;" ::"r"(a), "r"(v) : "memory");
}
__device__ __forceinline__ unsigned ld_acquire_cta_shared(uint32_t a) {
    unsigned v;
    asm volatile("ld.acquire.cta.shared::cta.u32 %0, [%1];" : "=r"(v) : "r"(a) : "memory");
    return v;
}
__device__ __forceinline__ void st_release_cta_shared(uint32_t a, unsigned v) {
    asm volatile("st.release.cta.shared::cta.u32 [%0], %1;" ::"r"(a), "r"(v) : "memory");
}
__device__ __forceinline__ void wait_count(const unsigned* p, unsigned target) {
    unsigned n = 0;
    while (ld_acquire(p) < target) { if (++n > SPIN_LIMIT) __trap(); }
}
__device__ __forceinline__ uint32_t pack_bf16(float lo, float hi) {
    uint32_t r;
    asm("cvt.rn.bf16x2.f32 %0, %1, %2;" : "=r"(r) : "f"(hi), "f"(lo));
    return r;
}
__device__ __forceinline__ float bf_lo(uint32_t v) { return __uint_as_float(v << 16); }
__device__ __forceinline__ float bf_hi(uint32_t v) { return __uint_as_float(v & 0xffff0000u); }
__device__ __forceinline__ float ex2(float x) { float y; asm("ex2.approx.ftz.f32 %0, %1;" : "=f"(y) : "f"(x)); return y; }
__device__ __forceinline__ float expsub(float a, float b) { return ex2((a - b) * LOG2E); }
__device__ __forceinline__ float warp_max(float v) {
#pragma unroll
    for (int m = 16; m; m >>= 1) v = fmaxf(v, __shfl_xor_sync(~0u, v, m));
    return v;
}
__device__ __forceinline__ float warp_sum(float v) {
#pragma unroll
    for (int m = 16; m; m >>= 1) v += __shfl_xor_sync(~0u, v, m);
    return v;
}
__device__ __forceinline__ unsigned unit_block(int u) {
    const unsigned v = u & (NUK - 1);
    return u < NUK ? (v & ~0x78u) | (v & 0x18u) << 2 | (v & 0x60u) >> 2 : v;
}
__device__ __forceinline__ const char* block_src(const void* base, unsigned blk) {
    const unsigned po = blk / UPP;
    return reinterpret_cast<const char*>(base) + (size_t)(((po & 3) * NH + (po >> 2)) * UPP + blk % UPP) * TILE_BYTES;
}

template <bool CLU>
__device__ __forceinline__ void a_worker(const Params& p, int un, int un2, bool once, bool hold, int nstatic, uint32_t slot, uint32_t bar, uint32_t wb,
                                         uint32_t help, unsigned epoch, uint64_t pol) {
    constexpr int NU = 2 * NUK;
    const int lane = threadIdx.x & 31, g = lane >> 2, t = lane & 3;
    const int li = lane & 7;
    uint32_t kaddr[4], vaddr[8];
    {
        const int e = (lane >> 3) & 1, kk = lane >> 4;
#pragma unroll
        for (int s = 0; s < 4; s++) kaddr[s] = slot + (16 * li + e) * 256 + ((2 * s + kk + li) & 7) * 16;
        const int vrow = 4 * (li >> 1) + (li & 1) + 2 * kk;
#pragma unroll
        for (int c = 0; c < 8; c++) vaddr[c] = slot + vrow * 256 + e * 128 + ((c + li) & 7) * 16;
#pragma unroll
        for (int c = 0; c < 8; c++) asm volatile("" : "+r"(vaddr[c]));
    }
    const uint32_t vmask = (g >> 1) != t ? 0u : ((g & 1) ? 0xffff0000u : 0xffffu);
    int kseen = -1;
    unsigned long long H0 = 0, H1 = 0;
    auto header = [&](int v, unsigned vb) {
        if (v >= NU) return;
        const void *a0, *a1;
        if (v < NUK) {
            const unsigned po = vb / UPP;
            a0 = g_qll + (po & 3) * 2048 + (po >> 2) * 64 + lane;
            a1 = reinterpret_cast<const uint2*>(a0) + 32;
        } else {
            const int half = vb / (NUK / 2);
            if (half > kseen) {
                unsigned n = 0;
                while (ld_acquire_cta_shared(help + 12 + 4 * half) == 0) { if (++n > (SPIN_LIMIT << 4)) __trap(); }
                kseen = half;
            }
            a0 = &g_scores[vb * (KEYS / 4) + lane];
            a1 = &g_stats[(vb / UPP) * UPP + lane];
        }
        H0 = ld_relaxed64(a0);
        H1 = ld_relaxed64(a1);
    };
    epoch = __shfl_sync(~0u, epoch, 0);
    if (hold) { unsigned n = 0; while (ld_acquire_cta_shared(help + 24) < 2) { if (++n > (SPIN_LIMIT << 4)) __trap(); } }
    unsigned (*ctl)[32] = g_ctl[epoch & 1];
    const unsigned tag = epoch + 1;
    unsigned nxt = un2 - nstatic;
    if (CLU && un2 < NU && lane == 0) {
        mbar_expect_tx(bar + 16, TILE_BYTES);
        bulk_load(slot + SLOT, block_src(p.kc, unit_block(un2)), TILE_BYTES, bar + 16, pol);
    }
    int u = -1;
    unsigned bu = 0, bn = unit_block(un);
    bool have = false;
    uint32_t phase = 0;
    unsigned kpend = 0;
    const unsigned zero = gridDim.x >> 24;
    uint32_t Q[16];
    float4 oret = make_float4(0.f, 0.f, 0.f, 0.f);
    while (true) {
        const char* nsrc = block_src(un < NUK ? p.kc : p.vc, bn);
        float4* odst = &g_oacc[(bu / UPP) * 32 + lane];
        unsigned* vdst = &g_vdone[(lane & (NREP - 1)) * NH + bu / (4 * UPP)][0];
        float d[8][4];
        CLK(c1);
        asm volatile("" : "+l"(odst));
        if (u >= NUK) {
#pragma unroll
            for (int j = 0; j < 8; j++) { d[j][0] = d[j][1] = d[j][2] = d[j][3] = 0.f; }
            mbar_wait(wb, phase);
            LAND(NUK + bu);
            uint32_t a[2][8][4];
#pragma unroll
            for (int c = 0; c < 8; c++) ldsm4t(a[0][c], vaddr[c]);
#pragma unroll
            for (int j = 0; j < 8; j++) {
                if (j < 7) {
#pragma unroll
                    for (int c = 0; c < 8; c++) ldsm4t(a[(j + 1) & 1][c], vaddr[c] + (j + 1) * 4096);
                }
#pragma unroll
                for (int c = 0; c < 8; c++) mma16816(d[c], a[j & 1][c], Q[2 * j], Q[2 * j + 1]);
            }
            float o[4];
#pragma unroll
            for (int r = 0; r < 2; r++) {
                o[2 * r] = d[0][2 * r] + d[7][2 * r + 1];
                o[2 * r + 1] = d[0][2 * r + 1] + d[1][2 * r];
#pragma unroll
                for (int k = 1; k < 4; k++) {
                    const int src = (lane & 28) | ((t - k) & 3);
                    o[2 * r] += __shfl_sync(~0u, d[2 * k][2 * r] + d[2 * k - 1][2 * r + 1], src);
                    o[2 * r + 1] += __shfl_sync(~0u, d[2 * k][2 * r + 1] + d[2 * k + 1][2 * r], src);
                }
            }
            oret = atom_add_f4(odst, o[0], o[1], o[2], o[3]);
        } else if (u >= 0) {
#pragma unroll
            for (int j = 0; j < 8; j++) { d[j][0] = d[j][1] = d[j][2] = d[j][3] = 0.f; }
            mbar_wait(wb, phase);
            LAND(bu);
            uint32_t a[2][8][4];
#pragma unroll
            for (int j = 0; j < 8; j++) ldsm4(a[0][j], kaddr[0] + (4 * (j & 3) + 2 * (j >> 2)) * 256);
#pragma unroll
            for (int s = 0; s < 8; s++) {
                if (s < 7) {
#pragma unroll
                    for (int j = 0; j < 8; j++)
                        ldsm4(a[(s + 1) & 1][j], kaddr[(s + 1) & 3] + (4 * (j & 3) + 2 * (j >> 2)) * 256 + ((s + 1) >> 2) * 128);
                }
#pragma unroll
                for (int j = 0; j < 8; j++)
                    mma16816(d[j], a[s & 1][j], Q[(s & 4) * 2 + ((2 * s - 2 * j) & 7)], Q[(s & 4) * 2 + ((2 * s + 1 - 2 * j) & 7)]);
            }
        }
        const bool pre = wb != bar;
        if (u >= 0) {
            phase = pre || once ? 0 : phase ^ 1;
            wb = once ? bar + 16 : bar;
            if (CLU && once) {
#pragma unroll
                for (int s = 0; s < 4; s++) kaddr[s] += SLOT;
            }
        }
        CLK(c2b);
        if (un < NU && lane == 0) {
            if (!once) nxt = atom_inc(&ctl[C_QUEUE][0]);
            if (u >= 0 ? !once : !pre) {
                mbar_expect_tx(bar, TILE_BYTES);
                bulk_load(slot, nsrc, TILE_BYTES, bar, pol);
            }
        }
        const uint32_t tiss = now_ns();
        CLK(c3);
        if ((unsigned)u < (unsigned)NUK) {
            const int j0 = (t - (g >> 1)) & 3;
            float v[4];
#pragma unroll
            for (int q = 0; q < 4; q++) {
                const int jq = (q >> 1) * 4, e = (q & 1) * 2;
                const float x0 = (g & 1) ? d[jq + 0][e + 1] : d[jq + 0][e];
                const float x1 = (g & 1) ? d[jq + 1][e + 1] : d[jq + 1][e];
                const float x2 = (g & 1) ? d[jq + 2][e + 1] : d[jq + 2][e];
                const float x3 = (g & 1) ? d[jq + 3][e + 1] : d[jq + 3][e];
                const float y0 = (j0 & 1) ? x1 : x0, y1 = (j0 & 1) ? x3 : x2;
                v[q] = (j0 & 2) ? y1 : y0;
            }
            const uint32_t r0 = pack_bf16(v[0], v[1]), r1 = pack_bf16(v[2], v[3]);
            const uint32_t s0 = pack_bf16(bf_lo(r0) * SCALE, bf_hi(r0) * SCALE);
            const uint32_t s1 = pack_bf16(bf_lo(r1) * SCALE, bf_hi(r1) * SCALE);
            g_scores[bu * (KEYS / 4) + 4 * g + j0] = make_uint2(s0, s1);
            const float f0 = bf_lo(s0), f1 = bf_hi(s0), f2 = bf_lo(s1), f3 = bf_hi(s1);
            const float m = warp_max(fmaxf(fmaxf(f0, f1), fmaxf(f2, f3)));
            const float l = warp_sum((expsub(f0, m) + expsub(f1, m)) + (expsub(f2, m) + expsub(f3, m)));
            if (lane == 0) g_stats[bu] = make_float2(m, l);
            kpend++;
            if (un / (NUK / 2) != u / (NUK / 2)) {
                __syncwarp();
                if (lane == 0) {
                    red_release_cta_shared(help + 4 * (u / (NUK / 2)), kpend);
                    if (un >= NUK) red_release_cta_shared(help + 8, 1u);
                }
                kpend = 0;
            }
        }
        CLK(c4);
        int unn = NU;
        if (un < NU) {
            unsigned n = 0;
            while (true) {
                if (!have) header(un, bn);
                if (un >= NUK || __all_sync(~0u, (uint32_t)(H0 >> 32) == tag && (uint32_t)(H1 >> 32) == tag)) break;
                if (++n > SPIN_LIMIT) __trap();
                have = false;
            }
            if (un >= NUK) {
                const uint32_t s0 = (uint32_t)H0, s1 = (uint32_t)(H0 >> 32);
                const float mu = __uint_as_float((uint32_t)H1);
                const float m = warp_max(mu);
                const float l = warp_sum(__uint_as_float((uint32_t)(H1 >> 32)) * expsub(mu, m));
                const float inv = 1.0f / l;
                const uint32_t w0 = pack_bf16(expsub(bf_lo(s0), m) * inv, expsub(bf_hi(s0), m) * inv);
                const uint32_t w1 = pack_bf16(expsub(bf_lo(s1), m) * inv, expsub(bf_hi(s1), m) * inv);
#pragma unroll
                for (int j = 0; j < 8; j++) {
                    Q[2 * j] = __shfl_sync(~0u, w0, 4 * j + t) & vmask;
                    Q[2 * j + 1] = __shfl_sync(~0u, w1, 4 * j + t) & vmask;
                }
            } else {
#pragma unroll
                for (int j = 0; j < 8; j++) {
                    const int src = (((j + g) & 7) << 2) + t;
                    Q[j] = __shfl_sync(~0u, (uint32_t)H0, src);
                    Q[8 + j] = __shfl_sync(~0u, (uint32_t)H1, src);
                }
            }
            if (u < 0) TS(2);
            unn = nstatic + (int)__shfl_sync(~0u, nxt, 0);
            nxt = NU;
            if (CLU && !once && unn >= NU && lane == 0)
                asm volatile("st.relaxed.cta.shared::cta.u32 [%0], %1;" ::"r"(help + 28), "r"((tiss + (FJ - (unn - NU)) * 10) | 1u) : "memory");
        }
        if (u >= NUK && lane < (CLU ? 1 : NREP))
            red_add_u32(vdst,
                        1u + ((__float_as_uint(oret.x) | __float_as_uint(oret.y) | __float_as_uint(oret.z) | __float_as_uint(oret.w)) & zero));
        if (un >= NU) break;
        bu = bn;
        have = !(un < NUK && unn >= NUK && !(un >= NUK / 2 && unn < NUK + NUK / 2));
        bn = unit_block(unn);
        if (have) header(unn, bn);
        u = un;
        un = unn;
    }
    TS(4);
}

__device__ __forceinline__ void k_helper(uint32_t help, unsigned epoch) {
    if ((threadIdx.x & 31) != 0) return;
    unsigned (*ctl)[32] = g_ctl[epoch & 1];
    unsigned sent0 = 0, sent1 = 0, n = 0;
    int seen = 0;
    bool fin = false;
    while (!fin || seen < 2) {
        if (!fin) {
            fin = ld_acquire_cta_shared(help + 8) == NW + XW;
            const unsigned c0 = ld_acquire_cta_shared(help), c1 = ld_acquire_cta_shared(help + 4);
            if (c0 != sent0 || c1 != sent1) {
                fence_gpu();
                if (c0 != sent0) red_add_u32(&ctl[C_KDONE][0], c0 - sent0);
                if (c1 != sent1) red_add_u32(&ctl[C_KDONE + 1][0], c1 - sent1);
                sent0 = c0; sent1 = c1;
            }
        }
        if (seen < 2 && ld_acquire(&ctl[C_KDONE + seen][0]) >= NUK / 2) {
            st_release_cta_shared(help + 12 + 4 * seen, 1u);
            seen++;
        } else {
            __nanosleep(300);
        }
        if (++n > SPIN_LIMIT) __trap();
    }
}

__device__ __forceinline__ void v_poller(uint32_t sbase, int f, int w) {
    const int lane = threadIdx.x & 31;
    const unsigned (*cp)[32] = &g_vdone[((f * NPOLL + w) % NREP) * NH];
    unsigned n = 0;
    while (ld_acquire_cta_shared(sbase + M_HELP + 12) == 0) { __nanosleep(1000); if (++n > SPIN_LIMIT) __trap(); }
    int h = 0;
    bool fast = false;
    while (h < NH) {
        const unsigned r = __ballot_sync(~0u, ld_acquire(&cp[min(h + (lane & 3), NH - 1)][0]) >= 4 * UPP) & 15u;
        if (r & 1) {
            h = min(NH, h + __ffs(~r) - 1);
            __syncwarp();
            if (lane == 0) asm volatile("red.release.cta.shared::cta.max.u32 [%0], %1;" ::"r"(sbase + M_HELP + 20), "r"(h) : "memory");
        }
        if (h < NH - 4) {
            __nanosleep(h ? 300 : 1000);
        } else if (!fast) {
            fast = true;
            const long long t0 = clock64();
            while (clock64() - t0 < w * PGAP) {}
        }
        if (++n > SPIN_LIMIT) __trap();
    }
}
__device__ __forceinline__ void finisher(const Params& p, uint32_t sbase, int f) {
    const int lane = threadIdx.x & 31;
    {
        const char* wg = reinterpret_cast<const char*>(p.wo);
        const uint32_t dst = sbase + 4 * SLOT + (16 * (lane & 7) + (lane >> 3)) * 16;
#pragma unroll 1
        for (int h = -FPF - 4; h < NH; h++) {
            if (lane == 0 && (unsigned)(h + FPF) < (unsigned)NH) l2_prefetch(wg + (size_t)(h + FPF) * 147456 + f * 2048, 2048);
            if (h >= 0) {
#pragma unroll
                for (int r = 0; r < 4; r++)
                    asm volatile("cp.async.cg.shared.global [%0], [%1], 16;" ::"r"(dst + h * 2048 + ((r & 1) * 4 + (r >> 1) * 8) * 16),
                                 "l"(wg + (size_t)(h * 128 + r * 32 + lane) * (DM * 2) + f * 16) : "memory");
            }
            __nanosleep(FSLEEP);
        }
        asm volatile("cp.async.wait_all;" ::: "memory");
        __syncwarp();
    }
    TS(11);
    const float4* vec = g_oacc + ((lane >> 2) & 3) * 32 + (lane >> 4) * 16 + (lane & 3);
    float acc[2][2][4];
#pragma unroll
    for (int i = 0; i < 16; i++) acc[i >> 3][(i >> 2) & 1][i & 3] = 0.f;
    uint32_t* outp = reinterpret_cast<uint32_t*>(p.out + (lane >> 2) * (2 * DM) + f * 8 + (lane & 3) * 2);
    uint32_t wa = sbase + 4 * SLOT + lane * 16;
    auto project = [&](const float4 (&x)[4], const uint32_t (&w)[4][4]) {
#pragma unroll
        for (int s = 0; s < 4; s++) {
            const uint32_t a[4] = {pack_bf16(x[s].x, x[s].y), 0u, pack_bf16(x[s].z, x[s].w), 0u};
            mma16816(acc[0][s & 1], a, w[s >> 1][(s & 1) * 2], w[s >> 1][(s & 1) * 2 + 1]);
            mma16816(acc[1][s & 1], a, w[2 + (s >> 1)][(s & 1) * 2], w[2 + (s >> 1)][(s & 1) * 2 + 1]);
        }
    };
    int h = 0;
    unsigned n = 0;
    while (h < NH) {
        uint32_t w[4][4];
#pragma unroll
        for (int q = 0; q < 4; q++) ldsm4t(w[q], wa + q * 512);
        int ready;
        while ((ready = ld_acquire_cta_shared(sbase + M_HELP + 20)) <= h) {
            if (h < NH - 3) __nanosleep(100);
            if (++n > (SPIN_LIMIT << 4)) __trap();
        }
        float4 x[4], y[4];
#pragma unroll
        for (int s = 0; s < 4; s++) x[s] = ld_relaxed16(vec + s * 4);
        const bool two = ready > h + 1;
        if (two) {
#pragma unroll
            for (int s = 0; s < 4; s++) y[s] = ld_relaxed16(vec + 128 + s * 4);
        }
        project(x, w);
        if (two) {
#pragma unroll
            for (int q = 0; q < 4; q++) ldsm4t(w[q], wa + 2048 + q * 512);
            project(y, w);
        }
        const int nr = two ? 2 : 1;
        h += nr;
        vec += nr * 128;
        wa += nr * 2048;
        const float o0 = acc[0][0][0] + acc[0][1][0] + __shfl_down_sync(~0u, acc[1][0][0] + acc[1][1][0], 16);
        const float o1 = acc[0][0][1] + acc[0][1][1] + __shfl_down_sync(~0u, acc[1][0][1] + acc[1][1][1], 16);
        asm volatile("{\n.reg .pred p;\nsetp.ne.u32 p, %2, 0;\n@p st.global.u32 [%0], %1;\n}" ::"l"(outp), "r"(pack_bf16(o0, o1)),
                     "r"((uint32_t)(lane < 16 && h == NH)) : "memory");
    }
}

__device__ __forceinline__ void out_fetch(uint32_t sbase, int j, int h) {
    const int lane = threadIdx.x & 31, g = lane >> 2;
    float4 x[4];
#pragma unroll
    for (int b = 0; b < 4; b++) x[b] = ld_relaxed16(&g_oacc[(h * 4 + ((b + g) & 3)) * 32 + lane]);
#pragma unroll
    for (int b = 0; b < 4; b++) {
        const uint32_t a = sbase + F_X + j * FXP + g * 128 + ((b + g) & 3) * 16 + (lane & 3) * 4;
        asm volatile("st.shared.u32 [%0], %1;\nst.shared.u32 [%0 + 64], %2;" ::"r"(a), "r"(pack_bf16(x[b].x, x[b].y)), "r"(pack_bf16(x[b].z, x[b].w)) : "memory");
    }
    asm volatile("fence.proxy.async.shared::cta;" ::: "memory");
}
__device__ __forceinline__ void out_early(uint32_t sbase, int rank, unsigned tag) {
    const int lane = threadIdx.x & 31;
    if (lane < 10) {
        mbar_init(sbase + F_BAR + 16 + lane * 8, lane >= 8 ? 4 : lane == 6 ? 2 : 1);
        if (lane < 8) mbar_expect_tx(sbase + F_BAR + 16 + lane * 8, 16384);
    }
    asm volatile("fence.mbarrier_init.release.cluster;" ::: "memory");
    unsigned n = 0;
    auto head = [&](int k) { return k < 4 ? k : k == 4 ? 4 + (rank >> 1) : (k - 4) * 8 + rank; };
#pragma unroll 1
    for (int k = rank < 4 ? 4 : 0; k < 7; k++) {
        for (unsigned q = 0; ld_acquire(&g_vdone[head(k)][0]) < 4 * UPP; q++) { __nanosleep(500); if (q > SPIN_LIMIT) __trap(); }
        out_fetch(sbase, k < 4 ? 8 + k : k == 4 ? 7 : k - 1, head(k));
#pragma unroll 1
        for (int m = rank < 4 ? 0 : 4; m < 8 && k == 4;) {
            ulonglong2 v[4];
            bool ok = true;
#pragma unroll
            for (int i = 0; i < 4; i++) v[i] = ld_tagged2(&g_ctx[head(m) * 128 + i * 32 + lane]);
#pragma unroll
            for (int i = 0; i < 4; i++) {
                ok = ok && (unsigned)(v[i].x >> 32) == tag && (unsigned)(v[i].y >> 32) == tag;
                asm volatile("st.shared.v2.u32 [%0], {%1,%2};" ::"r"(sbase + F_X + (m < 4 ? 8 + m : m - 4) * FXP + (i * 32 + lane) * 8),
                             "r"((uint32_t)v[i].x), "r"((uint32_t)v[i].y) : "memory");
            }
            if (__all_sync(~0u, ok)) {
                m++;
            } else {
                __nanosleep(500);
                if (++n > SPIN_LIMIT) __trap();
            }
        }
    }
    __syncwarp();
    if (lane == 0) st_release_cta_shared(sbase + M_HELP + 32, 1u);
}
__device__ __forceinline__ void out_late(uint32_t sbase, int rank) {
    unsigned n = 0;
    while (ld_acquire_cta_shared(sbase + M_HELP + 32) == 0) { if (++n > (SPIN_LIMIT << 4)) __trap(); }
    while (ld_acquire(&g_vdone[24 + rank][0]) < 4 * UPP) { if (++n > SPIN_LIMIT) __trap(); }
    TS(12);
    out_fetch(sbase, 6, 24 + rank);
    __syncwarp();
    if ((threadIdx.x & 31) == 0) asm volatile("mbarrier.arrive.shared::cta.b64 _, [%0];" ::"r"(sbase + F_BAR + 16 + 6 * 8) : "memory");
    TS(13);
}
__device__ __forceinline__ void out_project(uint32_t sbase, int rank, int w) {
    const int lane = threadIdx.x & 31, g = lane >> 2, t = lane & 3;
    unsigned n = 0;
    while (ld_acquire_cta_shared(sbase + M_HELP + 32) == 0) { __nanosleep(500); if (++n > SPIN_LIMIT) __trap(); }
    asm volatile("barrier.cluster.wait.acquire.aligned;" ::: "memory");
    uint32_t rdst[2], rbar[2];
#pragma unroll
    for (int e = 0; e < 2; e++) {
        rdst[e] = mapa(sbase + F_RECV + rank * 256 + g * 32 + t * 16, 4 * e + w);
        rbar[e] = mapa(sbase + F_BAR, 4 * e + w);
    }
    while (ld_acquire_cta_shared(sbase + M_HELP + 28) == 0) { __nanosleep(200); if (++n > SPIN_LIMIT) __trap(); }
    const uint32_t da = (1u << 16) | (((sbase + F_W) & 0x3ffff) >> 4), db = (4u << 16) | (((sbase + F_X) & 0x3ffff) >> 4);
    float d[2][4] = {0.f, 0.f, 0.f, 0.f, 0.f, 0.f, 0.f, 0.f};
#pragma unroll
    for (int i = 0; i < 7; i++) {
        const int e = i >> 2;
        mbar_first(sbase + F_BAR + 16 + i * 8);
        asm volatile("wgmma.fence.sync.aligned;" ::: "memory");
        if (i == 0) {
            wgmma_k64(d[0], da, db + (rank & 1) * 32, 0);
            wgmma_k64(d[1], da + 512, db + 7 * (FXP / 16) + (rank & 1) * 32, 0);
        } else {
            wgmma_k64(d[e], da + (i % 6) * 1024, db + i * (FXP / 16), 1);
            wgmma_k64(d[e], da + (i % 6) * 1024 + 512, db + i * (FXP / 16) + 32, 1);
        }
        asm volatile("wgmma.commit_group.sync.aligned;" ::: "memory");
        if (i < 2 || i % 3 == 0)
            asm volatile("wgmma.wait_group.sync.aligned 0;" : "+f"(d[e][0]), "+f"(d[e][1]), "+f"(d[e][2]), "+f"(d[e][3])::"memory");
        if (i < 2) {
            asm volatile("{\n.reg .pred p;\nsetp.eq.u32 p, %1, 0;\n@p mbarrier.arrive.shared::cta.b64 _, [%0];\n}"
                         ::"r"(sbase + F_BAR + 80 + i * 8), "r"(lane) : "memory");
        } else if (i % 3 == 0) {
            if (t < 2)
                asm volatile("st.async.weak.shared::cluster.mbarrier::complete_tx::bytes.v4.f32 [%0], {%1,%2,%3,%4}, [%5];"
                             ::"r"(rdst[e]), "f"(d[e][0]), "f"(d[e][1]), "f"(d[e][2]), "f"(d[e][3]), "r"(rbar[e]) : "memory");
            __syncwarp();
        }
    }
}
__device__ __forceinline__ void out_issue(const Params& p, uint32_t sbase, int c, int rank, uint64_t pol) {
    unsigned n = 0;
    while (ld_acquire_cta_shared(sbase + M_HELP + 32) == 0) { __nanosleep(500); if (++n > SPIN_LIMIT) __trap(); }
#pragma unroll
    for (int i = 0; i < 6; i++) asm volatile("prefetch.tensormap [%0];" ::"l"(&p.tm_out[i >> 1][i & 1]) : "memory");
    uint32_t t0;
    while ((t0 = ld_acquire_cta_shared(sbase + M_HELP + 28)) == 0) { __nanosleep(100); if (++n > SPIN_LIMIT) __trap(); }
#pragma unroll
    for (int i = 0; i < 8; i++) {
        const uint32_t dst = sbase + F_W + (i % 6) * 16384, bar = sbase + F_BAR + 16 + i * 8;
        if (i >= 6) mbar_wait(sbase + F_BAR + 32 + i * 8, 0);
        for (int k = 0; k < 4096 && (int)(now_ns() - t0) < 0; k++) {}
        if (i == 0) {
            TS(16);
            tma4d(dst, &p.tm_out[0][0], c * 64, (rank & 1) * 4, 4 + (rank >> 1), bar, pol);
            tma4d(dst + 8192, &p.tm_out[0][1], c * 64, (rank & 1) * 4, 4 + (rank >> 1), bar, pol);
        } else if (i < 7) {
            tma4d(dst, &p.tm_out[1][i >> 2], c * 64, 0, ((i - 1) % 3 + 1) * 8 + rank, bar, pol);
        } else {
#pragma unroll
            for (int q = 0; q < 2; q++) {
                const int h = ((q + rank) & 1) * 2;
                tma4d(dst + h * 4096, &p.tm_out[2][rank >> 2], c * 64 + (rank & 3) * 16, 0, h, bar, pol);
            }
        }
        t0 += i == 6 ? FP - FN : FP;
    }
    TS(17);
}
__device__ __forceinline__ void out_final(const Params& p, uint32_t sbase, int c, int rank, int hf) {
    const int lane = threadIdx.x & 31, g = lane >> 2, t = lane & 3;
    unsigned n = 0;
    while (ld_acquire_cta_shared(sbase + M_HELP + 32) == 0) { if (++n > (SPIN_LIMIT << 4)) __trap(); }
    uint32_t bf[16][2];
#pragma unroll
    for (int s = 0; s < 16; s++) {
        const uint32_t a = sbase + F_X + (8 + 2 * (g >> 2) + (s >> 3)) * FXP + (s & 7) * 128 + (g & 3) * 16 + t * 4;
        bf[s][0] = lds32(a);
        bf[s][1] = lds32(a + 64);
    }
    __nv_bfloat16* dst = p.out + (2 * (t & 1) + (t >> 1)) * (2 * DM) + (rank < 4 ? DM : 0) + c * 64 + (rank & 3) * 16 + hf * 8 + g;
    uint32_t src = sbase + F_RECV + g * 32 + (t & 1) * 16 + hf * 8 + (t >> 1) * 4;
    uint32_t wa = sbase + F_W + 16384 + ((lane >> 3) & 1) * 8192 + ((lane & 7) + (lane >> 4) * 8) * 32 + ((hf ^ (lane >> 2)) & 1) * 16;
    wa += bf[15][1] & (gridDim.x >> 24);
    asm volatile("" : "+l"(dst), "+r"(src), "+r"(wa));
    float x[8];
    auto partials = [&]() {
        mbar_first_cluster(sbase + F_BAR);
#pragma unroll
        for (int i = 0; i < 8; i++) asm volatile("ld.shared.f32 %0, [%1];" : "=f"(x[i]) : "r"(src + i * 256) : "memory");
    };
    const bool pre = rank < 4;
    if (pre) partials();
    mbar_first(sbase + F_BAR + 16 + 7 * 8);
    uint32_t a[16][4];
    float acc[4][4];
#pragma unroll
    for (int i = 0; i < 16; i++) acc[i >> 2][i & 3] = 0.f;
#pragma unroll
    for (int s = 0; s < 16; s++) ldsm4t(a[s], wa + s * 512);
#pragma unroll
    for (int s = 0; s < 16; s++) mma16816(acc[s & 3], a[s], bf[s][0], bf[s][1]);
    float y[4];
#pragma unroll
    for (int i = 0; i < 4; i++) y[i] = (acc[0][i] + acc[1][i]) + (acc[2][i] + acc[3][i]);
    float v = __shfl_xor_sync(~0u, (t & 2) ? y[2] : y[1], 2);
    if (!pre) partials();
    v = (v + ((t & 2) ? y[3] : y[0])) + (((x[0] + x[1]) + (x[2] + x[3])) + ((x[4] + x[5]) + (x[6] + x[7])));
    asm volatile("{\n.reg .b16 h;\ncvt.rn.bf16.f32 h, %1;\nst.global.b16 [%0], h;\n}" ::"l"(dst), "f"(v) : "memory");
}

constexpr int BS_WUK = 5, BS_Q = 9, BS_CKV = 11, BS_PART = 27, BS_WUV = 29, BS_END = 33;

__device__ __noinline__ void b_issue(const Params& p, int n, int bi, uint32_t sbase, uint64_t pol) {
    if (n >= BS_END || (n >= BS_Q && n < BS_CKV) || (n >= BS_PART && n < BS_WUV)) return;
    const uint32_t bar = sbase + M_BAR + (NSLOT + n % BRING) * 8;
    const CUtensorMap* tm;
    int row, panel = 2 * bi;
    if (n < BS_WUK) { tm = &p.tm_wq; row = n * 128; }
    else if (n < BS_Q) { tm = &p.tm_wuk; row = (n - BS_WUK) * 128; }
    else if (n < BS_PART) {
        tm = &p.tm_ckv; panel = 0;
        row = (bi >> 3) * SK + ((n - BS_CKV) * 8 + (bi & 7)) * 32;
    }
    else { tm = &p.tm_wuv; row = (n - BS_WUV) * 128; }
    mbar_expect_tx(bar, n == 0 ? 32768 + 4 * 1152 : 32768);
    tma3d(sbase + (n % BRING) * SLOT, tm, 0, row, panel, bar, pol);
}
__device__ __forceinline__ void b_issue_xchg(int n, const void* src, uint32_t sbase, uint64_t pol) {
    asm volatile("fence.proxy.async;" ::: "memory");
#pragma unroll
    for (int i = 0; i < 2; i++) {
        const uint32_t bar = sbase + M_BAR + (NSLOT + (n + i) % BRING) * 8;
        mbar_expect_tx(bar, 32768);
        bulk_load(sbase + ((n + i) % BRING) * SLOT, reinterpret_cast<const char*>(src) + i * 32768, 32768, bar, pol);
    }
}
__device__ __forceinline__ void b_wait(int n, uint32_t sbase) {
    mbar_wait(sbase + M_BAR + (NSLOT + n % BRING) * 8, (n / BRING) & 1);
}

__device__ __noinline__ void b_gemm(const Params& p, uint32_t sbase, int n0, int n1, int ktot, uint32_t xh, uint32_t xl, int pitch,
                                    int bi, uint64_t pol) {
    const int tid = threadIdx.x, warp = tid >> 5, lane = tid & 31, g = lane >> 2, t = lane & 3;
    const uint32_t woff = (warp >> 2) * 16384 + (lane & 15) * 128 + ((((warp & 3) * 2 + (lane >> 4)) ^ (lane & 7)) * 16);
    const uint32_t xoff = (g & 3) * pitch + t * 4;
    float acc[2][4];
#pragma unroll
    for (int i = 0; i < 8; i++) acc[i >> 2][i & 3] = 0.f;
#pragma unroll 1
    for (int n = n0; n < n1; n++) {
        b_wait(n, sbase);
        const uint32_t slot = sbase + (n % BRING) * SLOT + woff;
        const int k0 = (n - n0) * 128;
        const int ns = min(8, (ktot - k0) >> 4);
#pragma unroll 2
        for (int s = 0; s < ns; s++) {
            uint32_t a[4], w[4];
            const uint32_t xo = xoff + (k0 + 16 * s) * 2;
            a[0] = lds32(xh + xo); a[2] = lds32(xh + xo + 16);
            a[1] = xl ? lds32(xl + xo) : 0u; a[3] = xl ? lds32(xl + xo + 16) : 0u;
            ldsm4t(w, slot + s * 2048);
            mma16816(acc[0], a, w[0], w[1]);
            mma16816(acc[1], a, w[2], w[3]);
        }
        __syncthreads();
        if (tid == 0) b_issue(p, n + BD, bi, sbase, pol);
    }
    if (g < 4) {
#pragma unroll
        for (int j = 0; j < 2; j++)
            asm volatile("st.shared.u32 [%0], %1;" ::"r"(sbase + M_QB + g * QP + (warp * 16 + j * 8 + t * 2) * 2),
                         "r"(pack_bf16(acc[j][0] + acc[j][2], acc[j][1] + acc[j][3])) : "memory");
    }
    __syncthreads();
}

__device__ __forceinline__ void b_exchange(unsigned* c, int n, const void* src, uint32_t sbase, uint64_t pol) {
    TS(n == BS_Q ? 24 : 28);
    __syncthreads();
    if (threadIdx.x == 0) {
        TS(n == BS_Q ? 25 : 29);
        fence_gpu();
        TS(n == BS_Q ? 26 : 30);
        red_add_u32(c, 1u);
        wait_count(c, NBCTA);
        TS(n == BS_Q ? 27 : 31);
        b_issue_xchg(n, src, sbase, pol);
    }
}

template <bool CLU>
__device__ __noinline__ void b_chain(const Params& p, char* smem, uint32_t sbase, int bi, unsigned epoch, uint64_t pol) {
    const int tid = threadIdx.x, warp = tid >> 5, lane = tid & 31, g = lane >> 2, t = lane & 3;
    unsigned (*ctl)[32] = g_ctl[epoch & 1];
    float* red = reinterpret_cast<float*>(smem + 5 * SLOT);
    b_gemm(p, sbase, 0, BS_WUK, DM, sbase + M_XB, 0, XP, bi, pol);
    TS(6);
    {
        uint32_t Q[16];
#pragma unroll
        for (int c = 0; c < 16; c++) Q[c] = lds32(sbase + M_QB + (g & 3) * QP + c * 16 + t * 4);
        float* qa = reinterpret_cast<float*>(smem + M_QA);
#pragma unroll 1
        for (int n = BS_WUK; n < BS_Q; n++) {
            b_wait(n, sbase);
            const uint32_t base = sbase + (n % BRING) * SLOT + (warp * 16 + (lane & 15)) * 128;
            float d[2][4];
#pragma unroll
            for (int i = 0; i < 8; i++) d[i >> 2][i & 3] = 0.f;
#pragma unroll
            for (int s = 0; s < 8; s++) {
                uint32_t a[4];
                ldsm4(a, base + (s >> 2) * 16384 + (((2 * (s & 3) + (lane >> 4)) ^ (lane & 7)) * 16));
                mma16816(d[s & 1], a, Q[2 * s], Q[2 * s + 1]);
            }
            const int c = (n - BS_WUK) * 128 + warp * 16 + g + 8 * (t >> 1);
            qa[(2 * (t & 1)) * 512 + c] = (t & 2) ? d[0][2] + d[1][2] : d[0][0] + d[1][0];
            qa[(2 * (t & 1) + 1) * 512 + c] = (t & 2) ? d[0][3] + d[1][3] : d[0][1] + d[1][1];
            __syncthreads();
            if (tid == 0) b_issue(p, n + BD, bi, sbase, pol);
        }
#pragma unroll 1
        for (int r = 0; r < 2; r++) {
            const int id = tid + r * 256;
            const int b = id >> 7, c0 = ((id >> 2) & 31) * 16 + (id & 3) * 2;
            const float2 u0 = *reinterpret_cast<const float2*>(qa + b * 512 + c0);
            const float2 u1 = *reinterpret_cast<const float2*>(qa + b * 512 + c0 + 8);
            const uint32_t h0 = pack_bf16(u0.x, u0.y), h1 = pack_bf16(u1.x, u1.y);
            const uint32_t l0 = pack_bf16(u0.x - bf_lo(h0), u0.y - bf_hi(h0)), l1 = pack_bf16(u1.x - bf_lo(h1), u1.y - bf_hi(h1));
            g_qabs[((id >> 2) * 4 + (bi >> 3)) * 32 + (bi & 7) * 4 + (id & 3)] = make_uint4(h0, l0, h1, l1);
        }
    }
    b_exchange(&ctl[C_BBAR][0], BS_Q, &g_qabs[(bi >> 3) * 4096], sbase, pol);
    {
        uint32_t qf[4][4][4];
        b_wait(BS_Q + (warp >> 2), sbase);
        TS(7);
        {
            const uint4* qs = reinterpret_cast<const uint4*>(smem + ((BS_Q + (warp >> 2)) % BRING) * SLOT) + (warp & 3) * 512 + lane;
#pragma unroll
            for (int s = 0; s < 4; s++)
#pragma unroll
                for (int i = 0; i < 4; i++) {
                    const uint4 v = qs[(s * 4 + i) * 32];
                    qf[i][s][0] = v.x; qf[i][s][1] = v.y; qf[i][s][2] = v.z; qf[i][s][3] = v.w;
                }
        }
        __syncthreads();
        if (tid == 0) { b_issue(p, BS_Q + BD, bi, sbase, pol); b_issue(p, BS_Q + 1 + BD, bi, sbase, pol); }
        float acc[2][8][4];
#pragma unroll
        for (int i = 0; i < 2; i++)
#pragma unroll
            for (int j = 0; j < 8; j++) { acc[i][j][0] = acc[i][j][1] = acc[i][j][2] = acc[i][j][3] = 0.f; }
        float mrun = -INFINITY, lrun = 0.f;
        const int head = tid >> 3, kq = tid & 7;
        float* alpha = reinterpret_cast<float*>(smem + M_ALPHA);
        for (int n = BS_CKV; n < BS_PART; n++) {
            b_wait(n, sbase);
            const uint32_t slot = sbase + (n % BRING) * SLOT;
            float sc[4][4][4];
#pragma unroll
            for (int i = 0; i < 4; i++)
#pragma unroll
                for (int j = 0; j < 4; j++) { sc[i][j][0] = sc[i][j][1] = sc[i][j][2] = sc[i][j][3] = 0.f; }
#pragma unroll
            for (int j = 0; j < 4; j++)
#pragma unroll
                for (int sp = 0; sp < 2; sp++) {
                    uint32_t bf[4];
                    ldsm4(bf, slot + warp * 4096 + (8 * j + (lane & 7)) * 128 + (((4 * sp + (lane >> 3)) ^ (lane & 7)) * 16));
#pragma unroll
                    for (int i = 0; i < 4; i++) {
                        mma16816(sc[i][j], qf[i][2 * sp], bf[0], bf[1]);
                        mma16816(sc[i][j], qf[i][2 * sp + 1], bf[2], bf[3]);
                    }
                }
#pragma unroll
            for (int i = 0; i < 4; i++)
#pragma unroll
                for (int j = 0; j < 4; j++)
                    *reinterpret_cast<float2*>(red + warp * 1024 + (8 * i + g) * 32 + ((8 * j) ^ (8 * (g & 3))) + 2 * t) =
                        make_float2(sc[i][j][0] + sc[i][j][2], sc[i][j][1] + sc[i][j][3]);
            __syncthreads();
            if (tid == 0 && n > BS_CKV) b_issue(p, n - 1 + BD, bi, sbase, pol);
            {
                float4 s = make_float4(0.f, 0.f, 0.f, 0.f);
#pragma unroll
                for (int w = 0; w < 8; w++) {
                    const float4 v = *reinterpret_cast<const float4*>(red + w * 1024 + head * 32 + ((4 * kq) ^ (8 * (head & 3))));
                    s.x += v.x; s.y += v.y; s.z += v.z; s.w += v.w;
                }
                const uint32_t r0 = pack_bf16(s.x, s.y), r1 = pack_bf16(s.z, s.w);
                const uint32_t s0 = pack_bf16(bf_lo(r0) * SCALE, bf_hi(r0) * SCALE);
                const uint32_t s1 = pack_bf16(bf_lo(r1) * SCALE, bf_hi(r1) * SCALE);
                const float f0 = bf_lo(s0), f1 = bf_hi(s0), f2 = bf_lo(s1), f3 = bf_hi(s1);
                float mx = fmaxf(fmaxf(f0, f1), fmaxf(f2, f3));
                mx = fmaxf(mx, __shfl_xor_sync(~0u, mx, 1));
                mx = fmaxf(mx, __shfl_xor_sync(~0u, mx, 2));
                mx = fmaxf(mx, __shfl_xor_sync(~0u, mx, 4));
                const float mnew = fmaxf(mrun, mx);
                const float al = expsub(mrun, mnew);
                const float p0 = expsub(f0, mnew), p1 = expsub(f1, mnew), p2 = expsub(f2, mnew), p3 = expsub(f3, mnew);
                lrun = lrun * al + ((p0 + p1) + (p2 + p3));
                mrun = mnew;
                *reinterpret_cast<uint2*>(smem + M_P + head * 80 + kq * 8) = make_uint2(pack_bf16(p0, p1), pack_bf16(p2, p3));
                if (kq == 0) alpha[head] = al;
            }
            __syncthreads();
            {
                uint32_t pf[2][2][4];
#pragma unroll
                for (int i = 0; i < 2; i++)
#pragma unroll
                    for (int ks = 0; ks < 2; ks++)
                        ldsm4(pf[i][ks], sbase + M_P + (16 * i + (lane & 15)) * 80 + (16 * ks + 8 * (lane >> 4)) * 2);
#pragma unroll
                for (int i = 0; i < 2; i++) {
                    const float a0 = alpha[16 * i + g], a1 = alpha[16 * i + 8 + g];
#pragma unroll
                    for (int j = 0; j < 8; j++) { acc[i][j][0] *= a0; acc[i][j][1] *= a0; acc[i][j][2] *= a1; acc[i][j][3] *= a1; }
                }
#pragma unroll
                for (int j = 0; j < 8; j++) {
                    uint32_t bf[4];
                    ldsm4t(bf, slot + warp * 4096 + lane * 128 + ((j ^ (lane & 7)) * 16));
#pragma unroll
                    for (int i = 0; i < 2; i++) {
                        mma16816(acc[i][j], pf[i][0], bf[0], bf[1]);
                        mma16816(acc[i][j], pf[i][1], bf[2], bf[3]);
                    }
                }
            }
        }
        __syncthreads();
        if (tid == 0) b_issue(p, BS_PART - 1 + BD, bi, sbase, pol);
        lrun += __shfl_xor_sync(~0u, lrun, 1);
        lrun += __shfl_xor_sync(~0u, lrun, 2);
        lrun += __shfl_xor_sync(~0u, lrun, 4);
        if (kq == 0) g_bml[head * NBCTA + bi] = make_float2(mrun, lrun);
#pragma unroll
        for (int i = 0; i < 2; i++)
#pragma unroll
            for (int j = 0; j < 8; j++) {
                g_bpart[((16 * i + g) * NBCTA + bi) * 256 + warp * 32 + j * 4 + t] = make_float2(acc[i][j][0], acc[i][j][1]);
                g_bpart[((16 * i + 8 + g) * NBCTA + bi) * 256 + warp * 32 + j * 4 + t] = make_float2(acc[i][j][2], acc[i][j][3]);
            }
    }
#pragma unroll 1
    for (int i = tid; i < NH * 36 && !(CLU); i += 256) g_outb[bi * NH * 36 + i] = make_uint4(0u, epoch, 0u, epoch);
    b_exchange(&ctl[C_BBAR + 1][0], BS_PART, &g_bpart[bi * NBCTA * 256], sbase, pol);
    {
        float* omega = reinterpret_cast<float*>(smem + M_OMEGA);
        if (warp == 0) {
            __syncwarp();
            const uint2 ml = ld_relaxed8(&g_bml[bi * NBCTA + lane]);
            const float ms = __uint_as_float(ml.x);
            float m = ms;
            m = fmaxf(m, __shfl_xor_sync(~0u, m, 1));
            m = fmaxf(m, __shfl_xor_sync(~0u, m, 2));
            m = fmaxf(m, __shfl_xor_sync(~0u, m, 4));
            const float w = expsub(ms, m);
            float l = w * __uint_as_float(ml.y);
            l += __shfl_xor_sync(~0u, l, 1);
            l += __shfl_xor_sync(~0u, l, 2);
            l += __shfl_xor_sync(~0u, l, 4);
            omega[lane] = w / l;
        }
        __syncthreads();
        b_wait(BS_PART, sbase);
        b_wait(BS_PART + 1, sbase);
#pragma unroll 1
        for (int b = 0; b < 4; b++) {
            const float2* ps = reinterpret_cast<const float2*>(smem + ((BS_PART + (b >> 1)) % BRING) * SLOT) + (b & 1) * 2048 + tid;
            float c0 = 0.f, c1 = 0.f;
#pragma unroll
            for (int s = 0; s < 8; s++) {
                const float w = omega[b * 8 + s];
                const float2 v = ps[s * 256];
                c0 = fmaf(w, v.x, c0);
                c1 = fmaf(w, v.y, c1);
            }
            const uint32_t hi = pack_bf16(c0, c1);
            *reinterpret_cast<uint32_t*>(smem + M_CH + b * CP + tid * 4) = hi;
            *reinterpret_cast<uint32_t*>(smem + M_CL + b * CP + tid * 4) = pack_bf16(c0 - bf_lo(hi), c1 - bf_hi(hi));
        }
        __syncthreads();
        if (tid == 0) { b_issue(p, BS_PART + BD, bi, sbase, pol); b_issue(p, BS_PART + 1 + BD, bi, sbase, pol); }
    }
    b_gemm(p, sbase, BS_WUV, BS_END, 512, sbase + M_CH, sbase + M_CL, CP, bi, pol);
    TS(12);
    if (CLU) {
        if (tid < 128) {
            const uint32_t xo = sbase + M_QB + ((tid >> 1) & 3) * QP + (tid >> 3) * 16 + (tid & 1) * 8;
            st_tagged2(&g_ctx[bi * 128 + tid], __uint_as_float(lds32(xo)), __uint_as_float(lds32(xo + 4)), epoch + 1);
        }
        return;
    }
    if (tid == 0) {
#pragma unroll 1
        for (int i = 0; i < 4; i++) {
            mbar_expect_tx(sbase + M_BAR + i * 8, 36864);
            tma3d(sbase + i * 36864, &p.tm_wo, 0, bi * 128 + i * 32, 0, sbase + M_BAR + i * 8, pol);
        }
    }
    TS(8);
    {
        float acc[9][4];
#pragma unroll
        for (int j = 0; j < 9; j++) { acc[j][0] = acc[j][1] = acc[j][2] = acc[j][3] = 0.f; }
#pragma unroll 1
        for (int i = 0; i < 4; i++) {
            const uint32_t xo = sbase + M_QB + (g & 3) * QP + i * 64 + t * 4;
            const uint32_t a0[4] = {lds32(xo), 0u, lds32(xo + 16), 0u}, a1[4] = {lds32(xo + 32), 0u, lds32(xo + 48), 0u};
            mbar_wait(sbase + M_BAR + i * 8, 0);
#pragma unroll
            for (int j = 0; j < 9; j++) {
                const int nt = warp * 9 + j;
                uint32_t w[4];
                ldsm4t(w, sbase + i * 36864 + (nt >> 3) * 4096 + lane * 128 + (((nt & 7) ^ (lane & 7)) * 16));
                mma16816(acc[j], a0, w[0], w[1]);
                mma16816(acc[j], a1, w[2], w[3]);
            }
        }
        if (g < 4) {
#pragma unroll
            for (int j = 0; j < 9; j++) {
                const int c2 = (warp * 9 + j) * 4 + t;
                st_tagged2(&g_outb[((c2 / 9) * NH + bi) * 36 + g * 9 + c2 % 9], acc[j][0], acc[j][1], epoch + 1);
            }
        }
    }
    TS(9);
    {
        const uint4* src = g_outb + (bi * NH + (tid >> 3)) * 36 + (tid & 7);
        float2* part = reinterpret_cast<float2*>(red);
        unsigned n = 0;
        while (true) {
            ulonglong2 v[5];
            bool ok = true;
#pragma unroll
            for (int i = 0; i < 5; i++)
                if (i < 4 || (tid & 7) < 4) v[i] = ld_tagged2(src + i * 8);
#pragma unroll
            for (int i = 0; i < 5; i++)
                if (i < 4 || (tid & 7) < 4) {
                    ok = ok && (unsigned)(v[i].x >> 32) == epoch + 1 && (unsigned)(v[i].y >> 32) == epoch + 1;
                    part[(tid >> 3) * 36 + (tid & 7) + i * 8] = make_float2(__uint_as_float((unsigned)v[i].x), __uint_as_float((unsigned)v[i].y));
                }
            if (ok) break;
            __nanosleep(400);
            if (++n > SPIN_LIMIT) __trap();
        }
        __syncthreads();
        if (tid < 36) {
            float s0 = 0.f, s1 = 0.f;
#pragma unroll 8
            for (int h = 0; h < NH; h++) { const float2 v = part[h * 36 + tid]; s0 += v.x; s1 += v.y; }
            *reinterpret_cast<uint32_t*>(p.out + (tid / 9) * 2 * DM + DM + bi * 18 + (tid % 9) * 2) = pack_bf16(s0, s1);
        }
    }
    TS(10);
}

template <bool CLU>
__global__ void __launch_bounds__(256, 1) fused_decode_kernel(const __grid_constant__ First f, const __grid_constant__ Params p) {
    extern __shared__ __align__(1024) char smem_raw[];
    const uint32_t sbase = (smem_u32(smem_raw) + 1023u) & ~1023u;
    char* smem = smem_raw + (sbase - smem_u32(smem_raw));
    const int tid = threadIdx.x, warp = tid >> 5, lane = tid & 31;
    asm volatile("{\n.reg .pred p;\nsetp.ne.u32 p, %1, 0;\n@p prefetch.global.L2 [%0];\n}"
                 ::"l"(f.ptr[tid >> 10] + (blockIdx.x * 8 + warp) * 2048 + lane * 128), "r"((uint32_t)(lane < 16)) : "memory");
    const char* eptr = f.ptr[3 + (tid >> 10)];
    const int blk = CLU ? cluster_role(blockIdx.x) : blockIdx.x;
    const bool isB = CLU ? blk < NBCTA : (blk & 3) == 0 && (blk >> 2) < NBCTA;
    const int bi = CLU ? blk : blk >> 2;
    const int nb = CLU ? blk - NBCTA : blk - min(NBCTA, (blk + 3) >> 2);
    const int nblk = CLU ? 8 * MINCL : gridDim.x, nnb = nblk - NBCTA;
    constexpr int NFIRST = NW + XW + CLU;
    const int nstatic = nnb * NFIRST;
    uint64_t pol, poln;
    asm volatile("createpolicy.fractional.L2::evict_first.b64 %0, 1.0;" : "=l"(pol));
    asm volatile("createpolicy.fractional.L2::evict_normal.b64 %0, 1.0;" : "=l"(poln));
    const bool hold = blk < 16;
    const uint32_t jbar = sbase + M_BAR + (NSLOT + BRING) * 8, fbar = sbase + M_BAR + 4 * 8;
    const bool kfirst = CLU && !isB && !(nb & 4);
    if (warp < 4) {
        if (lane == 0) {
            if (warp == 0) {
                mbar_init(jbar, 1);
                asm volatile("fence.mbarrier_init.release.cluster;" ::: "memory");
                mbar_expect_tx(jbar, 36864 + 4 * 1152);
                if ((CLU || blk < 128) && !kfirst) tma3d(sbase + J0W, &p.tm_j0, blk * 32, 0, 0, jbar, poln);
            } else if (warp & 1) {
                if (warp & 2) {
#pragma unroll
                    for (int i = 0; i < NSLOT + BRING; i++) mbar_init(sbase + M_BAR + i * 8, 1);
                    mbar_expect_tx(fbar, NEARLY * TILE_BYTES);
                } else if (CLU && !isB) {
                    mbar_init(sbase + F_BAR, 1);
                    mbar_expect_tx(sbase + F_BAR, 2048);
                }
                asm volatile("fence.mbarrier_init.release.cluster;" ::: "memory");
            } else {
#pragma unroll
                for (int i = 0; i < 4; i++) asm volatile("st.shared.v4.u32 [%0], {%1,%1,%1,%1};" ::"r"(sbase + M_HELP + i * 16), "r"(0) : "memory");
            }
        }
    } else if (blockIdx.x >= NFIN) {
        if (tid == 128) {
            asm volatile("prefetch.tensormap [%0];" ::"l"(&p.tm_j0) : "memory");
            asm volatile("prefetch.tensormap [%0];" ::"l"(&p.tm_wq) : "memory");
        } else if (blockIdx.x == NFIN + 4 && tid >= 220) {
            asm volatile("prefetch.global.L2 [%0];" ::"l"(f.ptr[2 + (tid >> 10)] + (tid - 220) * 128) : "memory");
        }
    }
    __syncthreads();
    if (tid == 128) {
        if ((CLU || blk < 128) && !kfirst) bulk_load(sbase + M_XA, f.ptr[2], 4608, jbar, poln);
        if (!isB && !hold) bulk_load(sbase, block_src(f.ptr[1], unit_block(nb * NEARLY)), NEARLY * TILE_BYTES, fbar, pol);
        if (kfirst) {
            tma3d(sbase + J0W, &p.tm_j0, blk * 32, 0, 0, jbar, poln);
            bulk_load(sbase + M_XA, f.ptr[2], 4608, jbar, poln);
        }
    }
    const uint32_t wbar = sbase + M_BAR + warp * 8, wslot = sbase + warp * SLOT;
    const int u0 = ((warp / NEARLY) * nnb + nb) * NEARLY + warp % NEARLY;
    unsigned epoch = 0;
    if (lane == 0) epoch = ld_relaxed4(eptr);
    TS(0);
    if (CLU && (unsigned)nb < NFIN) asm volatile("barrier.cluster.arrive.relaxed.aligned;" ::: "memory");
    if ((warp >> 1) == 2 && blk < 128) st_relaxed64(&g_qll[((tid - 128) >> 4) * 2048 + blk * 16 + (tid & 15)], 0ull);
    if (isB || warp >= NW + XW) epoch = __shfl_sync(~0u, epoch, 0);
    if (isB && tid == 96) {
        if (hold) { unsigned n = 0; while (ld_acquire_cta_shared(sbase + M_HELP + 24) < 2) { if (++n > (SPIN_LIMIT << 4)) __trap(); } }
#pragma unroll 1
        for (int b = 0; b < 4; b++) bulk_load(sbase + M_XB + b * XP, p.xb + b * DM, 1152, sbase + M_BAR + NSLOT * 8, pol);
#pragma unroll 1
        for (int n = 0; n < BD; n++) b_issue(p, n, bi, sbase, pol);
    }
    if (warp >= 4 && blk < 128) {
        const int g = lane >> 2, t = lane & 3, j = tid - 128;
#pragma unroll 1
        for (int sl = blk, ph = 0;; sl += 128 - nblk, ph = 1) {
        mbar_wait(jbar, ph);
        TS(13);
        float acc[4][4];
#pragma unroll
        for (int i = 0; i < 16; i++) acc[i >> 2][i & 3] = 0.f;
        const uint32_t wa = sbase + J0W + ((warp - 4) * 144 + (lane & 15)) * 64;
        const uint32_t sw = (lane >> 1) & 3, xa = sbase + M_XA + (g & 3) * 1152 + (warp - 4) * 288 + t * 4;
#pragma unroll 3
        for (int s = 0; s < 9; s++) {
            const uint32_t a[4] = {lds32(xa + s * 32), 0u, lds32(xa + s * 32 + 16), 0u};
            uint32_t w0[4], w1[4];
            ldsm4t(w0, wa + s * 1024 + (((lane >> 4) ^ sw) * 16));
            ldsm4t(w1, wa + s * 1024 + (((2 + (lane >> 4)) ^ sw) * 16));
            mma16816(acc[0], a, w0[0], w0[1]);
            mma16816(acc[1], a, w0[2], w0[3]);
            mma16816(acc[2], a, w1[0], w1[1]);
            mma16816(acc[3], a, w1[2], w1[3]);
        }
        float2* j0 = reinterpret_cast<float2*>(smem + M_J0);
        if (g < 4) {
#pragma unroll
            for (int i = 0; i < 4; i++) j0[(warp - 4) * 64 + g * 16 + i * 4 + t] = make_float2(acc[i][0], acc[i][1]);
        }
        asm volatile("bar.sync 1, 128;" ::: "memory");
        const bool again = sl == blk && blk + 128 - nblk >= nblk;
        if (again && tid == 224) {
            mbar_expect_tx(jbar, 36864);
            tma3d(sbase + J0W, &p.tm_j0, (blk + 128 - nblk) * 32, 0, 0, jbar, pol);
        }
        if (warp < 6) {
            const float2 v0 = j0[j], v1 = j0[64 + j], v2 = j0[128 + j], v3 = j0[192 + j];
            st_relaxed64(&g_qll[(j >> 4) * 2048 + sl * 16 + (j & 15)],
                         (unsigned long long)pack_bf16((v0.x + v1.x) + (v2.x + v3.x), (v0.y + v1.y) + (v2.y + v3.y)) |
                             ((unsigned long long)(epoch + 1) << 32));
            __syncwarp();
            if (lane == 0) asm volatile("red.relaxed.cta.shared::cta.add.u32 [%0], 1;" ::"r"(sbase + M_HELP + 24) : "memory");
        } else if (warp == 7) {
            if (blk < C_LINES) g_ctl[(epoch & 1) ^ 1][blk][lane] = 0;
        }
        TS(1);
        if (!again) break;
        asm volatile("bar.sync 1, 128;" ::: "memory");
        }
    }
    if (isB) {
        b_chain<CLU>(p, smem, sbase, bi, epoch, pol);
        return;
    }
    if (warp < NW + XW) {
        a_worker<CLU>(p, u0, CLU && warp == 3 ? 4 * nnb + nb : 2 * NUK, warp >= NW + (((nb * 5) & 7) < (CLU ? X3C : X3) ? 1 : 0), hold, nstatic,
                      wslot, wbar, warp < NEARLY && !hold ? fbar : wbar, sbase + M_HELP, epoch, pol);
        if (CLU && nb < NFIN) {
            if (tid == 96) out_issue(p, sbase, nb >> 3, nb & 7, pol);
            __syncwarp();
            if (warp & 1) out_final(p, sbase, nb >> 3, nb & 7, warp >> 1);
            else if (warp == 0) out_late(sbase, nb & 7);
        }
        return;
    } else if (warp == 7) {
#pragma unroll 1
        for (int i = nb; i < 4 * NH; i += nnb) g_oacc[i * 32 + lane] = make_float4(0.f, 0.f, 0.f, 0.f);
        if (nb < NREP * NH) g_vdone[nb][lane] = 0;
        __syncwarp();
        k_helper(sbase + M_HELP, epoch);
        if (nb == 0 && lane == 0) g_epoch = epoch + 1;
        __syncwarp();
        if (CLU && nb < NFIN) out_early(sbase, nb & 7, epoch + 1);
    } else if (CLU) {
    } else if (warp == 6 && nb < NFIN) {
        finisher(p, sbase, nb);
        TS(4);
    } else if (warp >= 6 - NPOLL && nb < NFIN) {
        v_poller(sbase, nb, warp - (6 - NPOLL));
    }
    if (CLU && nb < NFIN) out_project(sbase, nb & 7, warp - 4);
}

}

typedef CUresult (*EncodeFn)(CUtensorMap*, CUtensorMapDataType, cuuint32_t, void*, const cuuint64_t*, const cuuint64_t*,
                             const cuuint32_t*, const cuuint32_t*, CUtensorMapInterleave, CUtensorMapSwizzle,
                             CUtensorMapL2promotion, CUtensorMapFloatOOBfill);

extern "C" void kernel_launch(void* const* d_in, const int* in_sizes, int n_in, void* d_out, int out_size) {
    (void)in_sizes; (void)n_in; (void)out_size;
    static int nsm = 0, ncl = 0;
    static EncodeFn encode = nullptr;
    static const char* epoch_ptr = nullptr;
    cudaLaunchConfig_t cfg = {};
    cudaLaunchAttribute at[1];
    at[0].id = cudaLaunchAttributeClusterDimension;
    at[0].val.clusterDim.x = 8; at[0].val.clusterDim.y = 1; at[0].val.clusterDim.z = 1;
    cfg.blockDim = dim3(256); cfg.dynamicSmemBytes = SMEM_BYTES; cfg.stream = cudaStreamPerThread; cfg.attrs = at; cfg.numAttrs = 1;
    if (nsm == 0) {
        int dev = 0;
        cudaGetDevice(&dev);
        cudaDeviceGetAttribute(&nsm, cudaDevAttrMultiProcessorCount, dev);
        cudaFuncSetAttribute(fused_decode_kernel<false>, cudaFuncAttributeMaxDynamicSharedMemorySize, SMEM_BYTES);
        cudaFuncSetAttribute(fused_decode_kernel<true>, cudaFuncAttributeMaxDynamicSharedMemorySize, SMEM_BYTES);
        cfg.gridDim = dim3(128);
        if (cudaOccupancyMaxActiveClusters(&ncl, fused_decode_kernel<true>, &cfg) != cudaSuccess) { ncl = 0; (void)cudaGetLastError(); }
        if (ncl > MINCL) ncl = MINCL;
        cudaGetSymbolAddress((void**)&epoch_ptr, g_epoch);
        void* fn = nullptr;
        cudaDriverEntryPointQueryResult qr;
        cudaGetDriverEntryPoint("cuTensorMapEncodeTiled", &fn, cudaEnableDefault, &qr);
        encode = (EncodeFn)fn;
    }
    Params p;
    auto panels = [&](CUtensorMap* tm, void* ptr, int rows, int cols, int box_rows, int box_panels) {
        const cuuint64_t gd[3] = {64, (cuuint64_t)rows, (cuuint64_t)(cols / 64)}, gs[2] = {(cuuint64_t)cols * 2, 128};
        const cuuint32_t box[3] = {64, (cuuint32_t)box_rows, (cuuint32_t)box_panels}, es[3] = {1, 1, 1};
        encode(tm, CU_TENSOR_MAP_DATA_TYPE_BFLOAT16, 3, ptr, gd, gs, box, es, CU_TENSOR_MAP_INTERLEAVE_NONE,
               CU_TENSOR_MAP_SWIZZLE_128B, CU_TENSOR_MAP_L2_PROMOTION_L2_256B, CU_TENSOR_MAP_FLOAT_OOB_FILL_NONE);
    };
    panels(&p.tm_wq, d_in[7], DM, 4096, 128, 2);
    panels(&p.tm_wuk, d_in[8], 512, 4096, 128, 2);
    panels(&p.tm_wuv, d_in[9], 512, 4096, 128, 2);
    panels(&p.tm_wo, d_in[10], 4096, DM, 32, 9);
    panels(&p.tm_ckv, d_in[6], 4 * SK, 512, 32, 8);
    {
        const cuuint64_t gd[3] = {4096, 192, 3}, gs[2] = {8192, 192 * 8192};
        const cuuint32_t box[3] = {32, 192, 3}, es[3] = {1, 1, 1};
        encode(&p.tm_j0, CU_TENSOR_MAP_DATA_TYPE_BFLOAT16, 3, d_in[3], gd, gs, box, es, CU_TENSOR_MAP_INTERLEAVE_NONE,
               CU_TENSOR_MAP_SWIZZLE_64B, CU_TENSOR_MAP_L2_PROMOTION_L2_128B, CU_TENSOR_MAP_FLOAT_OOB_FILL_NONE);
    }
    for (int i = 0; i < 6; i++) {
        const int k = i >> 1, a = i & 1;
        const cuuint64_t gd[4] = {DM, 16, 8, NH}, gs[3] = {(cuuint64_t)(a ? 8 : 1) * DM * 2, (cuuint64_t)(a ? 1 : 16) * DM * 2, 128 * DM * 2};
        const cuuint32_t box[4] = {k < 2 ? 64u : 16u, 16, k ? 8u : 4u, k < 2 ? 1u : 2u}, es[4] = {1, 1, 1, 1};
        encode(&p.tm_out[k][a], CU_TENSOR_MAP_DATA_TYPE_BFLOAT16, 4, d_in[a ? 4 : 10], gd, gs, box, es, CU_TENSOR_MAP_INTERLEAVE_NONE,
               k < 2 ? CU_TENSOR_MAP_SWIZZLE_128B : CU_TENSOR_MAP_SWIZZLE_32B,
               k < 2 ? CU_TENSOR_MAP_L2_PROMOTION_L2_256B : CU_TENSOR_MAP_L2_PROMOTION_L2_128B, CU_TENSOR_MAP_FLOAT_OOB_FILL_NONE);
    }
    p.kc = (const __nv_bfloat16*)d_in[1];
    p.vc = (const __nv_bfloat16*)d_in[2];
    p.wo = (const __nv_bfloat16*)d_in[4];
    p.xb = (const __nv_bfloat16*)d_in[5];
    p.out = (__nv_bfloat16*)d_out;
    const First f = {{(const char*)d_in[3], (const char*)d_in[1], (const char*)d_in[0], epoch_ptr}};
    if (ncl >= MINCL) {
        cfg.gridDim = dim3(8 * ncl);
        cudaLaunchKernelEx(&cfg, fused_decode_kernel<true>, f, p);
    } else {
        fused_decode_kernel<false><<<nsm, 256, SMEM_BYTES, cudaStreamPerThread>>>(f, p);
    }
}
```
